```python
import torch

def _softmax(x, axis=-1):
    return torch.softmax(x, dim=axis)

def _gelu(x):
    return torch.nn.functional.gelu(x, approximate='tanh')

def _silu(x):
    return torch.nn.functional.silu(x)

def _sigmoid(x):
    return torch.sigmoid(x)

def _layernorm(x, axis=-1, eps=1e-05):
    m = x.mean(dim=axis, keepdim=True)
    v = x.var(dim=axis, keepdim=True, unbiased=False)
    return (x - m) / torch.sqrt(v + eps)

def _scatter_add(tgt, idx, src, axis=0):
    return tgt.clone().index_add_(axis, idx, src)

def _segment_sum(src, seg, n):
    out = torch.zeros((n,) + src.shape[1:], dtype=src.dtype)
    return out.index_add_(0, seg, src)

def _pad(x, pw):
    flat = tuple((v for pair in reversed(pw) for v in pair))
    return torch.nn.functional.pad(x, flat)
kernel_name = 'adaLN_cond__linear_kernel_hedgehog__moe_arch_mod__prompt'

def setup_inputs():

    _w = lambda a: (lambda t: t.to(torch.bfloat16) if t.is_floating_point() else t)(torch.as_tensor(a))

    def _A_setup():
        B, S, D, H = (1, 2048, 1024, 32)
        Dh = D // H
        return {'x': _w((lambda *s: torch.randn(*s, dtype=torch.bfloat16) * 0.05)(B, S, D)), 'wqkv': _w((lambda *s: torch.randn(*s, dtype=torch.bfloat16) * 0.4)(D, 3 * D)), 'w_phi': _w((lambda *s: torch.randn(*s, dtype=torch.bfloat16) * 0.4)(H, Dh, Dh) * Dh ** (-0.5)), 'wo': _w((lambda *s: torch.randn(*s, dtype=torch.bfloat16) * 0.05)(D, D))}
    _A_in = _A_setup()

    def _B_setup():
        B, S, D, F, C = (1, 2048, 1024, 3584, 2)
        return {'x': _w((lambda *s: torch.randn(*s, dtype=torch.bfloat16) * 0.05)(B, S, D)), 'w_r': _w((lambda *s: torch.randn(*s, dtype=torch.bfloat16) * 0.1)(D)), 'w_gate': _w((lambda *s: torch.randn(*s, dtype=torch.bfloat16) * 0.05)(D, F)), 'w_up': _w((lambda *s: torch.randn(*s, dtype=torch.bfloat16) * 0.05)(D, F)), 'w_down': _w((lambda *s: torch.randn(*s, dtype=torch.bfloat16) * 0.05)(F, D))}
    _B_in = _B_setup()
    return {'A_x': _A_in['x'], 'A_wqkv': _A_in['wqkv'], 'A_w_phi': _A_in['w_phi'], 'A_wo': _A_in['wo'], 'B_x': _B_in['x'], 'B_w_r': _B_in['w_r'], 'B_w_gate': _B_in['w_gate'], 'B_w_up': _B_in['w_up'], 'B_w_down': _B_in['w_down'], 'c': _w((lambda *s: torch.randn(*s, dtype=torch.bfloat16) * 0.2)(1, 1024) * 8.0), 'w_mod': _w((lambda *s: torch.randn(*s, dtype=torch.bfloat16) * 0.2)(1024, 6 * 1024) * 1024 ** (-0.5) * 8.0)}

def reference(A_x, A_wqkv, A_w_phi, A_wo, B_x, B_w_r, B_w_gate, B_w_up, B_w_down, c, w_mod):

    def _A_ref(x, wqkv, w_phi, wo):
        B, S, D = x.shape
        H = 32
        Dh = D // H
        qkv = (lambda x, *d: x.permute(*d))((x @ wqkv).reshape(B, S, 3, H, Dh), 2, 0, 3, 1, 4)
        q, k, v = (qkv[0], qkv[1], qkv[2])
        pq = torch.einsum('bhsd,hdf->bhsf', q, w_phi)
        pk = torch.einsum('bhsd,hdf->bhsf', k, w_phi)
        phi_q = torch.concatenate([_softmax(pq, axis=-1), _softmax(-pq, axis=-1)], axis=-1)
        phi_k = torch.concatenate([_softmax(pk, axis=-1), _softmax(-pk, axis=-1)], axis=-1)
        kv = torch.einsum('bhsf,bhsd->bhfd', phi_k, v)
        z = torch.einsum('bhsf->bhf', phi_k)
        num = torch.einsum('bhqf,bhfd->bhqd', phi_q, kv)
        den = torch.einsum('bhqf,bhf->bhq', phi_q, z)[..., None] + 1e-06
        o = num / den
        return (lambda x, *d: x.permute(*d))(o, 0, 2, 1, 3).reshape(B, S, D) @ wo

    def _B_ref(x, w_r, w_gate, w_up, w_down):
        B, S, D = x.shape
        C = 2
        r = x @ w_r
        idx = torch.argsort(-r, axis=-1)[:, :C]
        idx_e = (lambda x, n, axis: torch.repeat_interleave(x, n, dim=axis))(idx.reshape(B, C, 1), D, axis=2)
        x_sel = (lambda x, i, axis: torch.take_along_dim(x, i, dim=axis))(x, idx_e, axis=1)
        g = _silu(x_sel @ w_gate)
        u = x_sel @ w_up
        y = g * u @ w_down
        r_sel = _sigmoid((lambda x, i, axis: torch.take_along_dim(x, i, dim=axis))(r, idx, axis=1))
        y = y * r_sel.reshape(B, C, 1)
        b_off = (torch.arange(B) * S).reshape(B, 1)
        flat_idx = (idx + b_off).reshape(B * C)
        zero = (x * 0.0).reshape(B * S, D)
        upd = _scatter_add(zero, flat_idx, y.reshape(B * C, D), axis=0)
        return x + upd.reshape(B, S, D)
    x = A_x
    mod = (_silu(c) @ w_mod).reshape(c.shape[0], 6, 1, -1)
    sa, ca, ga, sb, cb, gb = (mod[:, 0].clone(), mod[:, 1].clone(), mod[:, 2].clone(), mod[:, 3].clone(), mod[:, 4].clone(), mod[:, 5].clone())
    h = _layernorm(x, axis=-1) * (1 + ca) + sa
    x = x + ga * _A_ref(h, A_wqkv, A_w_phi, A_wo)
    h = _layernorm(x, axis=-1) * (1 + cb) + sb
    x = x + gb * _B_ref(h, B_w_r, B_w_gate, B_w_up, B_w_down)
    return x
```

```cpp
#include <cuda_runtime.h>
#include <cuda.h>
#include <cuda_bf16.h>
#include <stdint.h>

namespace {

typedef __nv_bfloat16 bf16;

constexpr int NTHREADS = 384;
constexpr int POLL_MAX = 400000;

constexpr uint32_t OFF_R0   = 0;
constexpr uint32_t OFF_A    = 65536;
constexpr uint32_t OFF_B    = 114688;
constexpr uint32_t OFF_V    = 65536;
constexpr uint32_t OFF_PHI  = 98304;
constexpr uint32_t OFF_F2   = 65536;
constexpr uint32_t OFF_DB   = 131072;
constexpr uint32_t OFF_KS   = 196608;
constexpr uint32_t OFF_WPHI = 214016;
constexpr uint32_t OFF_KVT  = OFF_WPHI;
constexpr uint32_t OFF_Z    = 222208;
constexpr uint32_t OFF_TAB  = OFF_Z;
constexpr uint32_t OFF_ONES = 226304;
constexpr uint32_t OFF_BAR  = 227328;
constexpr uint32_t OFF_PFL  = OFF_BAR + 512;
constexpr uint32_t OFF_CST  = OFF_PFL + 576;
constexpr uint32_t OFF_T1   = OFF_CST + 64;
constexpr uint32_t OFF_T2   = OFF_T1 + 512;
constexpr uint32_t OFF_T3   = OFF_T2 + 512;
constexpr uint32_t OFF_KEY  = OFF_T3 + 256;
constexpr uint32_t OFF_ST2  = OFF_KEY + 512;
constexpr uint32_t OFF_SILU = OFF_ST2;
constexpr uint32_t SMEM_BYTES = 232448;
constexpr uint32_t OFF_OUT  = OFF_R0 + 32768;
constexpr uint32_t OFF_HSEL = OFF_KS;
constexpr uint32_t OFF_RED  = OFF_KS + 4096;
constexpr uint32_t OFF_RED2 = OFF_RED + 2048;
static_assert(OFF_ST2 + 2048 <= SMEM_BYTES, "layout");

enum {
    B_FA = 0  , B_WPHI = 3, B_FB = 4  , B_KSD = 8, B_KVL = 9  , B_OST = 11, B_GF = 12, B_WD = 13, B_PAR = 14, B_CAND = 15,
    B_FD = 16  , B_UF = 20,
    B_EA = 24  , B_QE = 27, B_EB = 28  , B_ED = 32  , B_KST = 36  , B_VF = 38, B_KVC = 39, B_OWN = 40  ,
    B_STP = 42, B_KEYS = 43, B_SWP = 44, B_STS = 45,
    B_XP = 48
};

struct Scratch {
    uint4 os[16 * 16 * 1024];
    uint4 kvacc[8 * 4 * 528];
    uint4 llstat[2048];
    uint4 llm1[16 * 64];
    uint4 flk[3 * 128 * 2];
    uint4 flo[16 * 16 * 2];
    uint4 llmod2[4 * 256];
    uint4 llln2[16 * 8 * 128];
    uint4 llcand[16 * 2];
    uint4 llrowh[32 * 256];
    uint4 llrowx[32 * 256];
    uint4 lly[112 * 512];
    unsigned done[4];
};
__device__ __align__(1024) Scratch g_scratch;
#define TS(i) do {} while (0)
#define TR(i) do {} while (0)

__device__ __forceinline__ uint32_t smem_u32(const void* p) { return (uint32_t)__cvta_generic_to_shared(p); }
__device__ __forceinline__ uint32_t clk32() { uint32_t c; asm volatile("mov.u32 %0, %%clock;" : "=r"(c) :: "memory"); return c; }
__device__ __forceinline__ void spin_until(uint32_t t) { while ((int)(clk32() - t) < 0) {} }
__device__ __forceinline__ void mbar_init(uint32_t bar, uint32_t cnt) { asm volatile("mbarrier.init.shared::cta.b64 [%0], %1;" :: "r"(bar), "r"(cnt) : "memory"); }
__device__ __forceinline__ void mbar_init_fence() { asm volatile("fence.mbarrier_init.release.cluster;" ::: "memory"); }
__device__ __forceinline__ void mbar_arrive_tx(uint32_t bar, uint32_t bytes) { asm volatile("mbarrier.arrive.expect_tx.shared::cta.b64 _, [%0], %1;" :: "r"(bar), "r"(bytes) : "memory"); }
__device__ __forceinline__ void mbar_expect_tx(uint32_t bar, uint32_t bytes) { asm volatile("mbarrier.expect_tx.relaxed.cta.shared::cta.b64 [%0], %1;" :: "r"(bar), "r"(bytes) : "memory"); }
__device__ __forceinline__ void mbar_arrive(uint32_t bar) { asm volatile("mbarrier.arrive.shared::cta.b64 _, [%0];" :: "r"(bar) : "memory"); }
__device__ __forceinline__ void mbar_wait(uint32_t bar, uint32_t parity) {
    asm volatile("{\n.reg .pred P1;\nLAB_WAIT:\nmbarrier.try_wait.parity.shared::cta.b64 P1, [%0], %1;\n@!P1 bra LAB_WAIT;\n}" :: "r"(bar), "r"(parity) : "memory");
}
__device__ __forceinline__ bool mbar_test(uint32_t bar, uint32_t parity) {
    uint32_t ok;
    asm volatile("{\n.reg .pred p;\nmbarrier.test_wait.parity.shared::cta.b64 p, [%1], %2;\nselp.u32 %0, 1, 0, p;\n}" : "=r"(ok) : "r"(bar), "r"(parity) : "memory");
    return ok;
}
__device__ __forceinline__ uint64_t policy_evict_first() { uint64_t p; asm("createpolicy.fractional.L2::evict_first.b64 %0, 1.0;" : "=l"(p)); return p; }
__device__ __forceinline__ void tma_load_ef(uint32_t dst, const CUtensorMap* tm, int c0, int c1, uint32_t bar) {
    asm volatile("cp.async.bulk.tensor.2d.shared::cluster.global.mbarrier::complete_tx::bytes.L2::cache_hint [%0], [%1, {%3, %4}], [%2], %5;"
        :: "r"(dst), "l"(tm), "r"(bar), "r"(c0), "r"(c1), "l"(policy_evict_first()) : "memory");
}
__device__ __forceinline__ void tma_load(uint32_t dst, const CUtensorMap* tm, int c0, int c1, uint32_t bar) {
    asm volatile("cp.async.bulk.tensor.2d.shared::cluster.global.mbarrier::complete_tx::bytes [%0], [%1, {%3, %4}], [%2];"
        :: "r"(dst), "l"(tm), "r"(bar), "r"(c0), "r"(c1) : "memory");
}
__device__ __forceinline__ void tma_load4(uint32_t dst, const CUtensorMap* tm, int row, int blk, uint32_t bar) {
    asm volatile("cp.async.bulk.tensor.4d.shared::cluster.global.mbarrier::complete_tx::bytes [%0], [%1, {0, %3, %4, 0}], [%2];"
        :: "r"(dst), "l"(tm), "r"(bar), "r"(row), "r"(blk) : "memory");
}
__device__ __forceinline__ void tma_store4(const CUtensorMap* tm, int row, int blk, uint32_t src) {
    asm volatile("cp.async.bulk.tensor.4d.global.shared::cta.bulk_group [%0, {0, %2, %3, 0}], [%1];" :: "l"(tm), "r"(src), "r"(row), "r"(blk) : "memory");
}
__device__ __forceinline__ void bulk_load(uint32_t dst, const void* src, uint32_t bytes, uint32_t bar) {
    asm volatile("cp.async.bulk.shared::cluster.global.mbarrier::complete_tx::bytes [%0], [%1], %2, [%3];" :: "r"(dst), "l"(src), "r"(bytes), "r"(bar) : "memory");
}
__device__ __forceinline__ void bulk_store(void* dst, uint32_t src, uint32_t bytes) {
    asm volatile("cp.async.bulk.global.shared::cta.bulk_group [%0], [%1], %2;" :: "l"(dst), "r"(src), "r"(bytes) : "memory");
}
__device__ __forceinline__ void bulk_reduce(void* dst, uint32_t src, uint32_t bytes) {
    asm volatile("cp.reduce.async.bulk.global.shared::cta.bulk_group.add.f32 [%0], [%1], %2;" :: "l"(dst), "r"(src), "r"(bytes) : "memory");
}
__device__ __forceinline__ void bulk_wait_read() { asm volatile("cp.async.bulk.commit_group;\ncp.async.bulk.wait_group.read 0;" ::: "memory"); }
__device__ __forceinline__ void bulk_wait() { asm volatile("cp.async.bulk.commit_group;\ncp.async.bulk.wait_group 0;" ::: "memory"); }
__device__ __forceinline__ void l2_prefetch(const void* p, uint32_t bytes) {
    asm volatile("cp.async.bulk.prefetch.L2.global [%0], %1;" :: "l"(p), "r"(bytes) : "memory");
}
__device__ __forceinline__ void tmap_prefetch(const CUtensorMap* tm) { asm volatile("prefetch.tensormap [%0];" :: "l"(tm) : "memory"); }
__device__ __forceinline__ void wg_fence() { asm volatile("wgmma.fence.sync.aligned;" ::: "memory"); }
__device__ __forceinline__ void wg_commit() { asm volatile("wgmma.commit_group.sync.aligned;" ::: "memory"); }
template<int N> __device__ __forceinline__ void wg_wait() { asm volatile("wgmma.wait_group.sync.aligned %0;" :: "n"(N) : "memory"); }
template<int N> __device__ __forceinline__ void acc_fence(float (&d)[N]) {
    #pragma unroll
    for (int i = 0; i < N; i++) asm volatile("" : "+f"(d[i]) :: "memory");
}
__device__ __forceinline__ uint32_t desc_lo(uint32_t addr, uint32_t lbo) { return (addr >> 4) | ((lbo >> 4) << 16); }
constexpr uint32_t H128 = 0x40000040u;
constexpr uint32_t H64 = 0x80000020u;
__device__ __forceinline__ void fence_async_smem() { asm volatile("fence.proxy.async.shared::cta;" ::: "memory"); }
__device__ __forceinline__ void bar_sync(int id, int n) { asm volatile("bar.sync %0, %1;" :: "r"(id), "r"(n) : "memory"); }
template<int R> __device__ __forceinline__ void reg_inc() { asm volatile("setmaxnreg.inc.sync.aligned.u32 %0;" :: "n"(R)); }
template<int R> __device__ __forceinline__ void reg_dec() { asm volatile("setmaxnreg.dec.sync.aligned.u32 %0;" :: "n"(R)); }

__device__ __forceinline__ void stsm4(uint32_t addr, uint32_t r0, uint32_t r1, uint32_t r2, uint32_t r3) {
    asm volatile("stmatrix.sync.aligned.m8n8.x4.shared.b16 [%0], {%1,%2,%3,%4};" :: "r"(addr), "r"(r0), "r"(r1), "r"(r2), "r"(r3) : "memory");
}
__device__ __forceinline__ void ldsm4(uint32_t* r, uint32_t addr) {
    asm volatile("ldmatrix.sync.aligned.m8n8.x4.shared.b16 {%0,%1,%2,%3}, [%4];" : "=r"(r[0]), "=r"(r[1]), "=r"(r[2]), "=r"(r[3]) : "r"(addr) : "memory");
}
__device__ __forceinline__ void ldsm4t(uint32_t* r, uint32_t addr) {
    asm volatile("ldmatrix.sync.aligned.m8n8.x4.trans.shared.b16 {%0,%1,%2,%3}, [%4];" : "=r"(r[0]), "=r"(r[1]), "=r"(r[2]), "=r"(r[3]) : "r"(addr) : "memory");
}
__device__ __forceinline__ void mma16816(float (&d)[4], uint32_t a0, uint32_t a1, uint32_t a2, uint32_t a3, uint32_t b0, uint32_t b1) {
    asm volatile("mma.sync.aligned.m16n8k16.row.col.f32.bf16.bf16.f32 {%0,%1,%2,%3}, {%4,%5,%6,%7}, {%8,%9}, {%0,%1,%2,%3};"
        : "+f"(d[0]), "+f"(d[1]), "+f"(d[2]), "+f"(d[3]) : "r"(a0), "r"(a1), "r"(a2), "r"(a3), "r"(b0), "r"(b1));
}
__device__ __forceinline__ uint4 lds128(uint32_t a) { uint4 v; asm volatile("ld.shared.v4.b32 {%0,%1,%2,%3}, [%4];" : "=r"(v.x), "=r"(v.y), "=r"(v.z), "=r"(v.w) : "r"(a) : "memory"); return v; }
__device__ __forceinline__ uint32_t lds32(uint32_t a) { uint32_t v; asm volatile("ld.shared.b32 %0, [%1];" : "=r"(v) : "r"(a) : "memory"); return v; }
__device__ __forceinline__ uint2 lds64(uint32_t a) { uint2 v; asm volatile("ld.shared.v2.b32 {%0,%1}, [%2];" : "=r"(v.x), "=r"(v.y) : "r"(a) : "memory"); return v; }
__device__ __forceinline__ float ldsf(uint32_t a) { float v; asm volatile("ld.shared.f32 %0, [%1];" : "=f"(v) : "r"(a) : "memory"); return v; }
__device__ __forceinline__ uint32_t lds16(uint32_t a) { uint16_t v; asm volatile("ld.shared.b16 %0, [%1];" : "=h"(v) : "r"(a) : "memory"); return v; }
__device__ __forceinline__ void sts128(uint32_t a, uint4 v) { asm volatile("st.shared.v4.b32 [%0], {%1,%2,%3,%4};" :: "r"(a), "r"(v.x), "r"(v.y), "r"(v.z), "r"(v.w) : "memory"); }
__device__ __forceinline__ void sts64(uint32_t a, uint32_t x, uint32_t y) { asm volatile("st.shared.v2.b32 [%0], {%1,%2};" :: "r"(a), "r"(x), "r"(y) : "memory"); }
__device__ __forceinline__ void sts32(uint32_t a, uint32_t x) { asm volatile("st.shared.b32 [%0], %1;" :: "r"(a), "r"(x) : "memory"); }
__device__ __forceinline__ void stsf(uint32_t a, float x) { asm volatile("st.shared.f32 [%0], %1;" :: "r"(a), "f"(x) : "memory"); }
__device__ __forceinline__ float u2f(uint32_t v) { return __uint_as_float(v); }
__device__ __forceinline__ uint32_t f2u(float v) { return __float_as_uint(v); }

__device__ __forceinline__ uint4 ldg128(const void* p) { uint4 v; asm volatile("ld.global.nc.v4.b32 {%0,%1,%2,%3}, [%4];" : "=r"(v.x), "=r"(v.y), "=r"(v.z), "=r"(v.w) : "l"(p)); return v; }
__device__ __forceinline__ uint32_t ldg32(const void* p) { uint32_t v; asm volatile("ld.global.nc.b32 %0, [%1];" : "=r"(v) : "l"(p)); return v; }
__device__ __forceinline__ void stg128(void* p, uint4 v) { asm volatile("st.global.v4.b32 [%0], {%1,%2,%3,%4};" :: "l"(p), "r"(v.x), "r"(v.y), "r"(v.z), "r"(v.w) : "memory"); }
__device__ __forceinline__ void stg_zero(void* p) { stg128(p, make_uint4(0, 0, 0, 0)); }
__device__ __forceinline__ void st_ll(uint4* p, uint32_t x, uint32_t y, uint32_t z, uint32_t w) {
    asm volatile("{\n.reg .b128 t;\n.reg .b64 a, b;\nmov.b64 a, {%1, %2};\nmov.b64 b, {%3, %4};\nmov.b128 t, {a, b};\nst.relaxed.gpu.global.b128 [%0], t;\n}"
        :: "l"(p), "r"(x), "r"(y), "r"(z), "r"(w) : "memory");
}
__device__ __forceinline__ uint4 ld_ll(const uint4* p) {
    uint4 v;
    asm volatile("{\n.reg .b128 t;\n.reg .b64 a, b;\nld.relaxed.gpu.global.b128 t, [%4];\nmov.b128 {a, b}, t;\nmov.b64 {%0, %1}, a;\nmov.b64 {%2, %3}, b;\n}"
        : "=r"(v.x), "=r"(v.y), "=r"(v.z), "=r"(v.w) : "l"(p) : "memory");
    return v;
}
__device__ __forceinline__ void st_ll4(uint4* p, float a, float b, float c, float d, uint32_t tag) {
    st_ll(p, (f2u(a) & ~1u) | (tag & 1u), (f2u(b) & ~1u) | ((tag >> 1) & 1u), (f2u(c) & ~1u) | ((tag >> 2) & 1u), f2u(d) | 1u);
}
__device__ __forceinline__ bool ll4_ok(const uint4& v, uint32_t tag) { return !(((v.x ^ tag) | (v.y ^ (tag >> 1)) | (v.z ^ (tag >> 2)) | ~v.w) & 1u); }
__device__ __forceinline__ unsigned ld_rlx(const void* p) { unsigned v; asm volatile("ld.relaxed.gpu.global.u32 %0, [%1];" : "=r"(v) : "l"(p) : "memory"); return v; }
__device__ __forceinline__ void st_flag(void* p, unsigned v) { asm volatile("st.relaxed.gpu.global.u32 [%0], %1;" :: "l"(p), "r"(v) : "memory"); }
__device__ __forceinline__ void poll_flags(const uint4* f, uint32_t tag) {
    unsigned v0 = ld_rlx(f), v1;
    spin_until(clk32() + 140);
    #pragma unroll 1
    for (int it = 0; it < POLL_MAX; it++) {
        v1 = ld_rlx(f);
        if (__all_sync(0xffffffffu, v0 == tag)) break;
        v0 = ld_rlx(f);
        if (__all_sync(0xffffffffu, v1 == tag)) break;
    }
}
template<int Z> __device__ __forceinline__ bool ll_ok(const uint4& v, uint32_t tag) { return (v.w ^ (Z >= 1 ? v.z : 0u)) == tag; }
template<int N, int Z> __device__ __forceinline__ void poll_words(uint4 (&v)[N], const uint4* p, int stride, uint32_t tag) {
    #pragma unroll 1
    for (int it = 0; it < POLL_MAX; it++) {
        bool ok = true;
        #pragma unroll
        for (int i = 0; i < N; i++) v[i] = ld_ll(p + i * stride);
        #pragma unroll
        for (int i = 0; i < N; i++) ok = ok && ll_ok<Z>(v[i], tag);
        if (__all_sync(0xffffffffu, ok)) break;
    }
}
template<int N> __device__ __forceinline__ void poll_words4(uint4 (&v)[N], const uint4* p, int stride, uint32_t tag) {
    #pragma unroll 1
    for (int it = 0; it < POLL_MAX; it++) {
        bool ok = true;
        #pragma unroll
        for (int i = 0; i < N; i++) v[i] = ld_ll(p + i * stride);
        #pragma unroll
        for (int i = 0; i < N; i++) ok = ok && ll4_ok(v[i], tag);
        if (__all_sync(0xffffffffu, ok)) break;
    }
}
constexpr uint32_t ONE2 = 0x3F803F80u;
__device__ __forceinline__ uint32_t pack2(float lo, float hi) { uint32_t d; asm("cvt.rn.bf16x2.f32 %0, %1, %2;" : "=r"(d) : "f"(hi), "f"(lo)); return d; }
__device__ __forceinline__ float bf_lo(uint32_t v) { return u2f(v << 16); }
__device__ __forceinline__ float bf_hi(uint32_t v) { return u2f(v & 0xffff0000u); }
__device__ __forceinline__ float rbf(float x) { return bf_lo(pack2(x, 0.f)); }
__device__ __forceinline__ uint32_t hsub2(uint32_t a, uint32_t b) { uint32_t d; asm("sub.rn.bf16x2 %0, %1, %2;" : "=r"(d) : "r"(a), "r"(b)); return d; }
__device__ __forceinline__ uint32_t hadd2(uint32_t a, uint32_t b) { uint32_t d; asm("add.rn.bf16x2 %0, %1, %2;" : "=r"(d) : "r"(a), "r"(b)); return d; }
__device__ __forceinline__ uint32_t hmul2(uint32_t a, uint32_t b) { uint32_t d; asm("mul.rn.bf16x2 %0, %1, %2;" : "=r"(d) : "r"(a), "r"(b)); return d; }
__device__ __forceinline__ uint32_t hfma2(uint32_t a, uint32_t b, uint32_t c) { uint32_t d; asm("fma.rn.bf16x2 %0, %1, %2, %3;" : "=r"(d) : "r"(a), "r"(b), "r"(c)); return d; }
__device__ __forceinline__ uint32_t hmax2(uint32_t a, uint32_t b) { uint32_t d; asm("max.bf16x2 %0, %1, %2;" : "=r"(d) : "r"(a), "r"(b)); return d; }
__device__ __forceinline__ uint32_t hmin2(uint32_t a, uint32_t b) { uint32_t d; asm("min.bf16x2 %0, %1, %2;" : "=r"(d) : "r"(a), "r"(b)); return d; }
__device__ __forceinline__ float ex2(float x) { float y; asm("ex2.approx.ftz.f32 %0, %1;" : "=f"(y) : "f"(x)); return y; }
__device__ __forceinline__ float rcp(float x) { float y; asm("rcp.approx.ftz.f32 %0, %1;" : "=f"(y) : "f"(x)); return y; }
__device__ __forceinline__ float shfl_x(float v, int m) { return __shfl_xor_sync(0xffffffffu, v, m); }
__device__ __forceinline__ uint32_t hdiv2(uint32_t d, uint32_t rh, uint32_t rl) { return hfma2(d, rh, hmul2(d, rl)); }
__device__ __forceinline__ void split_rcp(float r, uint32_t& rh, uint32_t& rl) { rh = pack2(r, r); const float l = r - bf_lo(rh); rl = pack2(l, l); }
__device__ __forceinline__ uint32_t lnmod(uint32_t x, uint32_t m, uint32_t rh, uint32_t rl, uint32_t a, uint32_t s) { return hadd2(hmul2(hdiv2(hsub2(x, m), rh, rl), a), s); }
__device__ __forceinline__ void ln_final(float s1, float s2, uint32_t& m2, float& rinv) {
    const float mean = s1 * (1.0f / 1024.0f), var = fmaf(-mean, mean, s2 * (1.0f / 1024.0f));
    m2 = pack2(mean, mean);
    float sd;
    asm("sqrt.approx.ftz.f32 %0, %1;" : "=f"(sd) : "f"(rbf(rbf(fmaxf(var, 0.f)) + 1e-5f)));
    rinv = rcp(rbf(sd));
}
__device__ __forceinline__ float sigmoid_f(float x) { return rcp(1.0f + ex2(-1.4426950408889634f * x)); }
__device__ __forceinline__ uint32_t silu2(uint32_t v) { return pack2(bf_lo(v) * sigmoid_f(bf_lo(v)), bf_hi(v) * sigmoid_f(bf_hi(v))); }
__device__ __forceinline__ uint32_t f2key(float f) { uint32_t u = f2u(f); return (u & 0x80000000u) ? ~u : (u | 0x80000000u); }
template<int N> __device__ __forceinline__ void top2(uint32_t (&k)[N], uint32_t& b0, uint32_t& b1) {
    uint32_t m = k[0];
    #pragma unroll
    for (int i = 1; i < N; i++) m = max(m, k[i]);
    b0 = __reduce_max_sync(0xffffffffu, m);
    m = 0;
    #pragma unroll
    for (int i = 0; i < N; i++) m = max(m, k[i] == b0 ? 0u : k[i]);
    b1 = __reduce_max_sync(0xffffffffu, m);
}
template<class T> __device__ __forceinline__ T sel4(int c, T a0, T a1, T a2, T a3) { return (c & 2) ? ((c & 1) ? a3 : a2) : ((c & 1) ? a1 : a0); }

__device__ __forceinline__ void feature_map(const uint32_t* p, uint32_t* ph) {
    const float L = 1.4426950408889634f;
    #pragma unroll
    for (int h = 0; h < 2; h++) {
        uint32_t mx = hmax2(hmax2(p[h], p[2 + h]), hmax2(p[4 + h], p[6 + h]));
        uint32_t mn = hmin2(hmin2(p[h], p[2 + h]), hmin2(p[4 + h], p[6 + h])) ^ 0x80008000u;
        uint32_t mm = hmax2(__byte_perm(mx, mn, 0x5410), __byte_perm(mx, mn, 0x7632));
        mm = hmax2(mm, __shfl_xor_sync(0xffffffffu, mm, 1));
        mm = hmax2(mm, __shfl_xor_sync(0xffffffffu, mm, 2));
        float cp = -bf_lo(mm) * L, cn = -bf_hi(mm) * L;
        float ep[8], en[8];
        #pragma unroll
        for (int j = 0; j < 4; j++) {
            float f0 = bf_lo(p[2 * j + h]), f1 = bf_hi(p[2 * j + h]);
            ep[2 * j] = ex2(fmaf(f0, L, cp)); ep[2 * j + 1] = ex2(fmaf(f1, L, cp));
            en[2 * j] = ex2(fmaf(f0, -L, cn)); en[2 * j + 1] = ex2(fmaf(f1, -L, cn));
        }
        float sp = ((ep[0] + ep[1]) + (ep[2] + ep[3])) + ((ep[4] + ep[5]) + (ep[6] + ep[7]));
        float sn = ((en[0] + en[1]) + (en[2] + en[3])) + ((en[4] + en[5]) + (en[6] + en[7]));
        sp += shfl_x(sp, 1); sn += shfl_x(sn, 1);
        sp += shfl_x(sp, 2); sn += shfl_x(sn, 2);
        float rp = rcp(sp), rn = rcp(sn);
        #pragma unroll
        for (int j = 0; j < 4; j++) {
            ph[2 * j + h] = pack2(ep[2 * j] * rp, ep[2 * j + 1] * rp);
            ph[8 + 2 * j + h] = pack2(en[2 * j] * rn, en[2 * j + 1] * rn);
        }
    }
}

template<uint32_t BO, uint32_t BH> __device__ __forceinline__ void mma192_rs(float (&d)[96], const uint32_t* a, uint32_t blo) {
  asm volatile("{\n.reg .pred p;\n.reg .b32 ta, tb;\n.reg .b64 da, db;\nadd.u32 tb, %100, %101;\nmov.b64 db, {tb, %102};\nsetp.ne.b32 p, 1, 0;\n"
    "wgmma.mma_async.sync.aligned.m64n192k16.f32.bf16.bf16 {%0, %1, %2, %3, %4, %5, %6, %7, %8, %9, %10, %11, %12, %13, %14, %15, %16, %17, %18, %19, %20, %21, %22, %23, %24, %25, %26, %27, %28, %29, %30, %31, %32, %33, %34, %35, %36, %37, %38, %39, %40, %41, %42, %43, %44, %45, %46, %47, %48, %49, %50, %51, %52, %53, %54, %55, %56, %57, %58, %59, %60, %61, %62, %63, %64, %65, %66, %67, %68, %69, %70, %71, %72, %73, %74, %75, %76, %77, %78, %79, %80, %81, %82, %83, %84, %85, %86, %87, %88, %89, %90, %91, %92, %93, %94, %95}, {%96,%97,%98,%99}, db, p, 1, 1, 1;\n}\n"
    : "+f"(d[0]), "+f"(d[1]), "+f"(d[2]), "+f"(d[3]), "+f"(d[4]), "+f"(d[5]), "+f"(d[6]), "+f"(d[7]), "+f"(d[8]), "+f"(d[9]), "+f"(d[10]), "+f"(d[11]), "+f"(d[12]), "+f"(d[13]), "+f"(d[14]), "+f"(d[15]), "+f"(d[16]), "+f"(d[17]), "+f"(d[18]), "+f"(d[19]), "+f"(d[20]), "+f"(d[21]), "+f"(d[22]), "+f"(d[23]), "+f"(d[24]), "+f"(d[25]), "+f"(d[26]), "+f"(d[27]), "+f"(d[28]), "+f"(d[29]), "+f"(d[30]), "+f"(d[31]), "+f"(d[32]), "+f"(d[33]), "+f"(d[34]), "+f"(d[35]), "+f"(d[36]), "+f"(d[37]), "+f"(d[38]), "+f"(d[39]), "+f"(d[40]), "+f"(d[41]), "+f"(d[42]), "+f"(d[43]), "+f"(d[44]), "+f"(d[45]), "+f"(d[46]), "+f"(d[47]), "+f"(d[48]), "+f"(d[49]), "+f"(d[50]), "+f"(d[51]), "+f"(d[52]), "+f"(d[53]), "+f"(d[54]), "+f"(d[55]), "+f"(d[56]), "+f"(d[57]), "+f"(d[58]), "+f"(d[59]), "+f"(d[60]), "+f"(d[61]), "+f"(d[62]), "+f"(d[63]), "+f"(d[64]), "+f"(d[65]), "+f"(d[66]), "+f"(d[67]), "+f"(d[68]), "+f"(d[69]), "+f"(d[70]), "+f"(d[71]), "+f"(d[72]), "+f"(d[73]), "+f"(d[74]), "+f"(d[75]), "+f"(d[76]), "+f"(d[77]), "+f"(d[78]), "+f"(d[79]), "+f"(d[80]), "+f"(d[81]), "+f"(d[82]), "+f"(d[83]), "+f"(d[84]), "+f"(d[85]), "+f"(d[86]), "+f"(d[87]), "+f"(d[88]), "+f"(d[89]), "+f"(d[90]), "+f"(d[91]), "+f"(d[92]), "+f"(d[93]), "+f"(d[94]), "+f"(d[95])
    : "r"(a[0]), "r"(a[1]), "r"(a[2]), "r"(a[3]), "r"(blo), "n"(BO), "n"(BH));
}
template<uint32_t BO, uint32_t BH> __device__ __forceinline__ void mma192_rsp(float (&d)[96], const uint32_t* a, uint32_t blo, int sc) {
  asm volatile("{\n.reg .pred p;\n.reg .b32 ta, tb;\n.reg .b64 da, db;\nadd.u32 tb, %100, %101;\nmov.b64 db, {tb, %102};\nsetp.ne.b32 p, %103, 0;\n"
    "wgmma.mma_async.sync.aligned.m64n192k16.f32.bf16.bf16 {%0, %1, %2, %3, %4, %5, %6, %7, %8, %9, %10, %11, %12, %13, %14, %15, %16, %17, %18, %19, %20, %21, %22, %23, %24, %25, %26, %27, %28, %29, %30, %31, %32, %33, %34, %35, %36, %37, %38, %39, %40, %41, %42, %43, %44, %45, %46, %47, %48, %49, %50, %51, %52, %53, %54, %55, %56, %57, %58, %59, %60, %61, %62, %63, %64, %65, %66, %67, %68, %69, %70, %71, %72, %73, %74, %75, %76, %77, %78, %79, %80, %81, %82, %83, %84, %85, %86, %87, %88, %89, %90, %91, %92, %93, %94, %95}, {%96,%97,%98,%99}, db, p, 1, 1, 1;\n}\n"
    : "+f"(d[0]), "+f"(d[1]), "+f"(d[2]), "+f"(d[3]), "+f"(d[4]), "+f"(d[5]), "+f"(d[6]), "+f"(d[7]), "+f"(d[8]), "+f"(d[9]), "+f"(d[10]), "+f"(d[11]), "+f"(d[12]), "+f"(d[13]), "+f"(d[14]), "+f"(d[15]), "+f"(d[16]), "+f"(d[17]), "+f"(d[18]), "+f"(d[19]), "+f"(d[20]), "+f"(d[21]), "+f"(d[22]), "+f"(d[23]), "+f"(d[24]), "+f"(d[25]), "+f"(d[26]), "+f"(d[27]), "+f"(d[28]), "+f"(d[29]), "+f"(d[30]), "+f"(d[31]), "+f"(d[32]), "+f"(d[33]), "+f"(d[34]), "+f"(d[35]), "+f"(d[36]), "+f"(d[37]), "+f"(d[38]), "+f"(d[39]), "+f"(d[40]), "+f"(d[41]), "+f"(d[42]), "+f"(d[43]), "+f"(d[44]), "+f"(d[45]), "+f"(d[46]), "+f"(d[47]), "+f"(d[48]), "+f"(d[49]), "+f"(d[50]), "+f"(d[51]), "+f"(d[52]), "+f"(d[53]), "+f"(d[54]), "+f"(d[55]), "+f"(d[56]), "+f"(d[57]), "+f"(d[58]), "+f"(d[59]), "+f"(d[60]), "+f"(d[61]), "+f"(d[62]), "+f"(d[63]), "+f"(d[64]), "+f"(d[65]), "+f"(d[66]), "+f"(d[67]), "+f"(d[68]), "+f"(d[69]), "+f"(d[70]), "+f"(d[71]), "+f"(d[72]), "+f"(d[73]), "+f"(d[74]), "+f"(d[75]), "+f"(d[76]), "+f"(d[77]), "+f"(d[78]), "+f"(d[79]), "+f"(d[80]), "+f"(d[81]), "+f"(d[82]), "+f"(d[83]), "+f"(d[84]), "+f"(d[85]), "+f"(d[86]), "+f"(d[87]), "+f"(d[88]), "+f"(d[89]), "+f"(d[90]), "+f"(d[91]), "+f"(d[92]), "+f"(d[93]), "+f"(d[94]), "+f"(d[95])
    : "r"(a[0]), "r"(a[1]), "r"(a[2]), "r"(a[3]), "r"(blo), "n"(BO), "n"(BH), "r"(sc));
}
template<uint32_t BO, uint32_t BH> __device__ __forceinline__ void mma32_rs(float (&d)[16], const uint32_t* a, uint32_t blo) {
  asm volatile("{\n.reg .pred p;\n.reg .b32 ta, tb;\n.reg .b64 da, db;\nadd.u32 tb, %20, %21;\nmov.b64 db, {tb, %22};\nsetp.ne.b32 p, 1, 0;\n"
    "wgmma.mma_async.sync.aligned.m64n32k16.f32.bf16.bf16 {%0, %1, %2, %3, %4, %5, %6, %7, %8, %9, %10, %11, %12, %13, %14, %15}, {%16,%17,%18,%19}, db, p, 1, 1, 1;\n}\n"
    : "+f"(d[0]), "+f"(d[1]), "+f"(d[2]), "+f"(d[3]), "+f"(d[4]), "+f"(d[5]), "+f"(d[6]), "+f"(d[7]), "+f"(d[8]), "+f"(d[9]), "+f"(d[10]), "+f"(d[11]), "+f"(d[12]), "+f"(d[13]), "+f"(d[14]), "+f"(d[15])
    : "r"(a[0]), "r"(a[1]), "r"(a[2]), "r"(a[3]), "r"(blo), "n"(BO), "n"(BH));
}
template<uint32_t BO, uint32_t BH> __device__ __forceinline__ void mma32_rs0(float (&d)[16], const uint32_t* a, uint32_t blo) {
  asm volatile("{\n.reg .pred p;\n.reg .b32 ta, tb;\n.reg .b64 da, db;\nadd.u32 tb, %20, %21;\nmov.b64 db, {tb, %22};\nsetp.ne.b32 p, 0, 0;\n"
    "wgmma.mma_async.sync.aligned.m64n32k16.f32.bf16.bf16 {%0, %1, %2, %3, %4, %5, %6, %7, %8, %9, %10, %11, %12, %13, %14, %15}, {%16,%17,%18,%19}, db, p, 1, 1, 1;\n}\n"
    : "=f"(d[0]), "=f"(d[1]), "=f"(d[2]), "=f"(d[3]), "=f"(d[4]), "=f"(d[5]), "=f"(d[6]), "=f"(d[7]), "=f"(d[8]), "=f"(d[9]), "=f"(d[10]), "=f"(d[11]), "=f"(d[12]), "=f"(d[13]), "=f"(d[14]), "=f"(d[15])
    : "r"(a[0]), "r"(a[1]), "r"(a[2]), "r"(a[3]), "r"(blo), "n"(BO), "n"(BH));
}
template<uint32_t BO, uint32_t BH> __device__ __forceinline__ void mma40_rs(float (&d)[20], const uint32_t* a, uint32_t blo) {
  asm volatile("{\n.reg .pred p;\n.reg .b32 ta, tb;\n.reg .b64 da, db;\nadd.u32 tb, %24, %25;\nmov.b64 db, {tb, %26};\nsetp.ne.b32 p, 1, 0;\n"
    "wgmma.mma_async.sync.aligned.m64n40k16.f32.bf16.bf16 {%0, %1, %2, %3, %4, %5, %6, %7, %8, %9, %10, %11, %12, %13, %14, %15, %16, %17, %18, %19}, {%20,%21,%22,%23}, db, p, 1, 1, 1;\n}\n"
    : "+f"(d[0]), "+f"(d[1]), "+f"(d[2]), "+f"(d[3]), "+f"(d[4]), "+f"(d[5]), "+f"(d[6]), "+f"(d[7]), "+f"(d[8]), "+f"(d[9]), "+f"(d[10]), "+f"(d[11]), "+f"(d[12]), "+f"(d[13]), "+f"(d[14]), "+f"(d[15]), "+f"(d[16]), "+f"(d[17]), "+f"(d[18]), "+f"(d[19])
    : "r"(a[0]), "r"(a[1]), "r"(a[2]), "r"(a[3]), "r"(blo), "n"(BO), "n"(BH));
}
template<uint32_t BO, uint32_t BH> __device__ __forceinline__ void mma40_rs0(float (&d)[20], const uint32_t* a, uint32_t blo) {
  asm volatile("{\n.reg .pred p;\n.reg .b32 ta, tb;\n.reg .b64 da, db;\nadd.u32 tb, %24, %25;\nmov.b64 db, {tb, %26};\nsetp.ne.b32 p, 0, 0;\n"
    "wgmma.mma_async.sync.aligned.m64n40k16.f32.bf16.bf16 {%0, %1, %2, %3, %4, %5, %6, %7, %8, %9, %10, %11, %12, %13, %14, %15, %16, %17, %18, %19}, {%20,%21,%22,%23}, db, p, 1, 1, 1;\n}\n"
    : "=f"(d[0]), "=f"(d[1]), "=f"(d[2]), "=f"(d[3]), "=f"(d[4]), "=f"(d[5]), "=f"(d[6]), "=f"(d[7]), "=f"(d[8]), "=f"(d[9]), "=f"(d[10]), "=f"(d[11]), "=f"(d[12]), "=f"(d[13]), "=f"(d[14]), "=f"(d[15]), "=f"(d[16]), "=f"(d[17]), "=f"(d[18]), "=f"(d[19])
    : "r"(a[0]), "r"(a[1]), "r"(a[2]), "r"(a[3]), "r"(blo), "n"(BO), "n"(BH));
}
template<uint32_t AO, uint32_t AH, uint32_t BO, uint32_t BH> __device__ __forceinline__ void mma40_tt(float (&d)[20], uint32_t alo, uint32_t blo) {
  asm volatile("{\n.reg .pred p;\n.reg .b32 ta, tb;\n.reg .b64 da, db;\nadd.u32 ta, %20, %21;\nmov.b64 da, {ta, %22};\nadd.u32 tb, %23, %24;\nmov.b64 db, {tb, %25};\nsetp.ne.b32 p, 1, 0;\n"
    "wgmma.mma_async.sync.aligned.m64n40k16.f32.bf16.bf16 {%0, %1, %2, %3, %4, %5, %6, %7, %8, %9, %10, %11, %12, %13, %14, %15, %16, %17, %18, %19}, da, db, p, 1, 1, 1, 1;\n}\n"
    : "+f"(d[0]), "+f"(d[1]), "+f"(d[2]), "+f"(d[3]), "+f"(d[4]), "+f"(d[5]), "+f"(d[6]), "+f"(d[7]), "+f"(d[8]), "+f"(d[9]), "+f"(d[10]), "+f"(d[11]), "+f"(d[12]), "+f"(d[13]), "+f"(d[14]), "+f"(d[15]), "+f"(d[16]), "+f"(d[17]), "+f"(d[18]), "+f"(d[19])
    : "r"(alo), "n"(AO), "n"(AH), "r"(blo), "n"(BO), "n"(BH));
}
template<uint32_t AO, uint32_t AH, uint32_t BO, uint32_t BH> __device__ __forceinline__ void mma40_tt0(float (&d)[20], uint32_t alo, uint32_t blo) {
  asm volatile("{\n.reg .pred p;\n.reg .b32 ta, tb;\n.reg .b64 da, db;\nadd.u32 ta, %20, %21;\nmov.b64 da, {ta, %22};\nadd.u32 tb, %23, %24;\nmov.b64 db, {tb, %25};\nsetp.ne.b32 p, 0, 0;\n"
    "wgmma.mma_async.sync.aligned.m64n40k16.f32.bf16.bf16 {%0, %1, %2, %3, %4, %5, %6, %7, %8, %9, %10, %11, %12, %13, %14, %15, %16, %17, %18, %19}, da, db, p, 1, 1, 1, 1;\n}\n"
    : "=f"(d[0]), "=f"(d[1]), "=f"(d[2]), "=f"(d[3]), "=f"(d[4]), "=f"(d[5]), "=f"(d[6]), "=f"(d[7]), "=f"(d[8]), "=f"(d[9]), "=f"(d[10]), "=f"(d[11]), "=f"(d[12]), "=f"(d[13]), "=f"(d[14]), "=f"(d[15]), "=f"(d[16]), "=f"(d[17]), "=f"(d[18]), "=f"(d[19])
    : "r"(alo), "n"(AO), "n"(AH), "r"(blo), "n"(BO), "n"(BH));
}
template<uint32_t AO, uint32_t AH, uint32_t BO, uint32_t BH> __device__ __forceinline__ void mma128_ss(float (&d)[64], uint32_t alo, uint32_t blo) {
  asm volatile("{\n.reg .pred p;\n.reg .b32 ta, tb;\n.reg .b64 da, db;\nadd.u32 ta, %64, %65;\nmov.b64 da, {ta, %66};\nadd.u32 tb, %67, %68;\nmov.b64 db, {tb, %69};\nsetp.ne.b32 p, 1, 0;\n"
    "wgmma.mma_async.sync.aligned.m64n128k16.f32.bf16.bf16 {%0, %1, %2, %3, %4, %5, %6, %7, %8, %9, %10, %11, %12, %13, %14, %15, %16, %17, %18, %19, %20, %21, %22, %23, %24, %25, %26, %27, %28, %29, %30, %31, %32, %33, %34, %35, %36, %37, %38, %39, %40, %41, %42, %43, %44, %45, %46, %47, %48, %49, %50, %51, %52, %53, %54, %55, %56, %57, %58, %59, %60, %61, %62, %63}, da, db, p, 1, 1, 0, 1;\n}\n"
    : "+f"(d[0]), "+f"(d[1]), "+f"(d[2]), "+f"(d[3]), "+f"(d[4]), "+f"(d[5]), "+f"(d[6]), "+f"(d[7]), "+f"(d[8]), "+f"(d[9]), "+f"(d[10]), "+f"(d[11]), "+f"(d[12]), "+f"(d[13]), "+f"(d[14]), "+f"(d[15]), "+f"(d[16]), "+f"(d[17]), "+f"(d[18]), "+f"(d[19]), "+f"(d[20]), "+f"(d[21]), "+f"(d[22]), "+f"(d[23]), "+f"(d[24]), "+f"(d[25]), "+f"(d[26]), "+f"(d[27]), "+f"(d[28]), "+f"(d[29]), "+f"(d[30]), "+f"(d[31]), "+f"(d[32]), "+f"(d[33]), "+f"(d[34]), "+f"(d[35]), "+f"(d[36]), "+f"(d[37]), "+f"(d[38]), "+f"(d[39]), "+f"(d[40]), "+f"(d[41]), "+f"(d[42]), "+f"(d[43]), "+f"(d[44]), "+f"(d[45]), "+f"(d[46]), "+f"(d[47]), "+f"(d[48]), "+f"(d[49]), "+f"(d[50]), "+f"(d[51]), "+f"(d[52]), "+f"(d[53]), "+f"(d[54]), "+f"(d[55]), "+f"(d[56]), "+f"(d[57]), "+f"(d[58]), "+f"(d[59]), "+f"(d[60]), "+f"(d[61]), "+f"(d[62]), "+f"(d[63])
    : "r"(alo), "n"(AO), "n"(AH), "r"(blo), "n"(BO), "n"(BH));
}
template<uint32_t AO, uint32_t AH, uint32_t BO, uint32_t BH> __device__ __forceinline__ void mma128_ss0(float (&d)[64], uint32_t alo, uint32_t blo) {
  asm volatile("{\n.reg .pred p;\n.reg .b32 ta, tb;\n.reg .b64 da, db;\nadd.u32 ta, %64, %65;\nmov.b64 da, {ta, %66};\nadd.u32 tb, %67, %68;\nmov.b64 db, {tb, %69};\nsetp.ne.b32 p, 0, 0;\n"
    "wgmma.mma_async.sync.aligned.m64n128k16.f32.bf16.bf16 {%0, %1, %2, %3, %4, %5, %6, %7, %8, %9, %10, %11, %12, %13, %14, %15, %16, %17, %18, %19, %20, %21, %22, %23, %24, %25, %26, %27, %28, %29, %30, %31, %32, %33, %34, %35, %36, %37, %38, %39, %40, %41, %42, %43, %44, %45, %46, %47, %48, %49, %50, %51, %52, %53, %54, %55, %56, %57, %58, %59, %60, %61, %62, %63}, da, db, p, 1, 1, 0, 1;\n}\n"
    : "=f"(d[0]), "=f"(d[1]), "=f"(d[2]), "=f"(d[3]), "=f"(d[4]), "=f"(d[5]), "=f"(d[6]), "=f"(d[7]), "=f"(d[8]), "=f"(d[9]), "=f"(d[10]), "=f"(d[11]), "=f"(d[12]), "=f"(d[13]), "=f"(d[14]), "=f"(d[15]), "=f"(d[16]), "=f"(d[17]), "=f"(d[18]), "=f"(d[19]), "=f"(d[20]), "=f"(d[21]), "=f"(d[22]), "=f"(d[23]), "=f"(d[24]), "=f"(d[25]), "=f"(d[26]), "=f"(d[27]), "=f"(d[28]), "=f"(d[29]), "=f"(d[30]), "=f"(d[31]), "=f"(d[32]), "=f"(d[33]), "=f"(d[34]), "=f"(d[35]), "=f"(d[36]), "=f"(d[37]), "=f"(d[38]), "=f"(d[39]), "=f"(d[40]), "=f"(d[41]), "=f"(d[42]), "=f"(d[43]), "=f"(d[44]), "=f"(d[45]), "=f"(d[46]), "=f"(d[47]), "=f"(d[48]), "=f"(d[49]), "=f"(d[50]), "=f"(d[51]), "=f"(d[52]), "=f"(d[53]), "=f"(d[54]), "=f"(d[55]), "=f"(d[56]), "=f"(d[57]), "=f"(d[58]), "=f"(d[59]), "=f"(d[60]), "=f"(d[61]), "=f"(d[62]), "=f"(d[63])
    : "r"(alo), "n"(AO), "n"(AH), "r"(blo), "n"(BO), "n"(BH));
}

#define XD 0
#define XSTEP 250
#define XEARLY 1
#define SPG 3600
#define WL0 4700
#define WLS 350
#define PF_START 2900
#define PFP 112
#define LMLAG 1800
#define GATE0 22
#define WOGAP 300
#define UPGAP 450
#define OUTGAP 150
struct Ptrs { const bf16 *x, *wmod; Scratch* s; int by_sm; const bf16 *c, *wr, *wg, *wu, *wd, *wqkv, *wo; bf16* out; };

#define BAR(i) (sb + OFF_BAR + 8u * (i))

constexpr int PF_COUNT = 58;
__device__ __forceinline__ uint64_t bg_entry(const Ptrs& p, int b, int i) {
    if (i < 30 && (i < 2 || (i & 1))) return (uint64_t)(p.wqkv + (size_t)(((i + 1) >> 1) * 128 + b) * 1536) | 3;
    const int o = i < 30 ? (i - 2) >> 1 : i - 16;
    if (o < 8) return (uint64_t)(p.wmod + (size_t)(o * 128 + b) * 6144 + 2048) | 8;
    if (o < 16) return (uint64_t)(p.wg + (size_t)((o - 8) * 128 + b) * 3584) | 7;
    if (o < 18) return (uint64_t)(p.wo + (size_t)b * 8192 + (o - 16) * 4096) | 8;
    if (o < 26) return (uint64_t)(p.wu + (size_t)((o - 18) * 128 + b) * 3584) | 7;
    if (o < 34) return (uint64_t)(p.wd + (size_t)b * 28672 + (o - 26) * 3584) | 7;
    return (uint64_t)(p.x + (size_t)b * 16384 + (o - 34) * 2048) | 4;
}
struct Bg { uint32_t next, due; };
__device__ __forceinline__ void bg_step(uint32_t sb, Bg& g) {
    if (g.next < sb + OFF_PFL + PF_COUNT * 8 && (int)(clk32() - g.due) >= 0) {
        uint64_t e;
        asm volatile("ld.shared.b64 %0, [%1];" : "=l"(e) : "r"(g.next));
        const uint32_t kb = (uint32_t)e & 15u;
        l2_prefetch((const void*)(e ^ kb), kb << 10);
        g.next += 8; g.due += kb * PFP;
    }
}
__device__ __forceinline__ Bg bg_wait(uint32_t sb, uint32_t bar, uint32_t parity, uint32_t t, Bg g) {
    #pragma unroll 1
    for (int it = 0; it < POLL_MAX && !(mbar_test(bar, parity) && (int)(clk32() - t) >= 0); it++) { bg_step(sb, g); __nanosleep(20); }
    return g;
}
__device__ __forceinline__ int d_kb(int n, int hg) {
    if (n < 2) return 2 * hg + n;
    const int h = n >= 9, q = n - 2 - 7 * h;
    return 2 * (q + (q >= hg)) + h;
}

__global__ void __launch_bounds__(NTHREADS, 1)
fused_kernel(const Ptrs p, const __grid_constant__ CUtensorMap tmM, const __grid_constant__ CUtensorMap tmX, const __grid_constant__ CUtensorMap tmW,
             const __grid_constant__ CUtensorMap tmWo, const __grid_constant__ CUtensorMap tmPhi, const __grid_constant__ CUtensorMap tmG,
             const __grid_constant__ CUtensorMap tmU, const __grid_constant__ CUtensorMap tmD, const __grid_constant__ CUtensorMap tmO)
{
    extern __shared__ __align__(1024) uint8_t smem_raw[];
    const uint32_t sb = smem_u32(smem_raw);
    const uint32_t cstart = clk32();
    const int tid = threadIdx.x, lane = tid & 31, warp = __shfl_sync(0xffffffffu, tid >> 5, 0);
    if (warp == 8 && blockIdx.x < 128)
        asm volatile("prefetch.global.L2 [%0];" :: "l"(p.wmod + (size_t)(blockIdx.x * 8 + (lane >> 2)) * 6144 + (lane & 1) * 64 + (lane & 2) * 512));
    const uint32_t tag = ldg32(p.s->done) + 1;
    int b;
    {
        uint32_t sm;
        asm("mov.u32 %0, %%smid;" : "=r"(sm));
        const int tp = sm >> 1, u = tp - 32, q = (u * 37) >> 8;
        const int gp = tp < 32 ? tp & 7 : tp < 60 ? 1 + u - 7 * q : 0;
        const int sl = 2 * (tp < 32 ? tp >> 3 : tp < 60 ? 4 + q : tp - 58) + (sm & 1);
        b = (tp >> 1) == 30 ? (int)sm + 8 : ((gp >> 1) * 4 + (sl & 3)) * 8 + (gp & 1) * 4 + (sl >> 2);
        if (!p.by_sm) b = blockIdx.x;
    }
    if (lane == 0) {
        if (warp < 8) {
            mbar_init(BAR(B_XP + warp), 1);
            mbar_init_fence();
            if (b < 128 && XD + XSTEP * ((warp + b) & 7) < 900) {
                mbar_arrive_tx(BAR(B_XP + warp), 4096);
                bulk_load(sb + OFF_R0 + warp * 4096u, p.x + (size_t)(b * 16 + 2 * warp) * 1024, 4096, BAR(B_XP + warp));
            }
        }
        const uint32_t cn = warp < 4 ? 1 : warp < 6 ? 2 : 8;
        #pragma unroll
        for (int i = 0; i < 4; i++) mbar_init(BAR(4 * warp + i), cn);
        mbar_init_fence();
    }
    __syncthreads();

    if (b >= 128) {
        const int vec = b & 1, half = (b >> 1) & 1;
        if (warp == 8) {
            if (lane == 0) {
                #pragma unroll 1
                for (int j = 0, st = 0, ph = 1; j < 32; j++) {
                    if (j == 4) spin_until(cstart + SPG);
                    mbar_wait(BAR(B_EA + st), ph);
                    mbar_arrive_tx(BAR(st), 32768);
                    tma_load_ef(sb + st * 32768u, &tmM, vec * 1024 + (j >> 1) * 64, half * 512 + (j & 1) * 256, BAR(st));
                    if (++st == 6) { st = 0; ph ^= 1; }
                }
            }
        } else if (warp < 8) {
            const int g = lane >> 2, c = lane & 3;
            stg_zero(p.s->llm1 + (tid >> 4) * 64 + half * 32 + vec * 16 + (tid & 15));
            uint32_t sv[8];
            #pragma unroll
            for (int i = 0; i < 8; i++) sv[i] = ldg32(p.c + half * 512 + (i >> 2) * 256 + warp * 32 + (i & 3) * 8 + 2 * c);
            #pragma unroll
            for (int i = 0; i < 8; i++) sv[i] = silu2(sv[i]);
            const uint32_t wa = sb + (warp * 32 + (lane & 7) + (lane >> 4) * 8) * 128u + ((((lane >> 3) & 1) ^ (lane & 7)) << 4);
            #pragma unroll 1
            for (int kb = 0, st = 0, ph = 0; kb < 16; kb++) {
                float m[4][4];
                #pragma unroll
                for (int i = 0; i < 4; i++) m[i][0] = m[i][1] = m[i][2] = m[i][3] = 0.f;
                #pragma unroll
                for (int q = 0; q < 2; q++) {
                    mbar_wait(BAR(st + q), ph);
                    uint32_t f[8][4];
                    #pragma unroll
                    for (int i = 0; i < 8; i++) ldsm4t(f[i], (wa + (st + q) * 32768u + (i >> 2) * 2048u) ^ ((i & 3) << 5));
                    #pragma unroll
                    for (int i = 0; i < 8; i++) mma16816(m[i & 3], f[i][0], f[i][1], f[i][2], f[i][3], sv[4 * q + 2 * (i >> 2)], sv[4 * q + 2 * (i >> 2) + 1]);
                    __syncwarp();
                    if (lane == 0) mbar_arrive(BAR(B_EA + st + q));
                }
                const uint32_t red = sb + 196608u + (kb & 1) * 2048u;
                const uint32_t a = red + warp * 256u + (c * 16 + (g >> 1) * 4 + (g & 1)) * 4u;
                stsf(a, sel4(c, m[0][0], m[1][0], m[2][0], m[3][0])); stsf(a + 8, sel4(c, m[0][2], m[1][2], m[2][2], m[3][2]));
                bar_sync(1, 256);
                if (warp == (kb & 7)) {
                    const uint32_t ra = red + (lane >> 4) * 1024u + (lane & 15) * 16u;
                    const uint4 r0 = lds128(ra), r1 = lds128(ra + 256), r2 = lds128(ra + 512), r3 = lds128(ra + 768);
                    #define F4(f) ((u2f(r0.f) + u2f(r1.f)) + (u2f(r2.f) + u2f(r3.f)))
                    float x = F4(x), y = F4(y), z = F4(z), w = F4(w);
                    #undef F4
                    x += shfl_x(x, 16); y += shfl_x(y, 16); z += shfl_x(z, 16); w += shfl_x(w, 16);
                    if (lane < 16) st_ll4(p.s->llm1 + kb * 64 + half * 32 + vec * 16 + lane, x, y, z, w, tag);
                    TR(kb);
                }
                st += 2; if (st == 6) { st = 0; ph ^= 1; }
            }
        }
    } else if (warp >= 8) {
        reg_dec<40>();
        const int rb = b >> 3, hg = b & 7;
        const bool ffn = b < 112;
        if (warp == 8) {
            tmap_prefetch(&tmX);
            mbar_wait(BAR(B_STP), 0);
            #pragma unroll 1
            for (int j = 0, s = 0, ph = 1; j < 16; j++) {
                if (j == XEARLY) mbar_wait(BAR(B_STS), 0);
                mbar_wait(BAR(B_EA + s), ph);
                if (lane == 0) { mbar_expect_tx(BAR(B_FA + s), 16384); tma_load(sb + OFF_A + s * 16384u, &tmX, j * 64, rb * 128, BAR(B_FA + s)); }
                uint4 w[2];
                poll_words4<2>(w, p.s->llm1 + j * 64 + lane, 32, tag);
                uint32_t lo = pack2(u2f(w[0].x) + u2f(w[1].x), u2f(w[0].y) + u2f(w[1].y)), hi = pack2(u2f(w[0].z) + u2f(w[1].z), u2f(w[0].w) + u2f(w[1].w));
                if (lane >= 16) { lo = hadd2(lo, ONE2); hi = hadd2(hi, ONE2); }
                sts64(sb + OFF_TAB + j * 256 + (lane & 15) * 16 + (lane < 16 ? 8 : 0), lo, hi);
                __syncwarp();
                if (lane == 0) mbar_arrive(BAR(B_FA + s));
                if (j == 0) TS(2);
                TR(16 + j);
                if (++s == 3) { s = 0; ph ^= 1; }
            }
            tmap_prefetch(&tmO);
            if (lane < 2) mbar_arrive(BAR(B_FD + lane));
            mbar_wait(BAR(B_VF), 0);
            #pragma unroll 1
            for (int q = 0; q < 2; q++) {
                poll_flags(p.s->flk + (q + 1) * 256 + (hg * 16 + (lane & 15)) * 2, tag);
                if (lane == 0) { mbar_arrive_tx(BAR(B_KVL + q), 16896); bulk_load(sb + (q ? OFF_KS : OFF_PHI), p.s->kvacc + hg * 2112 + q * 1056, 16896, BAR(B_KVL + q)); }
                TS(12 + q);
            }
            const uint4* osrc = p.s->os + (size_t)rb * 16 * 1024;
            #pragma unroll 1
            for (int n = 2; n < 18; n++) {
                const uint32_t s = n & 3, fb = BAR(B_FD + s), dst = sb + OFF_R0 + s * 16384u;
                mbar_wait(BAR(B_ED + s), ((n >> 2) - 1) & 1);
                if (n == 5) mbar_wait(BAR(B_OST), 0);
                if (n == 2 || n == 9) poll_flags(p.s->flo + ((rb & 12) * 16 + lane * 2 + (n == 9)) * 2, tag);
                if (n == 2) TS(3);
                if (n == 9) TS(4);
                if (lane == 0) {
                    mbar_arrive_tx(fb, 16384);
                    if (n < 16) bulk_load(dst, osrc + d_kb(n, hg) * 1024, 16384, fb);
                    else { mbar_arrive(fb); tma_load(dst, &tmX, hg * 128 + (n - 16) * 64, rb * 128, fb); }
                }
                TR(32 + n);
            }
            mbar_wait(BAR(B_CAND), 0);
            const uint32_t lc = lds32(sb + OFF_CST + 16), w0 = (lc >> 4) & 7, w1 = lc >> 12;
            mbar_wait(BAR(B_SWP), 0);
            fence_async_smem();
            if (lane == 0) {
                #pragma unroll 1
                for (uint32_t w = 0; w < 8; w++)
                    if (w != w0 && w != w1) { tma_store4(&tmO, rb * 128 + w * 16, hg * 2, sb + OFF_OUT + w * 4096u); spin_until(clk32() + OUTGAP); }
            }
            __syncwarp();
            mbar_wait(BAR(B_XP), 1);
            const uint2 sel = lds64(sb + OFF_CST + 24);
            #pragma unroll 1
            for (uint32_t i = 0; i < (w0 == w1 ? 8u : 16u); i++) {
                const uint32_t w = i < 8 ? w0 : w1, r = (i & 7) * 2 + (lane >> 4), row = rb * 128 + w * 16 + r;
                const uint4 o = lds128(sb + OFF_OUT + w * 4096u + ((lane >> 3) & 1) * 2048u + r * 128u + (((lane ^ r) & 7) << 4));
                if (row != sel.x && row != sel.y) stg128(p.out + (size_t)row * 1024 + hg * 128 + (lane & 15) * 8, o);
            }
            bulk_wait_read();
        } else if (warp == 9) {
            #pragma unroll 1
            for (int i = lane; i < PF_COUNT; i += 32) { const uint64_t e = bg_entry(p, b, i); sts64(sb + OFF_PFL + i * 8, (uint32_t)e, (uint32_t)(e >> 32)); }
            __syncwarp();
            if (lane == 0) {
                tmap_prefetch(&tmW);
                Bg bg = {sb + OFF_PFL, cstart + PF_START};
                #pragma unroll 1
                for (int i = 0; i < 32; i++) {
                    const uint32_t s = i & 3;
                    bg = bg_wait(sb, BAR(B_EB + s), ((i >> 2) - 1) & 1, cstart + WL0 + WLS * s, bg);
                    mbar_arrive_tx(BAR(B_FB + s), 24576);
                    tma_load4(sb + OFF_B + s * 24576u, &tmW, i * 32, hg * 2, BAR(B_FB + s));
                    TR(64 + i);
                    if (i == 8) { tmap_prefetch(&tmPhi); tmap_prefetch(&tmG); tmap_prefetch(&tmWo); tmap_prefetch(&tmU); tmap_prefetch(&tmD); }
                    if (i == 16) { mbar_arrive_tx(BAR(B_WPHI), 8192); tma_load(sb + OFF_WPHI, &tmPhi, 0, hg * 128, BAR(B_WPHI)); mbar_arrive_tx(BAR(B_GF), ffn ? 65536 : 0); }
                    if (ffn && (uint32_t)(i - GATE0) < 8u) tma_load_ef(sb + OFF_R0 + (i - GATE0) * 8192u, &tmG, b * 32, (i - GATE0) * 128, BAR(B_GF));
                }
                mbar_arrive_tx(BAR(B_WD), ffn ? 65536 : 0);
                #pragma unroll 1
                for (int n = 0; n < 16; n++) {
                    const uint32_t s = n & 3;
                    if (n == 4) {
                        #pragma unroll 1
                        for (int i = 0; i < 8; i++) {
                            bg = bg_wait(sb, BAR(i < 4 ? B_VF : B_KVC), 0, clk32() + UPGAP, bg);
                            if (!(i & 3)) mbar_arrive_tx(BAR(B_UF), ffn ? 32768 : 0);
                            if (ffn) tma_load_ef(sb + OFF_F2 + i * 8192u, &tmU, b * 32, i * 128, BAR(B_UF));
                        }
                    }
                    bg = bg_wait(sb, n < 4 ? BAR(B_QE) : BAR(B_ED + s), n < 4 ? 0 : ((n >> 2) - 1) & 1, clk32() + (n < 4 ? WOGAP : 0), bg);
                    mbar_arrive_tx(BAR(B_FD + s), 16384);
                    tma_load4(sb + OFF_DB + s * 16384u, &tmWo, d_kb(n, hg) * 64, hg * 2, BAR(B_FD + s));
                    TR(96 + n);
                    if (ffn && n >= 8) {
                        const int z = 8 * (n & 1) + ((n - 8) >> 1);
                        tma_load_ef(sb + OFF_F2 + z * 4096u, &tmD, z * 64, b * 32, BAR(B_WD));
                        tma_load_ef(sb + OFF_F2 + z * 4096u + 16384u, &tmD, z * 64 + 256, b * 32, BAR(B_WD));
                    }
                }
            }
        } else {
            const int t = tid & 63, c = lane & 3;
            if (warp == 10) {
                if (lane < 8) stg_zero(p.s->llmod2 + b * 8 + lane);
                else if (lane < 12) stg_zero(p.s->flo + b * 4 + lane - 8);
                else if (lane < 16) stg_zero(p.s->flk + (((lane >> 1) & 1) + 1) * 256 + (hg * 16 + rb) * 2 + (lane & 1));
            }
            {
                #pragma unroll 1
                for (int i = 0; i < 2; i++) {
                    const uint4 cv = ldg128(p.c + (i * 64 + t) * 8);
                    sts128(sb + OFF_SILU + (i * 64 + t) * 16, make_uint4(silu2(cv.x), silu2(cv.y), silu2(cv.z), silu2(cv.w)));
                }
                if (warp == 11) {
                    spin_until(cstart + 7000);
                    #pragma unroll 1
                    for (int i = lane; i < 132; i += 32) stg_zero(p.s->kvacc + hg * 2112 + rb * 132 + i);
                    asm volatile("fence.acq_rel.gpu;" ::: "memory");
                    __syncwarp();
                    if (lane < 2) st_ll(p.s->flk + (hg * 16 + rb) * 2 + lane, tag, 0, 0, 0);
                }
                bar_sync(2, 64);
                float m[8];
                #pragma unroll
                for (int i = 0; i < 8; i++) m[i] = 0.f;
                const bf16* wp = p.wmod + (size_t)(t >> 2) * 6144 + 2048 + b * 32 + c * 8;
                #pragma unroll 1
                for (int j = 0; j < 16; j++) {
                    while ((int)(clk32() - cstart) < PF_START + LMLAG + (6 + 11 * (j >> 1)) * PFP) __nanosleep(50);
                    uint4 w[4];
                    #pragma unroll
                    for (int i = 0; i < 4; i++) w[i] = ldg128(wp + (size_t)(j * 64 + i * 16) * 6144);
                    #pragma unroll
                    for (int i = 0; i < 4; i++) {
                        const float sv = bf_lo(lds16(sb + OFF_SILU + (j * 64 + i * 16 + (t >> 2)) * 2));
                        m[0] = fmaf(bf_lo(w[i].x), sv, m[0]); m[1] = fmaf(bf_hi(w[i].x), sv, m[1]); m[2] = fmaf(bf_lo(w[i].y), sv, m[2]); m[3] = fmaf(bf_hi(w[i].y), sv, m[3]);
                        m[4] = fmaf(bf_lo(w[i].z), sv, m[4]); m[5] = fmaf(bf_hi(w[i].z), sv, m[5]); m[6] = fmaf(bf_lo(w[i].w), sv, m[6]); m[7] = fmaf(bf_hi(w[i].w), sv, m[7]);
                    }
                }
                #pragma unroll 1
                for (int d = 4; d < 32; d <<= 1) {
                    #pragma unroll
                    for (int i = 0; i < 8; i++) m[i] += shfl_x(m[i], d);
                }
                if (lane < 4) {
                    sts128(sb + OFF_KEY + (t >> 5) * 128 + c * 32, make_uint4(f2u(m[0]), f2u(m[1]), f2u(m[2]), f2u(m[3])));
                    sts128(sb + OFF_KEY + (t >> 5) * 128 + c * 32 + 16, make_uint4(f2u(m[4]), f2u(m[5]), f2u(m[6]), f2u(m[7])));
                }
                bar_sync(2, 64);
            }
            if (warp == 10) {
                if (lane < 8) {
                    const uint32_t ra = sb + OFF_KEY + (lane >> 2) * 64 + c * 8;
                    const uint2 a0 = lds64(ra), a1 = lds64(ra + 128), a2 = lds64(ra + 32), a3 = lds64(ra + 160);
                    uint32_t lo = pack2(u2f(a0.x) + u2f(a1.x), u2f(a0.y) + u2f(a1.y)), hi = pack2(u2f(a2.x) + u2f(a3.x), u2f(a2.y) + u2f(a3.y));
                    if ((b >> 5) == 2) { lo = hadd2(lo, ONE2); hi = hadd2(hi, ONE2); }
                    st_ll(p.s->llmod2 + b * 8 + lane, lo, hi, 0, tag);
                }
                __syncwarp();
                TS(5);
                float sa = 0.f, sc = 0.f;
                #pragma unroll 1
                for (int j = 0; j < 8; j++) {
                    uint4 w[2];
                    const bf16* wr = p.wr + j * 128 + (lane >> 2) * 16 + 2 * c;
                    const uint32_t wr0 = ldg32(wr), wr1 = ldg32(wr + 8);
                    poll_words<2, 1>(w, p.s->llmod2 + 256 + j * 32 + lane, 256, tag);
                    const uint32_t r0 = hmul2(w[1].x, wr0), r1 = hmul2(w[1].y, wr1);
                    sa += (bf_lo(r0) + bf_hi(r0)) + (bf_lo(r1) + bf_hi(r1));
                    sc += fmaf(bf_lo(w[0].x), bf_lo(wr0), bf_hi(w[0].x) * bf_hi(wr0)) + fmaf(bf_lo(w[0].y), bf_lo(wr1), bf_hi(w[0].y) * bf_hi(wr1));
                    if (j == hg) { sts64(sb + OFF_T1 + lane * 16 + 8, r0, r1); sts128(sb + OFF_T2 + lane * 16, make_uint4(w[1].x, w[1].y, w[0].x, w[0].y)); }
                }
                {
                    uint4 w[2];
                    poll_words<2, 1>(w, p.s->llmod2 + hg * 32 + lane, 768, tag);
                    sts64(sb + OFF_T1 + lane * 16, w[0].x, w[0].y); sts64(sb + OFF_T3 + lane * 8, w[1].x, w[1].y);
                }
                #pragma unroll 1
                for (int d = 1; d < 32; d <<= 1) { sa += shfl_x(sa, d); sc += shfl_x(sc, d); }
                if (lane == 0) { sts64(sb + OFF_CST + 8, f2u(sa), f2u(sc)); mbar_arrive(BAR(B_PAR)); }
                TS(6);
                #pragma unroll 1
                for (int q = 0; q < 2; q++) {
                    mbar_wait(BAR(B_OWN + q), 0);
                    fence_async_smem();
                    if (lane < 4) { bulk_store(p.s->os + ((size_t)b * 2 + q) * 1024 + lane * 256, sb + OFF_R0 + q * 16384u + lane * 4096u, 4096); bulk_wait(); }
                    __syncwarp();
                    if (lane == 0) st_flag(p.s->flo + (b * 2 + q) * 2, tag);
                    TS(7 + q);
                }
                if (lane == 0) mbar_arrive(BAR(B_OST));
                const int e = lane & 15;
                const uint4 ta = lds128(sb + OFF_T2 + e * 16), tb = lds128(sb + OFF_T2 + 256 + e * 16);
                mbar_wait(BAR(B_KEYS), 0);
                const uint4 kk = lds128(sb + OFF_KEY + lane * 16);
                uint32_t k[4] = {kk.x, kk.y, kk.z, kk.w}, b0, b1;
                top2<4>(k, b0, b1);
                const uint32_t key = lane < 16 ? b0 : b1, cd = 127 - (key & 127u), slot = rb * 2 + (lane >> 4);
                const uint4 st = lds128(sb + OFF_ST2 + cd * 16);
                const uint32_t xa = sb + OFF_R0 + cd * 128u + ((((e >> 2) * 2) ^ (cd & 7)) << 4) + c * 4;
                const uint32_t x0 = lds32(xa), x1 = lds32(xa ^ 16), x2 = lds32(xa + 16384), x3 = lds32((xa ^ 16) + 16384);
                if (hg == 0 && e == 0) st_ll(p.s->llcand + slot, key, rb * 128 + cd, st.w, tag);
                uint4* d = p.s->llrowh + slot * 256 + hg * 32 + e;
                st_ll(d, lnmod(x0, st.x, st.y, st.z, ta.x, ta.z), lnmod(x1, st.x, st.y, st.z, ta.y, ta.w), 0, tag);
                st_ll(d + 16, lnmod(x2, st.x, st.y, st.z, tb.x, tb.z), lnmod(x3, st.x, st.y, st.z, tb.y, tb.w), 0, tag);
                st_ll(d + 8192, x0, x1, 0, tag); st_ll(d + 8192 + 16, x2, x3, 0, tag);
                if (lane == 0) { sts32(sb + OFF_CST + 16, cd | (127 - (b1 & 127u)) << 8); mbar_arrive(BAR(B_CAND)); }
                TS(9);
            } else {
                {
                    #pragma unroll 1
                    for (int i = lane; i < 128; i += 32) {
                        stg_zero(p.s->llln2 + b * 128 + i);
                        stg_zero(p.s->llrowh + (i >> 6) * 8192 + (rb * 2 + ((i >> 5) & 1)) * 256 + hg * 32 + lane);
                    }
                    if (lane < 2 && hg == 0) stg_zero(p.s->llcand + rb * 2 + lane);
                    if (ffn) {
                        #pragma unroll 1
                        for (int i = lane; i < 512; i += 32) stg_zero(p.s->lly + b * 512 + i);
                    }
                }
                poll_flags(p.s->flk + (hg * 16 + (lane & 15)) * 2, tag);
                #pragma unroll 1
                for (int q = 0; q < 2; q++) {
                    mbar_wait(BAR(B_KST + q), 0);
                    fence_async_smem();
                    if (lane == 0) {
                        bulk_reduce(p.s->kvacc + hg * 2112 + q * 1056, sb + OFF_KS, 16896);
                        bulk_wait_read();
                        if (q == 0) mbar_arrive(BAR(B_KSD));
                        bulk_wait();
                        asm volatile("fence.acq_rel.gpu;" ::: "memory");
                        st_flag(p.s->flk + (q + 1) * 256 + (hg * 16 + rb) * 2, tag);
                    }
                    __syncwarp();
                    TS(10 + q);
                }
            }
        }
    } else {
        reg_inc<232>();
        float a0[96], a1[96];
        {
            const int g = lane >> 2, c = lane & 3;
            uint4* stp = p.s->llstat + b * 16 + warp * 2 + (lane >> 4);
            if ((lane & 15) == 0) stg_zero(stp);
            if (lane == 0 && XD + XSTEP * ((warp + b) & 7) >= 900) {
                spin_until(cstart + XD + XSTEP * ((warp + b) & 7));
                mbar_arrive_tx(BAR(B_XP + warp), 4096);
                bulk_load(sb + OFF_R0 + warp * 4096u, p.x + (size_t)(b * 16 + 2 * warp) * 1024, 4096, BAR(B_XP + warp));
            }
            if (tid < 64) sts128(sb + OFF_ONES + tid * 16, make_uint4(ONE2, ONE2, ONE2, ONE2));
            if (tid == 64) sts64(sb + OFF_CST, b, tag);
            mbar_wait(BAR(B_XP + warp), 0);
            if (lane == 0) mbar_arrive(BAR(B_STP));
            if (((warp + b) & 7) == 7) TS(14);
            float s[2][4], q0[2][4], q1[2][4];
            #pragma unroll
            for (int i = 0; i < 4; i++) s[0][i] = s[1][i] = q0[0][i] = q0[1][i] = q1[0][i] = q1[1][i] = 0.f;
            #pragma unroll
            for (int i = 0; i < 4; i++) {
                const uint4 x0 = lds128(sb + OFF_R0 + warp * 4096u + (lane + 32 * i) * 16u), x1 = lds128(sb + OFF_R0 + warp * 4096u + 2048u + (lane + 32 * i) * 16u);
                mma16816(s[0], x0.x, x1.x, x0.y, x1.y, ONE2, ONE2); mma16816(s[1], x0.z, x1.z, x0.w, x1.w, ONE2, ONE2);
                mma16816(q0[0], x0.x, x1.x, x0.y, x1.y, x0.x, x0.y); mma16816(q0[1], x0.z, x1.z, x0.w, x1.w, x0.z, x0.w);
                mma16816(q1[0], x0.x, x1.x, x0.y, x1.y, x1.x, x1.y); mma16816(q1[1], x0.z, x1.z, x0.w, x1.w, x1.z, x1.w);
            }
            const bool dg = c == (g >> 1);
            const float s0 = dg ? s[0][0] + s[1][0] : 0.f, s1 = dg ? s[0][2] + s[1][2] : 0.f;
            const float sq0 = dg ? ((g & 1) ? q0[0][1] + q0[1][1] : q0[0][0] + q0[1][0]) : 0.f, sq1 = dg ? ((g & 1) ? q1[0][3] + q1[1][3] : q1[0][2] + q1[1][2]) : 0.f;
            const bool up = lane >= 16;
            float sm = (up ? s1 : s0) + shfl_x(up ? s0 : s1, 16), sq = (up ? sq1 : sq0) + shfl_x(up ? sq0 : sq1, 16);
            #pragma unroll
            for (int m = 8; m >= 1; m >>= 1) { sm += shfl_x(sm, m); sq += shfl_x(sq, m); }
            uint32_t m2, rh, rl; float rinv;
            ln_final(sm, sq, m2, rinv);
            split_rcp(rinv, rh, rl);
            if ((lane & 15) == 0) st_ll(stp, m2, rh, rl, tag);
            if (((warp + b) & 7) == 7) TS(15);
            uint4 st[2];
            poll_words<2, 0>(st, p.s->llstat + (b >> 3) * 128 + warp * 16 + g, 8, tag);
            if (lane == 0) mbar_arrive(BAR(B_STS));
            if (warp == 0) TS(16);
            const uint32_t lrow = warp * 16 + (lane & 15);
            uint32_t aad = sb + OFF_A + lrow * 128u + (((lane >> 4) ^ (lrow & 7)) << 4);
            uint32_t tad = sb + OFF_TAB + c * 16, ab = BAR(B_FA), pa = 0;
            uint32_t f0[4], f1[4];
            #define PREP(f, q) do { \
                const uint4 t = lds128(tad + (q) * 64); \
                ldsm4(f, aad ^ ((q) << 5)); \
                f[0] = lnmod(f[0], st[0].x, st[0].y, st[0].z, t.x, t.z); f[1] = lnmod(f[1], st[1].x, st[1].y, st[1].z, t.x, t.z); \
                f[2] = lnmod(f[2], st[0].x, st[0].y, st[0].z, t.y, t.w); f[3] = lnmod(f[3], st[1].x, st[1].y, st[1].z, t.y, t.w); } while (0)
            #define MMA(f, off) do { wg_fence(); mma192_rs<(off), H128>(a0, f, blo); mma192_rs<(off) + 768, H128>(a1, f, blo); wg_commit(); wg_wait<1>(); } while (0)
            mbar_wait(ab, 0);
            PREP(f0, 0);
            #pragma unroll 1
            for (int j = 0; j < 16; j++) {
                const uint32_t bb = BAR(B_FB) + (j & 1) * 16, blo = desc_lo(sb + OFF_B, 4096) + (j & 1) * 3072, pb = (j >> 1) & 1;
                mbar_wait(bb, pb);
                wg_fence(); mma192_rsp<0, H128>(a0, f0, blo, j); mma192_rsp<768, H128>(a1, f0, blo, j); wg_commit(); wg_wait<1>();
                if (lane == 0 && j) mbar_arrive((bb ^ 16) + 8 * (B_EB - B_FB) + 8);
                PREP(f1, 1);
                MMA(f1, 128);
                PREP(f0, 2);
                mbar_wait(bb + 8, pb);
                MMA(f0, 1536);
                if (lane == 0) mbar_arrive(bb + 8 * (B_EB - B_FB));
                PREP(f1, 3);
                MMA(f1, 1536 + 128);
                if (lane == 0) mbar_arrive(ab + 8 * (B_EA - B_FA));
                ab += 8; aad += 16384; tad += 256;
                if (ab == BAR(B_FA + 3)) { ab -= 24; aad -= 49152; pa ^= 1; }
                if (j < 15) mbar_wait(ab, pa);
                PREP(f0, 0);
            }
            #undef PREP
            #undef MMA
        }
        int tid_o; asm volatile("mov.u32 %0, %%tid.x;" : "=r"(tid_o) :: "memory");
        const int tid = tid_o, lane = tid & 31, warp = __shfl_sync(0xffffffffu, tid >> 5, 0), wgi = warp >> 2, w4 = warp & 3, g = lane >> 2, c = lane & 3;
        const uint32_t srow = warp * 16 + (lane & 15);
        const uint32_t t128 = srow * 128u + (((lane >> 4) ^ (srow & 7)) << 4);
        mbar_wait(BAR(B_WPHI), 0);
        wg_wait<0>();
        acc_fence(a0); acc_fence(a1);
        if (lane == 0) mbar_arrive(BAR(B_QE));
        if (warp == 0) TS(18);
        uint32_t ph0[16], ph1[16], pk[16];
        {
            uint32_t kq[48];
            float p0[16], p1[16];
            const uint32_t dw = desc_lo(sb + OFF_WPHI, 16);
            #define PMMA(f, dw) do { mma32_rs0<0, H64>(p0, f, dw); mma32_rs0<128, H64>(p1, f + 8, dw); mma32_rs<64, H64>(p0, f + 4, dw); mma32_rs<192, H64>(p1, f + 12, dw); } while (0)
            #pragma unroll
            for (int i = 0; i < 16; i++) ph0[i] = pack2(a0[64 + 2 * i], a0[65 + 2 * i]);
            wg_fence();
            PMMA(ph0, dw);
            wg_commit();
            #pragma unroll
            for (int i = 0; i < 16; i++) kq[i] = pack2(a1[2 * i], a1[2 * i + 1]);
            #pragma unroll
            for (int i = 0; i < 32; i++) kq[16 + i] = pack2(a0[2 * i], a0[2 * i + 1]);
            mbar_wait(BAR(B_QE), 0);
            #pragma unroll
            for (int i = 0; i < 8; i++) {
                const int o = 32 + 8 * i;
                stsm4(sb + OFF_V + (i >> 1) * 8192u + srow * 64u + (((2 * (i & 1) + (lane >> 4)) ^ ((srow >> 1) & 3)) << 4),
                      pack2(a1[o], a1[o + 1]), pack2(a1[o + 2], a1[o + 3]), pack2(a1[o + 4], a1[o + 5]), pack2(a1[o + 6], a1[o + 7]));
            }
            wg_wait<0>();
            acc_fence(p0); acc_fence(p1);
            #pragma unroll
            for (int i = 0; i < 8; i++) { pk[i] = pack2(p0[2 * i], p0[2 * i + 1]); pk[8 + i] = pack2(p1[2 * i], p1[2 * i + 1]); }
            if (warp == 0) TS(19);
            #pragma unroll 1
            for (int u = 0; u < 3; u++) {
                float okv[20];
                const uint32_t vb = OFF_V + ((u & 2) + wgi) * 8192u;
                const uint32_t dp = desc_lo(sb + OFF_PHI + wgi * 16384u, 16), dv = desc_lo(sb + vb, OFF_ONES - vb), dn = dw + (~u & 1) * 256;
                fence_async_smem();
                wg_fence();
                #define KVS(i) mma40_tt<(i) * 128, H128, (i) * (64u - (64u << 16)), H64>(okv, dp, dv)
                mma40_tt0<0, H128, 0, H64>(okv, dp, dv); KVS(1); KVS(2); KVS(3); KVS(4); KVS(5); KVS(6); KVS(7);
                #undef KVS
                PMMA(kq, dn);
                wg_commit();
                feature_map(pk, ph0);
                wg_wait<0>();
                acc_fence(okv); acc_fence(p0); acc_fence(p1);
                if (u) {
                    if (u == 2) { if (lane == 0) mbar_arrive(BAR(B_VF)); mbar_wait(BAR(B_KSD), 0); }
                    const uint32_t ks = sb + OFF_KS + wgi * 8448u;
                    #pragma unroll
                    for (int k = 0; k < 4; k++) sts128(ks + (k * 128 + (tid & 127)) * 16u, make_uint4(f2u(okv[4 * k]), f2u(okv[4 * k + 1]), f2u(okv[4 * k + 2]), f2u(okv[4 * k + 3])));
                    if (c == 0) sts64(ks + 8192u + (w4 * 8 + g) * 8u, f2u(okv[16]), f2u(okv[18]));
                    __syncwarp();
                    if (lane == 0) mbar_arrive(BAR(B_KST - 1) + u * 8);
                    if (warp == 0) TS(19 + u);
                }
                feature_map(pk + 8, ph1);
                #pragma unroll
                for (int i = 0; i < 8; i++) { pk[i] = pack2(p0[2 * i], p0[2 * i + 1]); pk[8 + i] = pack2(p1[2 * i], p1[2 * i + 1]); }
                #pragma unroll
                for (int i = 0; i < 32; i++) kq[i] = kq[i + 16];
                if (u < 2) {
                    if (u) mbar_wait(BAR(B_KST), 0);
                    #pragma unroll
                    for (int q = 0; q < 4; q++) {
                        const uint32_t a = (sb + OFF_PHI + t128) ^ (q << 5);
                        stsm4(a, ph0[4 * q], ph0[4 * q + 1], ph0[4 * q + 2], ph0[4 * q + 3]);
                        stsm4(a + 16384, ph1[4 * q], ph1[4 * q + 1], ph1[4 * q + 2], ph1[4 * q + 3]);
                    }
                    bar_sync(1, 256);
                }
                if (warp == 0) TS(22 + u);
            }
            #undef PMMA
        }
        uint32_t gf[16][4], uf[16][4];
        const uint32_t fo = (warp >> 1) * 16384u + ((lane & 7) + (lane >> 4) * 8) * 64u + (((2 * (warp & 1) + ((lane >> 3) & 1)) ^ ((lane >> 1) & 3)) << 4);
        mbar_wait(BAR(B_GF), 0);
        #pragma unroll
        for (int i = 0; i < 16; i++) ldsm4t(gf[i], sb + OFF_R0 + fo + i * 1024u);
        #define O_BLOCK(pp) do { \
            const uint32_t kl = sb + ((pp) ? OFF_KS : OFF_PHI) + wgi * 8448u, f = w4 * 16 + g; \
            mbar_wait(BAR(B_KVL + (pp)), 0); \
            if (warp == 0) TS(25 + 3 * (pp)); \
            _Pragma("unroll") for (int k = 0; k < 4; k++) { \
                const uint4 v = lds128(kl + (k * 128 + (tid & 127)) * 16u); \
                const uint32_t a = sb + OFF_KVT + wgi * 4096u + f * 64u + ((k ^ ((g >> 1) & 3)) << 4) + 4 * c; \
                sts32(a, pack2(u2f(v.x), u2f(v.y))); sts32(a + 512, pack2(u2f(v.z), u2f(v.w))); \
            } \
            if (c < 2) {          \
                const float z = ldsf(kl + 8192u + (w4 * 8 + g) * 8u + c * 4); \
                const uint32_t zz = pack2(z, z); \
                sts128(sb + OFF_Z + (f + 8 * c) * 64u + ((wgi ^ ((g >> 1) & 3)) << 4), make_uint4(zz, zz, zz, zz)); \
            } \
            bar_sync(1, 256); \
            if (!(pp) && lane == 0) mbar_arrive(BAR(B_KVC)); \
            fence_async_smem(); \
            float o0[20], o1[20]; \
            const uint32_t dk = desc_lo(sb + OFF_KVT, OFF_Z - OFF_KVT); \
            constexpr uint32_t K1 = 256u - (255u << 16);          \
            wg_fence(); \
            mma40_rs0<0, H64>(o0, ph0, dk); mma40_rs0<K1, H64>(o1, ph1, dk); \
            mma40_rs<64, H64>(o0, ph0 + 4, dk); mma40_rs<K1 + 64, H64>(o1, ph1 + 4, dk); \
            mma40_rs<128, H64>(o0, ph0 + 8, dk); mma40_rs<K1 + 128, H64>(o1, ph1 + 8, dk); \
            mma40_rs<192, H64>(o0, ph0 + 12, dk); mma40_rs<K1 + 192, H64>(o1, ph1 + 12, dk); \
            wg_commit(); \
            wg_wait<0>(); \
            acc_fence(o0); acc_fence(o1); \
            if (warp == 0) TS(26 + 3 * (pp)); \
            _Pragma("unroll") for (int hh = 0; hh < 2; hh++) { \
                const float (&o)[20] = hh ? o1 : o0; \
                uint32_t h0, l0, h1, l1; \
                split_rcp(rcp(rbf(rbf(o[16]) + 1e-6f)), h0, l0); split_rcp(rcp(rbf(rbf(o[18]) + 1e-6f)), h1, l1); \
                _Pragma("unroll") for (int q = 0; q < 2; q++) \
                    stsm4((sb + OFF_R0 + (pp) * 16384u + t128) ^ ((2 * hh + q) << 5), hdiv2(pack2(o[8 * q], o[8 * q + 1]), h0, l0), hdiv2(pack2(o[8 * q + 2], o[8 * q + 3]), h1, l1), \
                          hdiv2(pack2(o[8 * q + 4], o[8 * q + 5]), h0, l0), hdiv2(pack2(o[8 * q + 6], o[8 * q + 7]), h1, l1)); \
            } \
            __syncwarp(); \
            if (lane == 0) mbar_arrive(BAR(B_OWN + (pp))); \
            if (warp == 0) TS(27 + 3 * (pp)); \
            mbar_wait(BAR(B_OWN + (pp)), 0); \
            fence_async_smem(); \
        } while (0)
        float acc[64];
        const uint32_t da = desc_lo(sb + OFF_R0 + wgi * 8192u, 16), db = desc_lo(sb + OFF_DB, 8192);
        #define D_MMA(first, s) do { \
            wg_fence(); \
            first<(s) * 1024, H128, (s) * 1024, H128>(acc, da, db); mma128_ss<(s) * 1024 + 2, H128, (s) * 1024 + 128, H128>(acc, da, db); \
            mma128_ss<(s) * 1024 + 4, H128, (s) * 1024 + 256, H128>(acc, da, db); mma128_ss<(s) * 1024 + 6, H128, (s) * 1024 + 384, H128>(acc, da, db); \
            wg_commit(); } while (0)
        O_BLOCK(0);
        mbar_wait(BAR(B_FD), 0);
        D_MMA(mma128_ss0, 0);
        feature_map(pk, ph0);
        wg_wait<0>();
        if (lane == 0) mbar_arrive(BAR(B_ED));
        feature_map(pk + 8, ph1);
        O_BLOCK(1);
        #undef O_BLOCK
        #define D_STEP(n) do { \
            mbar_wait(BAR(B_FD + ((n) & 3)), ((n) >> 2) & 1); \
            if (warp == 0) TR(112 + (n)); \
            D_MMA(mma128_ss, (n) & 3); \
            if ((n) == 3) mbar_wait(BAR(B_UF), 0); \
            if ((n) >= 3 && (n) < 11) { ldsm4t(uf[2 * (((n) + 5) & 7)], sb + OFF_F2 + fo + (((n) + 5) & 7) * 2048u); ldsm4t(uf[2 * (((n) + 5) & 7) + 1], sb + OFF_F2 + fo + (((n) + 5) & 7) * 2048u + 1024u); } \
            wg_wait<1>(); \
            if ((n) > 1 && lane == 0) mbar_arrive(BAR(B_ED + (((n) + 3) & 3))); } while (0)
        D_STEP(1); D_STEP(2);
        if (warp == 0) TS(31);
        D_STEP(3); D_STEP(4); D_STEP(5); D_STEP(6); D_STEP(7); D_STEP(8); D_STEP(9); D_STEP(10); D_STEP(11); D_STEP(12); D_STEP(13); D_STEP(14); D_STEP(15);
        #undef D_STEP
        #undef D_MMA
        mbar_wait(BAR(B_PAR), 0);
        mbar_wait(BAR(B_FD), 0); mbar_wait(BAR(B_FD + 1), 0);
        wg_wait<0>();
        acc_fence(acc);
        if (lane == 0) mbar_arrive(BAR(B_ED + 3));
        if (warp == 0) TS(32);
        uint32_t x2[8][4];
        const uint4 cst = lds128(sb + OFF_CST);
        const int b = cst.x;
        const uint32_t tag = cst.y;
        {
            float sd[4] = {0.f, 0.f, 0.f, 0.f}, qa[4] = {0.f, 0.f, 0.f, 0.f}, qb[4] = {0.f, 0.f, 0.f, 0.f};
            #pragma unroll
            for (int i = 0; i < 8; i++) {
                const uint4 t = lds128(sb + OFF_T1 + i * 64 + c * 16);
                ldsm4(x2[i], (sb + OFF_R0 + (i >> 2) * 16384u + t128) ^ ((i & 3) << 5));
                x2[i][0] = hadd2(x2[i][0], hmul2(t.x, pack2(acc[8 * i], acc[8 * i + 1]))); x2[i][1] = hadd2(x2[i][1], hmul2(t.x, pack2(acc[8 * i + 2], acc[8 * i + 3])));
                x2[i][2] = hadd2(x2[i][2], hmul2(t.y, pack2(acc[8 * i + 4], acc[8 * i + 5]))); x2[i][3] = hadd2(x2[i][3], hmul2(t.y, pack2(acc[8 * i + 6], acc[8 * i + 7])));
                mma16816(sd, x2[i][0], x2[i][1], x2[i][2], x2[i][3], (g & 1) ? t.z : ONE2, (g & 1) ? t.w : ONE2);
                mma16816(qa, x2[i][0], x2[i][1], x2[i][2], x2[i][3], x2[i][0], x2[i][2]);
                mma16816(qb, x2[i][0], x2[i][1], x2[i][2], x2[i][3], x2[i][1], x2[i][3]);
            }
            if (c == (g >> 1)) {
                uint4* d = p.s->llln2 + b * 128 + warp * 16 + g;
                st_ll(d, f2u(sd[0]), f2u((g & 1) ? qa[1] : qa[0]), f2u(sd[1]), tag);
                st_ll(d + 8, f2u(sd[2]), f2u((g & 1) ? qb[3] : qb[2]), f2u(sd[3]), tag);
            }
        }
        if (warp == 0) TS(33);
        #pragma unroll
        for (int i = 0; i < 8; i++) stsm4((sb + OFF_R0 + (i >> 2) * 16384u + t128) ^ ((i & 3) << 5), x2[i][0], x2[i][1], x2[i][2], x2[i][3]);
        {
            uint4 w[4];
            const uint32_t rl = warp * 16 + g + 8 * (c & 1);
            poll_words<4, 0>(w, p.s->llln2 + ((b & ~7) + (c >> 1) * 4) * 128 + rl, 128, tag);
            float s1 = (u2f(w[0].x) + u2f(w[1].x)) + (u2f(w[2].x) + u2f(w[3].x));
            float s2 = (u2f(w[0].y) + u2f(w[1].y)) + (u2f(w[2].y) + u2f(w[3].y));
            float dt = (u2f(w[0].z) + u2f(w[1].z)) + (u2f(w[2].z) + u2f(w[3].z));
            s1 += shfl_x(s1, 2); s2 += shfl_x(s2, 2); dt += shfl_x(dt, 2);
            uint32_t m2, rh, rl2; float rinv;
            ln_final(s1, s2, m2, rinv);
            split_rcp(rinv, rh, rl2);
            const float rkey = fmaf(fmaf(-bf_lo(m2), u2f(cst.z), dt), rinv, u2f(cst.w));
            if (c < 2) { sts32(sb + OFF_KEY + rl * 4, (f2key(rkey) & ~127u) | (127 - rl)); sts128(sb + OFF_ST2 + rl * 16, make_uint4(m2, rh, rl2, f2u(rkey))); }
            __syncwarp();
            if (lane == 0) mbar_arrive(BAR(B_KEYS));
        }
        if (warp == 0) TS(34);
        {
            const uint4 s0 = lds128(sb + OFF_ST2 + (warp * 16 + g) * 16), s1 = lds128(sb + OFF_ST2 + (warp * 16 + g + 8) * 16);
            mbar_wait(BAR(B_ED + 3), 1);
            const uint32_t oa = sb + OFF_OUT + warp * 2048u + t128;
            #pragma unroll
            for (int i = 0; i < 8; i++) {
                const uint4 t = lds128(sb + OFF_T2 + i * 64 + c * 16);
                const uint2 gb = lds64(sb + OFF_T3 + i * 32 + c * 8);
                stsm4((oa + (i >> 2) * 2048u) ^ ((i & 3) << 5),
                      hadd2(x2[i][0], hmul2(gb.x, lnmod(x2[i][0], s0.x, s0.y, s0.z, t.x, t.z))), hadd2(x2[i][1], hmul2(gb.x, lnmod(x2[i][1], s1.x, s1.y, s1.z, t.x, t.z))),
                      hadd2(x2[i][2], hmul2(gb.y, lnmod(x2[i][2], s0.x, s0.y, s0.z, t.y, t.w))), hadd2(x2[i][3], hmul2(gb.y, lnmod(x2[i][3], s1.x, s1.y, s1.z, t.y, t.w))));
            }
            __syncwarp();
            if (lane == 0) mbar_arrive(BAR(B_SWP));
        }
        if (warp == 0) TS(35);
        uint32_t df[16][4];
        mbar_wait(BAR(B_WD), 0);
        #pragma unroll
        for (int i = 0; i < 16; i++)
            ldsm4t(df[i], (sb + OFF_F2 + warp * 8192u + (i >> 3) * 4096u + (i & 1) * 2048u + ((lane & 7) + (lane >> 4) * 8) * 128u + ((((lane >> 3) & 1) ^ (lane & 7)) << 4)) ^ (((i >> 1) & 3) << 5));
        uint32_t fx = 0, fh = 0, fg = 0, frow, fr;
        {
            uint4 v[1];
            poll_words<1, 0>(v, p.s->llcand + lane, 0, tag);
            uint32_t k[1] = {(v[0].x & ~127u) | (63 - lane)}, b0, b1;
            top2<1>(k, b0, b1);
            if (warp == 0) TS(36);
            const uint32_t slot0 = 63 - (b0 & 127u), slot1 = 63 - (b1 & 127u), slot = (g & 1) ? slot1 : slot0;
            frow = __shfl_sync(0xffffffffu, v[0].y, slot); fr = __shfl_sync(0xffffffffu, v[0].z, slot);
            const int wd = b * 2 + (c >> 1);
            uint4 hv[2], fv[3];
            #pragma unroll 1
            for (int it = 0; it < POLL_MAX; it++) {
                hv[0] = ld_ll(p.s->llrowh + slot0 * 256 + tid); hv[1] = ld_ll(p.s->llrowh + slot1 * 256 + tid);
                bool ok = true;
                if (warp == 0) {
                    fv[0] = ld_ll(p.s->llrowx + slot * 256 + wd); fv[1] = ld_ll(p.s->llrowh + slot * 256 + wd); fv[2] = ld_ll(p.s->llmod2 + 768 + wd);
                    ok = ll_ok<1>(fv[0], tag) && ll_ok<1>(fv[1], tag) && ll_ok<1>(fv[2], tag);
                    fx = (g & 2) ? fv[0].y : fv[0].x; fh = (g & 2) ? fv[1].y : fv[1].x; fg = (g & 2) ? fv[2].y : fv[2].x;
                }
                if (__all_sync(0xffffffffu, ok && ll_ok<1>(hv[0], tag) && ll_ok<1>(hv[1], tag))) break;
            }
            const uint32_t ha = sb + OFF_HSEL + (tid >> 3) * 128u + c * 16u + (g & 1) * 8u;
            sts64(ha, hv[0].x, hv[0].y); sts64(ha + 64, hv[1].x, hv[1].y);
            if (warp == 0) {
                if (lane < 8 && c == 0) sts32(sb + OFF_CST + 24 + g * 4, frow);
                __syncwarp();
                if (lane == 0) mbar_arrive(BAR(B_XP));
            }
        }
        bar_sync(2 + (warp >> 1), 64);
        if (warp == 0) TS(37);
        {
            float ag[2][4], au[2][4];
            #pragma unroll
            for (int i = 0; i < 4; i++) ag[0][i] = ag[1][i] = au[0][i] = au[1][i] = 0.f;
            #pragma unroll
            for (int i = 0; i < 8; i++) {
                const uint4 h = lds128(sb + OFF_HSEL + (warp >> 1) * 1024u + i * 128u + (lane & 7) * 16u);
                mma16816(ag[0], gf[2 * i][0], gf[2 * i][1], gf[2 * i][2], gf[2 * i][3], h.x, h.y);
                mma16816(au[0], uf[2 * i][0], uf[2 * i][1], uf[2 * i][2], uf[2 * i][3], h.x, h.y);
                mma16816(ag[1], gf[2 * i + 1][0], gf[2 * i + 1][1], gf[2 * i + 1][2], gf[2 * i + 1][3], h.z, h.w);
                mma16816(au[1], uf[2 * i + 1][0], uf[2 * i + 1][1], uf[2 * i + 1][2], uf[2 * i + 1][3], h.z, h.w);
            }
            sts64(sb + OFF_RED + (warp >> 1) * 512u + (c & 1) * 256u + ((warp & 1) * 16 + (c >> 1) * 8 + g) * 8u,
                  f2u(sel4(c, ag[0][0], ag[0][1], ag[0][2], ag[0][3]) + sel4(c, ag[1][0], ag[1][1], ag[1][2], ag[1][3])),
                  f2u(sel4(c, au[0][0], au[0][1], au[0][2], au[0][3]) + sel4(c, au[1][0], au[1][1], au[1][2], au[1][3])));
        }
        bar_sync(1, 256);
        {
            const uint32_t ra = sb + OFF_RED + lane * 16u;
            const uint4 r0 = lds128(ra), r1 = lds128(ra + 512), r2 = lds128(ra + 1024), r3 = lds128(ra + 1536);
            #define F4(f) ((u2f(r0.f) + u2f(r1.f)) + (u2f(r2.f) + u2f(r3.f)))
            const uint32_t hid = hmul2(silu2(pack2(F4(x), F4(z))), pack2(F4(y), F4(w)));
            #undef F4
            if (warp == 0) TS(38);
            const int src = (g & 1) * 16 + c;
            const uint32_t b0 = __shfl_sync(0xffffffffu, hid, src), b1 = __shfl_sync(0xffffffffu, hid, src + 4), b2 = __shfl_sync(0xffffffffu, hid, src + 8), b3 = __shfl_sync(0xffffffffu, hid, src + 12);
            float y[8][4];
            #pragma unroll
            for (int i = 0; i < 8; i++) {
                y[i][0] = y[i][1] = y[i][2] = y[i][3] = 0.f;
                mma16816(y[i], df[2 * i][0], df[2 * i][1], df[2 * i][2], df[2 * i][3], b0, b1);
            }
            #pragma unroll
            for (int i = 0; i < 8; i++) mma16816(y[i], df[2 * i + 1][0], df[2 * i + 1][1], df[2 * i + 1][2], df[2 * i + 1][3], b2, b3);
            if (b < 112) {
                #pragma unroll
                for (int h = 0; h < 2; h++) {
                    #define YS(e) sel4(c, y[4 * h][e], y[4 * h + 1][e], y[4 * h + 2][e], y[4 * h + 3][e])
                    st_ll4(p.s->lly + b * 512 + (warp * 8 + 4 * h + c) * 8 + g, YS(0), YS(1), YS(2), YS(3), tag);
                    #undef YS
                }
            }
        }
        if (warp == 0) TS(39);
        if (warp < 7) {
            uint4 v[2];
            poll_words4<2>(v, p.s->lly + (tid >> 2) * 512 + b * 4 + c, 56 * 512, tag);
            float y0 = u2f(v[0].x) + u2f(v[1].x), y1 = u2f(v[0].y) + u2f(v[1].y), y2 = u2f(v[0].z) + u2f(v[1].z), y3 = u2f(v[0].w) + u2f(v[1].w);
            const bool g0 = g & 1, g1 = g & 2;
            const float k0 = (g0 ? y1 : y0) + shfl_x(g0 ? y0 : y1, 4), k1 = (g0 ? y3 : y2) + shfl_x(g0 ? y2 : y3, 4);
            float y = (g1 ? k1 : k0) + shfl_x(g1 ? k0 : k1, 8);
            y += shfl_x(y, 16);
            if (lane < 16) stsf(sb + OFF_RED2 + lane * 32u + warp * 4u, y);
            bar_sync(6, 224);
            if (tid < 16) {
                const uint4 ya = lds128(sb + OFF_RED2 + lane * 32u), yb = lds128(sb + OFF_RED2 + lane * 32u + 16);
                y = ((u2f(ya.x) + u2f(ya.y)) + (u2f(ya.z) + u2f(ya.w))) + ((u2f(yb.x) + u2f(yb.y)) + u2f(yb.z));
                const float sg = sigmoid_f(rbf(u2f(fr)));
                const uint32_t o = hadd2(fx, hmul2(fg, hadd2(fh, hmul2(pack2(y, y), pack2(sg, sg)))));
                ((uint16_t*)p.out)[(size_t)frow * 1024 + (b >> 1) * 16 + (b & 1) * 4 + c + 8 * (g >> 1)] = (c & 1) ? o >> 16 : o;
                if (b == 0 && tid == 0) p.s->done[0] = tag;
                TS(40);
            }
        }
    }
}

typedef CUresult (*EncodeFn)(CUtensorMap*, CUtensorMapDataType, cuuint32_t, void*, const cuuint64_t*, const cuuint64_t*, const cuuint32_t*,
                             const cuuint32_t*, CUtensorMapInterleave, CUtensorMapSwizzle, CUtensorMapL2promotion, CUtensorMapFloatOOBfill);

CUtensorMap make_map(EncodeFn enc, const void* ptr, uint64_t cols, uint64_t rows, uint32_t bc, uint32_t br, CUtensorMapSwizzle swz, CUtensorMapL2promotion promo) {
    CUtensorMap m;
    cuuint64_t dims[2] = {cols, rows}, strides[1] = {cols * 2};
    cuuint32_t box[2] = {bc, br}, es[2] = {1, 1};
    enc(&m, CU_TENSOR_MAP_DATA_TYPE_BFLOAT16, 2, const_cast<void*>(ptr), dims, strides, box, es, CU_TENSOR_MAP_INTERLEAVE_NONE, swz, promo,
        CU_TENSOR_MAP_FLOAT_OOB_FILL_NONE);
    return m;
}
CUtensorMap make_map4(EncodeFn enc, const void* ptr, uint32_t groups, uint64_t rows, uint32_t br, CUtensorMapL2promotion promo) {
    CUtensorMap m;
    cuuint64_t dims[4] = {64, rows, 16, groups}, strides[3] = {groups * 2048ull, 128, 2048};
    cuuint32_t box[4] = {64, br, 2, groups}, es[4] = {1, 1, 1, 1};
    enc(&m, CU_TENSOR_MAP_DATA_TYPE_BFLOAT16, 4, const_cast<void*>(ptr), dims, strides, box, es, CU_TENSOR_MAP_INTERLEAVE_NONE, CU_TENSOR_MAP_SWIZZLE_128B, promo,
        CU_TENSOR_MAP_FLOAT_OOB_FILL_NONE);
    return m;
}

}

extern "C" void kernel_launch(void* const* d_in, const int* in_sizes, int n_in, void* d_out, int out_size) {
    (void)in_sizes; (void)n_in; (void)out_size;
    void* fn = nullptr; cudaDriverEntryPointQueryResult qr;
    cudaGetDriverEntryPoint("cuTensorMapEncodeTiled", &fn, cudaEnableDefault, &qr);
    EncodeFn enc = (EncodeFn)fn;
    void* hs = nullptr;
    cudaGetSymbolAddress(&hs, g_scratch);
    int dev = 0, sms = 0;
    cudaGetDevice(&dev);
    cudaDeviceGetAttribute(&sms, cudaDevAttrMultiProcessorCount, dev);
    const CUtensorMapL2promotion P256 = CU_TENSOR_MAP_L2_PROMOTION_L2_256B, P128 = CU_TENSOR_MAP_L2_PROMOTION_L2_128B, P0 = CU_TENSOR_MAP_L2_PROMOTION_NONE;
    CUtensorMap tmW = make_map4(enc, d_in[1], 3, 1024, 32, P256);
    CUtensorMap tmWo = make_map4(enc, d_in[3], 1, 1024, 64, P256);
    CUtensorMap tmO = make_map4(enc, d_out, 1, 2048, 16, P0);
    CUtensorMap tmPhi = make_map(enc, d_in[2], 32, 1024, 32, 128, CU_TENSOR_MAP_SWIZZLE_64B, P128);
    CUtensorMap tmG = make_map(enc, d_in[6], 3584, 1024, 32, 128, CU_TENSOR_MAP_SWIZZLE_64B, P0);
    CUtensorMap tmU = make_map(enc, d_in[7], 3584, 1024, 32, 128, CU_TENSOR_MAP_SWIZZLE_64B, P0);
    CUtensorMap tmD = make_map(enc, d_in[8], 1024, 3584, 64, 32, CU_TENSOR_MAP_SWIZZLE_128B, P128);
    CUtensorMap tmX = make_map(enc, d_in[0], 1024, 2048, 64, 128, CU_TENSOR_MAP_SWIZZLE_128B, P128);
    CUtensorMap tmM = make_map(enc, d_in[10], 6144, 1024, 64, 256, CU_TENSOR_MAP_SWIZZLE_128B, P128);
    Ptrs p;
    p.x = (const bf16*)d_in[0]; p.c = (const bf16*)d_in[9]; p.wmod = (const bf16*)d_in[10]; p.wr = (const bf16*)d_in[5];
    p.wg = (const bf16*)d_in[6]; p.wu = (const bf16*)d_in[7]; p.wd = (const bf16*)d_in[8]; p.out = (bf16*)d_out; p.s = (Scratch*)hs;
    p.wqkv = (const bf16*)d_in[1]; p.wo = (const bf16*)d_in[3];
    p.by_sm = sms == 132;
    cudaFuncSetAttribute(fused_kernel, cudaFuncAttributeMaxDynamicSharedMemorySize, SMEM_BYTES);
    fused_kernel<<<132, NTHREADS, SMEM_BYTES, cudaStreamPerThread>>>(p, tmM, tmX, tmW, tmWo, tmPhi, tmG, tmU, tmD, tmO);
}
```

```cpp
#include <cuda_runtime.h>
#include <cuda.h>
#include <cuda_bf16.h>
#include <stdint.h>

namespace {

typedef __nv_bfloat16 bf16;

constexpr int NTHREADS = 512;
constexpr int POLL_MAX = 400000;

constexpr uint32_t OFF_R0   = 0;
constexpr uint32_t OFF_A    = 65536;
constexpr uint32_t OFF_B    = 114688;
constexpr uint32_t OFF_V    = 65536;
constexpr uint32_t OFF_PHI  = 98304;
constexpr uint32_t OFF_F2   = 65536;
constexpr uint32_t OFF_DB   = 131072;
constexpr uint32_t OFF_KL   = 196608;
constexpr uint32_t OFF_WPHI = 214016;
constexpr uint32_t OFF_KVT  = OFF_WPHI;
constexpr uint32_t OFF_Z    = 222208;
constexpr uint32_t OFF_TAB  = OFF_Z;
constexpr uint32_t OFF_ONES = 226304;
constexpr uint32_t OFF_BAR  = 227328;
constexpr uint32_t OFF_CST  = OFF_BAR + 640;
constexpr uint32_t OFF_T1   = OFF_CST + 64;
constexpr uint32_t OFF_T2   = OFF_T1 + 512;
constexpr uint32_t OFF_T3   = OFF_T2 + 512;
constexpr uint32_t OFF_KEY  = OFF_T3 + 256;
constexpr uint32_t OFF_ST2  = OFF_KEY + 512;
constexpr uint32_t OFF_ZS   = OFF_ST2;
constexpr uint32_t SMEM_BYTES = 232448;
constexpr uint32_t OFF_OUT  = OFF_R0 + 32768;
constexpr uint32_t OFF_HSEL = OFF_KL;
constexpr uint32_t OFF_RED  = OFF_KL + 4096;
constexpr uint32_t OFF_RED2 = OFF_RED + 2048;
static_assert(OFF_ST2 + 2048 <= SMEM_BYTES, "layout");

enum {
    B_O1 = 0, B_UF = 1, B_UD = 2, B_WPHI = 3, B_FB = 4  , B_OST = 8, B_GF = 9, B_WD = 10, B_KVL = 11  , B_KZ = 13, B_LMF = 14, B_SEL = 15, B_XP = 16  , B_TAG = 24,
    B_FA = 25  , B_FD = 30  , B_CAND = 34,
    B_PE = 35  , B_KST = 37  , B_KVT = 41  , B_LMD = 43, B_PAR = 44,
    B_EA = 45  , B_EB = 48  , B_ED = 52  , B_PF = 56  , B_OWN = 60  , B_QE = 62, B_STP = 63, B_KEYS = 64, B_SWP = 65, B_STS = 66
};

struct Scratch {
    uint4 os[16 * 16 * 1024];
    uint4 kvacc[8 * 4 * 528];
    uint4 flk[3 * 128 * 2];
    uint4 llstat[2048];
    uint4 llm1[16 * 64];
    uint4 flo[16 * 16 * 2];
    uint4 llmod2[2 * 256];
    uint4 llg[2 * 4 * 256];
    uint4 llln2[16 * 8 * 128];
    uint4 llcand[16 * 2];
    uint4 llrowh[32 * 256];
    uint4 llrowx[32 * 256];
    uint4 lly[128 * 512];
    unsigned done[4];
};
__device__ __align__(1024) Scratch g_scratch;
#define TS(i) do {} while (0)
#define TR(i) do {} while (0)

__device__ __forceinline__ uint32_t smem_u32(const void* p) { return (uint32_t)__cvta_generic_to_shared(p); }
__device__ __forceinline__ uint32_t clk32() { uint32_t c; asm volatile("mov.u32 %0, %%clock;" : "=r"(c) :: "memory"); return c; }
__device__ __forceinline__ void spin_until(uint32_t t) { while ((int)(clk32() - t) < 0) {} }
__device__ __forceinline__ void sleep_until(uint32_t t) { while ((int)(clk32() - t) < 0) __nanosleep(40); }
__device__ __forceinline__ void mbar_init_fence() { asm volatile("fence.mbarrier_init.release.cluster;" ::: "memory"); }
__device__ __forceinline__ void mbar_wait(uint32_t bar, uint32_t parity) {
    asm volatile("{\n.reg .pred P1;\nLAB_WAIT:\nmbarrier.try_wait.parity.shared::cta.b64 P1, [%0], %1;\n@!P1 bra LAB_WAIT;\n}" :: "r"(bar), "r"(parity) : "memory");
}
__device__ __forceinline__ uint64_t policy_evict_first() { uint64_t p; asm("createpolicy.fractional.L2::evict_first.b64 %0, 1.0;" : "=l"(p)); return p; }
#define ELECT "{\n.reg .pred e;\nelect.sync _|e, 0xffffffff;\n@e "
__device__ __forceinline__ void e_arrive(uint32_t bar) { asm volatile(ELECT "mbarrier.arrive.shared::cta.b64 _, [%0];\n}" :: "r"(bar) : "memory"); }
__device__ __forceinline__ void e_arrive_tx(uint32_t bar, uint32_t bytes) { asm volatile(ELECT "mbarrier.arrive.expect_tx.shared::cta.b64 _, [%0], %1;\n}" :: "r"(bar), "r"(bytes) : "memory"); }
__device__ __forceinline__ void e_init(uint32_t bar, uint32_t cnt) { asm volatile(ELECT "mbarrier.init.shared::cta.b64 [%0], %1;\n}" :: "r"(bar), "r"(cnt) : "memory"); }
__device__ __forceinline__ void tma_load_ef(uint32_t dst, const CUtensorMap* tm, int c0, int c1, uint32_t bar) {
    asm volatile(ELECT "cp.async.bulk.tensor.2d.shared::cluster.global.mbarrier::complete_tx::bytes.L2::cache_hint [%0], [%1, {%3, %4}], [%2], %5;\n}"
        :: "r"(dst), "l"(tm), "r"(bar), "r"(c0), "r"(c1), "l"(policy_evict_first()) : "memory");
}
__device__ __forceinline__ void tma_load(uint32_t dst, const CUtensorMap* tm, int c0, int c1, uint32_t bar) {
    asm volatile(ELECT "cp.async.bulk.tensor.2d.shared::cluster.global.mbarrier::complete_tx::bytes [%0], [%1, {%3, %4}], [%2];\n}"
        :: "r"(dst), "l"(tm), "r"(bar), "r"(c0), "r"(c1) : "memory");
}
__device__ __forceinline__ void tma_load4(uint32_t dst, const CUtensorMap* tm, int row, int blk, uint32_t bar) {
    asm volatile(ELECT "cp.async.bulk.tensor.4d.shared::cluster.global.mbarrier::complete_tx::bytes [%0], [%1, {0, %3, %4, 0}], [%2];\n}"
        :: "r"(dst), "l"(tm), "r"(bar), "r"(row), "r"(blk) : "memory");
}
__device__ __forceinline__ void tma_store4(const CUtensorMap* tm, int row, int blk, uint32_t src) {
    asm volatile(ELECT "cp.async.bulk.tensor.4d.global.shared::cta.bulk_group [%0, {0, %2, %3, 0}], [%1];\n}" :: "l"(tm), "r"(src), "r"(row), "r"(blk) : "memory");
}
__device__ __forceinline__ void bulk_load(uint32_t dst, const void* src, uint32_t bytes, uint32_t bar) {
    asm volatile(ELECT "cp.async.bulk.shared::cluster.global.mbarrier::complete_tx::bytes [%0], [%1], %2, [%3];\n}" :: "r"(dst), "l"(src), "r"(bytes), "r"(bar) : "memory");
}
__device__ __forceinline__ void bulk_store(void* dst, uint32_t src, uint32_t bytes) {
    asm volatile(ELECT "cp.async.bulk.global.shared::cta.bulk_group [%0], [%1], %2;\n}" :: "l"(dst), "r"(src), "r"(bytes) : "memory");
}
__device__ __forceinline__ void bulk_reduce(void* dst, uint32_t src, uint32_t bytes) {
    asm volatile(ELECT "cp.reduce.async.bulk.global.shared::cta.bulk_group.add.f32 [%0], [%1], %2;\n}" :: "l"(dst), "r"(src), "r"(bytes) : "memory");
}
__device__ __forceinline__ void tma_prefetch(const CUtensorMap* tm, int c0, int c1) {
    asm volatile(ELECT "cp.async.bulk.prefetch.tensor.2d.L2.global [%0, {%1, %2}];\n}" :: "l"(tm), "r"(c0), "r"(c1) : "memory");
}
__device__ __forceinline__ void l2_prefetch(const void* p, uint32_t bytes) {
    asm volatile(ELECT "cp.async.bulk.prefetch.L2.global [%0], %1;\n}" :: "l"(p), "r"(bytes) : "memory");
}
__device__ __forceinline__ void bulk_wait_read() { asm volatile("cp.async.bulk.commit_group;\ncp.async.bulk.wait_group.read 0;" ::: "memory"); }
__device__ __forceinline__ void bulk_wait() { asm volatile("cp.async.bulk.commit_group;\ncp.async.bulk.wait_group 0;" ::: "memory"); }
__device__ __forceinline__ void tmap_prefetch(const CUtensorMap* tm) { asm volatile("prefetch.tensormap [%0];" :: "l"(tm) : "memory"); }
__device__ __forceinline__ void wg_fence() { asm volatile("wgmma.fence.sync.aligned;" ::: "memory"); }
__device__ __forceinline__ void wg_commit() { asm volatile("wgmma.commit_group.sync.aligned;" ::: "memory"); }
template<int N> __device__ __forceinline__ void wg_wait() { asm volatile("wgmma.wait_group.sync.aligned %0;" :: "n"(N) : "memory"); }
template<int N> __device__ __forceinline__ void acc_fence(float (&d)[N]) {
    #pragma unroll
    for (int i = 0; i < N; i++) asm volatile("" : "+f"(d[i]) :: "memory");
}
__device__ __forceinline__ uint32_t desc_lo(uint32_t addr, uint32_t lbo) { return (addr >> 4) | ((lbo >> 4) << 16); }
constexpr uint32_t H128 = 0x40000040u;
constexpr uint32_t H64 = 0x80000020u;
__device__ __forceinline__ void fence_async_smem() { asm volatile("fence.proxy.async.shared::cta;" ::: "memory"); }
__device__ __forceinline__ void bar_sync(int id, int n) { asm volatile("bar.sync %0, %1;" :: "r"(id), "r"(n) : "memory"); }
template<int R> __device__ __forceinline__ void reg_inc() { asm volatile("setmaxnreg.inc.sync.aligned.u32 %0;" :: "n"(R)); }
template<int R> __device__ __forceinline__ void reg_dec() { asm volatile("setmaxnreg.dec.sync.aligned.u32 %0;" :: "n"(R)); }

__device__ __forceinline__ void stsm4(uint32_t addr, uint32_t r0, uint32_t r1, uint32_t r2, uint32_t r3) {
    asm volatile("stmatrix.sync.aligned.m8n8.x4.shared.b16 [%0], {%1,%2,%3,%4};" :: "r"(addr), "r"(r0), "r"(r1), "r"(r2), "r"(r3) : "memory");
}
__device__ __forceinline__ void ldsm4(uint32_t* r, uint32_t addr) {
    asm volatile("ldmatrix.sync.aligned.m8n8.x4.shared.b16 {%0,%1,%2,%3}, [%4];" : "=r"(r[0]), "=r"(r[1]), "=r"(r[2]), "=r"(r[3]) : "r"(addr) : "memory");
}
__device__ __forceinline__ void ldsm4t(uint32_t* r, uint32_t addr) {
    asm volatile("ldmatrix.sync.aligned.m8n8.x4.trans.shared.b16 {%0,%1,%2,%3}, [%4];" : "=r"(r[0]), "=r"(r[1]), "=r"(r[2]), "=r"(r[3]) : "r"(addr) : "memory");
}
__device__ __forceinline__ void mma16816(float (&d)[4], uint32_t a0, uint32_t a1, uint32_t a2, uint32_t a3, uint32_t b0, uint32_t b1) {
    asm volatile("mma.sync.aligned.m16n8k16.row.col.f32.bf16.bf16.f32 {%0,%1,%2,%3}, {%4,%5,%6,%7}, {%8,%9}, {%0,%1,%2,%3};"
        : "+f"(d[0]), "+f"(d[1]), "+f"(d[2]), "+f"(d[3]) : "r"(a0), "r"(a1), "r"(a2), "r"(a3), "r"(b0), "r"(b1));
}
__device__ __forceinline__ uint4 lds128(uint32_t a) { uint4 v; asm volatile("ld.shared.v4.b32 {%0,%1,%2,%3}, [%4];" : "=r"(v.x), "=r"(v.y), "=r"(v.z), "=r"(v.w) : "r"(a) : "memory"); return v; }
__device__ __forceinline__ uint32_t lds32(uint32_t a) { uint32_t v; asm volatile("ld.shared.b32 %0, [%1];" : "=r"(v) : "r"(a) : "memory"); return v; }
__device__ __forceinline__ uint2 lds64(uint32_t a) { uint2 v; asm volatile("ld.shared.v2.b32 {%0,%1}, [%2];" : "=r"(v.x), "=r"(v.y) : "r"(a) : "memory"); return v; }
__device__ __forceinline__ float ldsf(uint32_t a) { float v; asm volatile("ld.shared.f32 %0, [%1];" : "=f"(v) : "r"(a) : "memory"); return v; }
__device__ __forceinline__ void sts128(uint32_t a, uint4 v) { asm volatile("st.shared.v4.b32 [%0], {%1,%2,%3,%4};" :: "r"(a), "r"(v.x), "r"(v.y), "r"(v.z), "r"(v.w) : "memory"); }
__device__ __forceinline__ void sts64(uint32_t a, uint32_t x, uint32_t y) { asm volatile("st.shared.v2.b32 [%0], {%1,%2};" :: "r"(a), "r"(x), "r"(y) : "memory"); }
__device__ __forceinline__ void sts32(uint32_t a, uint32_t x) { asm volatile("st.shared.b32 [%0], %1;" :: "r"(a), "r"(x) : "memory"); }
__device__ __forceinline__ void stsf(uint32_t a, float x) { asm volatile("st.shared.f32 [%0], %1;" :: "r"(a), "f"(x) : "memory"); }
__device__ __forceinline__ float u2f(uint32_t v) { return __uint_as_float(v); }
__device__ __forceinline__ uint32_t f2u(float v) { return __float_as_uint(v); }

__device__ __forceinline__ uint32_t ldg32(const void* p) { uint32_t v; asm volatile("ld.global.nc.b32 %0, [%1];" : "=r"(v) : "l"(p)); return v; }
__device__ __forceinline__ void stg128(void* p, uint4 v) { asm volatile("st.global.v4.b32 [%0], {%1,%2,%3,%4};" :: "l"(p), "r"(v.x), "r"(v.y), "r"(v.z), "r"(v.w) : "memory"); }
__device__ __forceinline__ void stg_zero(void* p) { stg128(p, make_uint4(0, 0, 0, 0)); }
__device__ __forceinline__ void fence_gpu() { asm volatile("fence.acq_rel.gpu;" ::: "memory"); }
__device__ __forceinline__ void st_ll(uint4* p, uint32_t x, uint32_t y, uint32_t z, uint32_t w) {
    asm volatile("{\n.reg .b128 t;\n.reg .b64 a, b;\nmov.b64 a, {%1, %2};\nmov.b64 b, {%3, %4};\nmov.b128 t, {a, b};\nst.relaxed.gpu.global.b128 [%0], t;\n}"
        :: "l"(p), "r"(x), "r"(y), "r"(z), "r"(w) : "memory");
}
__device__ __forceinline__ uint4 ld_ll(const uint4* p) {
    uint4 v;
    asm volatile("{\n.reg .b128 t;\n.reg .b64 a, b;\nld.relaxed.gpu.global.b128 t, [%4];\nmov.b128 {a, b}, t;\nmov.b64 {%0, %1}, a;\nmov.b64 {%2, %3}, b;\n}"
        : "=r"(v.x), "=r"(v.y), "=r"(v.z), "=r"(v.w) : "l"(p) : "memory");
    return v;
}
__device__ __forceinline__ void st_ll4(uint4* p, float a, float b, float c, float d, uint32_t tag) {
    st_ll(p, (f2u(a) & ~1u) | (tag & 1u), (f2u(b) & ~1u) | ((tag >> 1) & 1u), (f2u(c) & ~1u) | ((tag >> 2) & 1u), f2u(d) | 1u);
}
__device__ __forceinline__ bool ll4_ok(const uint4& v, uint32_t tag) { return !(((v.x ^ tag) | (v.y ^ (tag >> 1)) | (v.z ^ (tag >> 2)) | ~v.w) & 1u); }
__device__ __forceinline__ unsigned ld_rlx(const void* p) { unsigned v; asm volatile("ld.relaxed.gpu.global.u32 %0, [%1];" : "=r"(v) : "l"(p) : "memory"); return v; }
__device__ __forceinline__ void st_flag(void* p, unsigned v) { asm volatile("st.relaxed.gpu.global.u32 [%0], %1;" :: "l"(p), "r"(v) : "memory"); }
__device__ __forceinline__ void poll_flags(const uint4* f, uint32_t tag) {
    unsigned v0 = ld_rlx(f), v1;
    spin_until(clk32() + 140);
    #pragma unroll 1
    for (int it = 0; it < POLL_MAX; it++) {
        v1 = ld_rlx(f);
        if (__all_sync(0xffffffffu, v0 == tag)) break;
        v0 = ld_rlx(f);
        if (__all_sync(0xffffffffu, v1 == tag)) break;
    }
}
template<int Z> __device__ __forceinline__ bool ll_ok(const uint4& v, uint32_t tag) { return v.w == tag && (!Z || (v.x & v.y & v.z) != ~0u); }
template<int N, int Z> __device__ __forceinline__ void poll_words(uint4 (&v)[N], const uint4* p, int stride, uint32_t tag) {
    #pragma unroll 1
    for (int it = 0; it < POLL_MAX; it++) {
        bool ok = true;
        #pragma unroll
        for (int i = 0; i < N; i++) v[i] = ld_ll(p + i * stride);
        #pragma unroll
        for (int i = 0; i < N; i++) ok = ok && ll_ok<Z>(v[i], tag);
        if (__all_sync(0xffffffffu, ok)) break;
    }
}
template<int N> __device__ __forceinline__ void poll_words4(uint4 (&v)[N], const uint4* p, int stride, uint32_t tag) {
    #pragma unroll 1
    for (int it = 0; it < POLL_MAX; it++) {
        bool ok = true;
        #pragma unroll
        for (int i = 0; i < N; i++) v[i] = ld_ll(p + i * stride);
        #pragma unroll
        for (int i = 0; i < N; i++) ok = ok && ll4_ok(v[i], tag);
        if (__all_sync(0xffffffffu, ok)) break;
    }
}
constexpr uint32_t ONE2 = 0x3F803F80u;
__device__ __forceinline__ uint32_t pack2(float lo, float hi) { uint32_t d; asm("cvt.rn.bf16x2.f32 %0, %1, %2;" : "=r"(d) : "f"(hi), "f"(lo)); return d; }
__device__ __forceinline__ float bf_lo(uint32_t v) { return u2f(v << 16); }
__device__ __forceinline__ float bf_hi(uint32_t v) { return u2f(v & 0xffff0000u); }
__device__ __forceinline__ float rbf(float x) { return bf_lo(pack2(x, 0.f)); }
__device__ __forceinline__ uint32_t hsub2(uint32_t a, uint32_t b) { uint32_t d; asm("sub.rn.bf16x2 %0, %1, %2;" : "=r"(d) : "r"(a), "r"(b)); return d; }
__device__ __forceinline__ uint32_t hadd2(uint32_t a, uint32_t b) { uint32_t d; asm("add.rn.bf16x2 %0, %1, %2;" : "=r"(d) : "r"(a), "r"(b)); return d; }
__device__ __forceinline__ uint32_t hmul2(uint32_t a, uint32_t b) { uint32_t d; asm("mul.rn.bf16x2 %0, %1, %2;" : "=r"(d) : "r"(a), "r"(b)); return d; }
__device__ __forceinline__ uint32_t hfma2(uint32_t a, uint32_t b, uint32_t c) { uint32_t d; asm("fma.rn.bf16x2 %0, %1, %2, %3;" : "=r"(d) : "r"(a), "r"(b), "r"(c)); return d; }
__device__ __forceinline__ uint32_t hmax2(uint32_t a, uint32_t b) { uint32_t d; asm("max.bf16x2 %0, %1, %2;" : "=r"(d) : "r"(a), "r"(b)); return d; }
__device__ __forceinline__ uint32_t hmin2(uint32_t a, uint32_t b) { uint32_t d; asm("min.bf16x2 %0, %1, %2;" : "=r"(d) : "r"(a), "r"(b)); return d; }
__device__ __forceinline__ float ex2(float x) { float y; asm("ex2.approx.ftz.f32 %0, %1;" : "=f"(y) : "f"(x)); return y; }
__device__ __forceinline__ float rcp(float x) { float y; asm("rcp.approx.ftz.f32 %0, %1;" : "=f"(y) : "f"(x)); return y; }
__device__ __forceinline__ float shfl_x(float v, int m) { return __shfl_xor_sync(0xffffffffu, v, m); }
__device__ __forceinline__ uint32_t hdiv2(uint32_t d, uint32_t rh, uint32_t rl) { return hfma2(d, rh, hmul2(d, rl)); }
__device__ __forceinline__ void split_rcp(float r, uint32_t& rh, uint32_t& rl) { rh = pack2(r, r); const float l = r - bf_lo(rh); rl = pack2(l, l); }
__device__ __forceinline__ uint32_t lnmod(uint32_t x, uint32_t m, uint32_t rh, uint32_t rl, uint32_t a, uint32_t s) { return hadd2(hmul2(hdiv2(hsub2(x, m), rh, rl), a), s); }
__device__ __forceinline__ void ln_final(float s1, float s2, uint32_t& m2, float& rinv) {
    const float mean = s1 * (1.0f / 1024.0f), var = fmaf(-mean, mean, s2 * (1.0f / 1024.0f));
    m2 = pack2(mean, mean);
    float sd;
    asm("sqrt.approx.ftz.f32 %0, %1;" : "=f"(sd) : "f"(rbf(rbf(fmaxf(var, 0.f)) + 1e-5f)));
    rinv = rcp(rbf(sd));
}
__device__ __forceinline__ float sigmoid_f(float x) { return rcp(1.0f + ex2(-1.4426950408889634f * x)); }
__device__ __forceinline__ uint32_t silu2(uint32_t v) { return pack2(bf_lo(v) * sigmoid_f(bf_lo(v)), bf_hi(v) * sigmoid_f(bf_hi(v))); }
__device__ __forceinline__ uint32_t f2key(float f) { uint32_t u = f2u(f); return (u & 0x80000000u) ? ~u : (u | 0x80000000u); }
template<int N> __device__ __forceinline__ void top2(uint32_t (&k)[N], uint32_t& b0, uint32_t& b1) {
    uint32_t m = k[0];
    #pragma unroll
    for (int i = 1; i < N; i++) m = max(m, k[i]);
    b0 = __reduce_max_sync(0xffffffffu, m);
    m = 0;
    #pragma unroll
    for (int i = 0; i < N; i++) m = max(m, k[i] == b0 ? 0u : k[i]);
    b1 = __reduce_max_sync(0xffffffffu, m);
}
template<class T> __device__ __forceinline__ T sel4(int c, T a0, T a1, T a2, T a3) { return (c & 2) ? ((c & 1) ? a3 : a2) : ((c & 1) ? a1 : a0); }

__device__ __forceinline__ void fm_max(const float (&a)[16], uint32_t* p, uint32_t* mm) {
    #pragma unroll
    for (int i = 0; i < 8; i++) p[i] = pack2(a[2 * i], a[2 * i + 1]);
    #pragma unroll
    for (int h = 0; h < 2; h++) {
        const uint32_t mx = hmax2(hmax2(p[h], p[2 + h]), hmax2(p[4 + h], p[6 + h]));
        const uint32_t mn = hmin2(hmin2(p[h], p[2 + h]), hmin2(p[4 + h], p[6 + h])) ^ 0x80008000u;
        mm[h] = hmax2(__byte_perm(mx, mn, 0x5410), __byte_perm(mx, mn, 0x7632));
    }
    #pragma unroll
    for (int d = 1; d <= 2; d++) { mm[0] = hmax2(mm[0], __shfl_xor_sync(0xffffffffu, mm[0], d)); mm[1] = hmax2(mm[1], __shfl_xor_sync(0xffffffffu, mm[1], d)); }
}
__device__ __forceinline__ void fm_args(const uint32_t* p, const uint32_t* mm, float (&e)[32]) {
    const float L = 1.4426950408889634f;
    #pragma unroll
    for (int h = 0; h < 2; h++) {
        const float cp = -bf_lo(mm[h]) * L, cn = -bf_hi(mm[h]) * L;
        #pragma unroll
        for (int j = 0; j < 4; j++) {
            const float f0 = bf_lo(p[2 * j + h]), f1 = bf_hi(p[2 * j + h]);
            e[8 * h + 2 * j] = fmaf(f0, L, cp); e[8 * h + 2 * j + 1] = fmaf(f1, L, cp);
            e[16 + 8 * h + 2 * j] = fmaf(f0, -L, cn); e[16 + 8 * h + 2 * j + 1] = fmaf(f1, -L, cn);
        }
    }
}
template<int LO, int HI> __device__ __forceinline__ void fm_exp(float (&e)[32]) {
    #pragma unroll
    for (int i = LO; i < HI; i++) e[i] = ex2(e[i]);
}
__device__ __forceinline__ void fm_norm(const float (&e)[32], uint32_t* ph) {
    float s[4];
    #pragma unroll
    for (int k = 0; k < 4; k++) s[k] = ((e[8 * k] + e[8 * k + 1]) + (e[8 * k + 2] + e[8 * k + 3])) + ((e[8 * k + 4] + e[8 * k + 5]) + (e[8 * k + 6] + e[8 * k + 7]));
    #pragma unroll
    for (int k = 0; k < 4; k++) s[k] += shfl_x(s[k], 1);
    #pragma unroll
    for (int k = 0; k < 4; k++) s[k] = rcp(s[k] + shfl_x(s[k], 2));
    #pragma unroll
    for (int k = 0; k < 4; k++)
        #pragma unroll
        for (int j = 0; j < 4; j++) ph[8 * (k >> 1) + 2 * j + (k & 1)] = pack2(e[8 * k + 2 * j] * s[k], e[8 * k + 2 * j + 1] * s[k]);
}
template<int N> __device__ __forceinline__ void pin(uint32_t* d) {
    #pragma unroll
    for (int i = 0; i < N; i++) asm volatile("" : "+r"(d[i]) :: "memory");
}

template<uint32_t BO, uint32_t BH> __device__ __forceinline__ void mma192_rs(float (&d)[96], const uint32_t* a, uint32_t blo) {
  asm volatile("{\n.reg .pred p;\n.reg .b32 ta, tb;\n.reg .b64 da, db;\nadd.u32 tb, %100, %101;\nmov.b64 db, {tb, %102};\nsetp.ne.b32 p, 1, 0;\n"
    "wgmma.mma_async.sync.aligned.m64n192k16.f32.bf16.bf16 {%0, %1, %2, %3, %4, %5, %6, %7, %8, %9, %10, %11, %12, %13, %14, %15, %16, %17, %18, %19, %20, %21, %22, %23, %24, %25, %26, %27, %28, %29, %30, %31, %32, %33, %34, %35, %36, %37, %38, %39, %40, %41, %42, %43, %44, %45, %46, %47, %48, %49, %50, %51, %52, %53, %54, %55, %56, %57, %58, %59, %60, %61, %62, %63, %64, %65, %66, %67, %68, %69, %70, %71, %72, %73, %74, %75, %76, %77, %78, %79, %80, %81, %82, %83, %84, %85, %86, %87, %88, %89, %90, %91, %92, %93, %94, %95}, {%96,%97,%98,%99}, db, p, 1, 1, 1;\n}\n"
    : "+f"(d[0]), "+f"(d[1]), "+f"(d[2]), "+f"(d[3]), "+f"(d[4]), "+f"(d[5]), "+f"(d[6]), "+f"(d[7]), "+f"(d[8]), "+f"(d[9]), "+f"(d[10]), "+f"(d[11]), "+f"(d[12]), "+f"(d[13]), "+f"(d[14]), "+f"(d[15]), "+f"(d[16]), "+f"(d[17]), "+f"(d[18]), "+f"(d[19]), "+f"(d[20]), "+f"(d[21]), "+f"(d[22]), "+f"(d[23]), "+f"(d[24]), "+f"(d[25]), "+f"(d[26]), "+f"(d[27]), "+f"(d[28]), "+f"(d[29]), "+f"(d[30]), "+f"(d[31]), "+f"(d[32]), "+f"(d[33]), "+f"(d[34]), "+f"(d[35]), "+f"(d[36]), "+f"(d[37]), "+f"(d[38]), "+f"(d[39]), "+f"(d[40]), "+f"(d[41]), "+f"(d[42]), "+f"(d[43]), "+f"(d[44]), "+f"(d[45]), "+f"(d[46]), "+f"(d[47]), "+f"(d[48]), "+f"(d[49]), "+f"(d[50]), "+f"(d[51]), "+f"(d[52]), "+f"(d[53]), "+f"(d[54]), "+f"(d[55]), "+f"(d[56]), "+f"(d[57]), "+f"(d[58]), "+f"(d[59]), "+f"(d[60]), "+f"(d[61]), "+f"(d[62]), "+f"(d[63]), "+f"(d[64]), "+f"(d[65]), "+f"(d[66]), "+f"(d[67]), "+f"(d[68]), "+f"(d[69]), "+f"(d[70]), "+f"(d[71]), "+f"(d[72]), "+f"(d[73]), "+f"(d[74]), "+f"(d[75]), "+f"(d[76]), "+f"(d[77]), "+f"(d[78]), "+f"(d[79]), "+f"(d[80]), "+f"(d[81]), "+f"(d[82]), "+f"(d[83]), "+f"(d[84]), "+f"(d[85]), "+f"(d[86]), "+f"(d[87]), "+f"(d[88]), "+f"(d[89]), "+f"(d[90]), "+f"(d[91]), "+f"(d[92]), "+f"(d[93]), "+f"(d[94]), "+f"(d[95])
    : "r"(a[0]), "r"(a[1]), "r"(a[2]), "r"(a[3]), "r"(blo), "n"(BO), "n"(BH));
}
template<uint32_t BO, uint32_t BH> __device__ __forceinline__ void mma192_rsp(float (&d)[96], const uint32_t* a, uint32_t blo, int sc) {
  asm volatile("{\n.reg .pred p;\n.reg .b32 ta, tb;\n.reg .b64 da, db;\nadd.u32 tb, %100, %101;\nmov.b64 db, {tb, %102};\nsetp.ne.b32 p, %103, 0;\n"
    "wgmma.mma_async.sync.aligned.m64n192k16.f32.bf16.bf16 {%0, %1, %2, %3, %4, %5, %6, %7, %8, %9, %10, %11, %12, %13, %14, %15, %16, %17, %18, %19, %20, %21, %22, %23, %24, %25, %26, %27, %28, %29, %30, %31, %32, %33, %34, %35, %36, %37, %38, %39, %40, %41, %42, %43, %44, %45, %46, %47, %48, %49, %50, %51, %52, %53, %54, %55, %56, %57, %58, %59, %60, %61, %62, %63, %64, %65, %66, %67, %68, %69, %70, %71, %72, %73, %74, %75, %76, %77, %78, %79, %80, %81, %82, %83, %84, %85, %86, %87, %88, %89, %90, %91, %92, %93, %94, %95}, {%96,%97,%98,%99}, db, p, 1, 1, 1;\n}\n"
    : "+f"(d[0]), "+f"(d[1]), "+f"(d[2]), "+f"(d[3]), "+f"(d[4]), "+f"(d[5]), "+f"(d[6]), "+f"(d[7]), "+f"(d[8]), "+f"(d[9]), "+f"(d[10]), "+f"(d[11]), "+f"(d[12]), "+f"(d[13]), "+f"(d[14]), "+f"(d[15]), "+f"(d[16]), "+f"(d[17]), "+f"(d[18]), "+f"(d[19]), "+f"(d[20]), "+f"(d[21]), "+f"(d[22]), "+f"(d[23]), "+f"(d[24]), "+f"(d[25]), "+f"(d[26]), "+f"(d[27]), "+f"(d[28]), "+f"(d[29]), "+f"(d[30]), "+f"(d[31]), "+f"(d[32]), "+f"(d[33]), "+f"(d[34]), "+f"(d[35]), "+f"(d[36]), "+f"(d[37]), "+f"(d[38]), "+f"(d[39]), "+f"(d[40]), "+f"(d[41]), "+f"(d[42]), "+f"(d[43]), "+f"(d[44]), "+f"(d[45]), "+f"(d[46]), "+f"(d[47]), "+f"(d[48]), "+f"(d[49]), "+f"(d[50]), "+f"(d[51]), "+f"(d[52]), "+f"(d[53]), "+f"(d[54]), "+f"(d[55]), "+f"(d[56]), "+f"(d[57]), "+f"(d[58]), "+f"(d[59]), "+f"(d[60]), "+f"(d[61]), "+f"(d[62]), "+f"(d[63]), "+f"(d[64]), "+f"(d[65]), "+f"(d[66]), "+f"(d[67]), "+f"(d[68]), "+f"(d[69]), "+f"(d[70]), "+f"(d[71]), "+f"(d[72]), "+f"(d[73]), "+f"(d[74]), "+f"(d[75]), "+f"(d[76]), "+f"(d[77]), "+f"(d[78]), "+f"(d[79]), "+f"(d[80]), "+f"(d[81]), "+f"(d[82]), "+f"(d[83]), "+f"(d[84]), "+f"(d[85]), "+f"(d[86]), "+f"(d[87]), "+f"(d[88]), "+f"(d[89]), "+f"(d[90]), "+f"(d[91]), "+f"(d[92]), "+f"(d[93]), "+f"(d[94]), "+f"(d[95])
    : "r"(a[0]), "r"(a[1]), "r"(a[2]), "r"(a[3]), "r"(blo), "n"(BO), "n"(BH), "r"(sc));
}
template<uint32_t BO, uint32_t BH> __device__ __forceinline__ void mma32_rs(float (&d)[16], const uint32_t* a, uint32_t blo) {
  asm volatile("{\n.reg .pred p;\n.reg .b32 ta, tb;\n.reg .b64 da, db;\nadd.u32 tb, %20, %21;\nmov.b64 db, {tb, %22};\nsetp.ne.b32 p, 1, 0;\n"
    "wgmma.mma_async.sync.aligned.m64n32k16.f32.bf16.bf16 {%0, %1, %2, %3, %4, %5, %6, %7, %8, %9, %10, %11, %12, %13, %14, %15}, {%16,%17,%18,%19}, db, p, 1, 1, 1;\n}\n"
    : "+f"(d[0]), "+f"(d[1]), "+f"(d[2]), "+f"(d[3]), "+f"(d[4]), "+f"(d[5]), "+f"(d[6]), "+f"(d[7]), "+f"(d[8]), "+f"(d[9]), "+f"(d[10]), "+f"(d[11]), "+f"(d[12]), "+f"(d[13]), "+f"(d[14]), "+f"(d[15])
    : "r"(a[0]), "r"(a[1]), "r"(a[2]), "r"(a[3]), "r"(blo), "n"(BO), "n"(BH));
}
template<uint32_t BO, uint32_t BH> __device__ __forceinline__ void mma32_rs0(float (&d)[16], const uint32_t* a, uint32_t blo) {
  asm volatile("{\n.reg .pred p;\n.reg .b32 ta, tb;\n.reg .b64 da, db;\nadd.u32 tb, %20, %21;\nmov.b64 db, {tb, %22};\nsetp.ne.b32 p, 0, 0;\n"
    "wgmma.mma_async.sync.aligned.m64n32k16.f32.bf16.bf16 {%0, %1, %2, %3, %4, %5, %6, %7, %8, %9, %10, %11, %12, %13, %14, %15}, {%16,%17,%18,%19}, db, p, 1, 1, 1;\n}\n"
    : "=f"(d[0]), "=f"(d[1]), "=f"(d[2]), "=f"(d[3]), "=f"(d[4]), "=f"(d[5]), "=f"(d[6]), "=f"(d[7]), "=f"(d[8]), "=f"(d[9]), "=f"(d[10]), "=f"(d[11]), "=f"(d[12]), "=f"(d[13]), "=f"(d[14]), "=f"(d[15])
    : "r"(a[0]), "r"(a[1]), "r"(a[2]), "r"(a[3]), "r"(blo), "n"(BO), "n"(BH));
}
template<uint32_t BO, uint32_t BH> __device__ __forceinline__ void mma40_rs(float (&d)[20], const uint32_t* a, uint32_t blo) {
  asm volatile("{\n.reg .pred p;\n.reg .b32 ta, tb;\n.reg .b64 da, db;\nadd.u32 tb, %24, %25;\nmov.b64 db, {tb, %26};\nsetp.ne.b32 p, 1, 0;\n"
    "wgmma.mma_async.sync.aligned.m64n40k16.f32.bf16.bf16 {%0, %1, %2, %3, %4, %5, %6, %7, %8, %9, %10, %11, %12, %13, %14, %15, %16, %17, %18, %19}, {%20,%21,%22,%23}, db, p, 1, 1, 1;\n}\n"
    : "+f"(d[0]), "+f"(d[1]), "+f"(d[2]), "+f"(d[3]), "+f"(d[4]), "+f"(d[5]), "+f"(d[6]), "+f"(d[7]), "+f"(d[8]), "+f"(d[9]), "+f"(d[10]), "+f"(d[11]), "+f"(d[12]), "+f"(d[13]), "+f"(d[14]), "+f"(d[15]), "+f"(d[16]), "+f"(d[17]), "+f"(d[18]), "+f"(d[19])
    : "r"(a[0]), "r"(a[1]), "r"(a[2]), "r"(a[3]), "r"(blo), "n"(BO), "n"(BH));
}
template<uint32_t BO, uint32_t BH> __device__ __forceinline__ void mma40_rs0(float (&d)[20], const uint32_t* a, uint32_t blo) {
  asm volatile("{\n.reg .pred p;\n.reg .b32 ta, tb;\n.reg .b64 da, db;\nadd.u32 tb, %24, %25;\nmov.b64 db, {tb, %26};\nsetp.ne.b32 p, 0, 0;\n"
    "wgmma.mma_async.sync.aligned.m64n40k16.f32.bf16.bf16 {%0, %1, %2, %3, %4, %5, %6, %7, %8, %9, %10, %11, %12, %13, %14, %15, %16, %17, %18, %19}, {%20,%21,%22,%23}, db, p, 1, 1, 1;\n}\n"
    : "=f"(d[0]), "=f"(d[1]), "=f"(d[2]), "=f"(d[3]), "=f"(d[4]), "=f"(d[5]), "=f"(d[6]), "=f"(d[7]), "=f"(d[8]), "=f"(d[9]), "=f"(d[10]), "=f"(d[11]), "=f"(d[12]), "=f"(d[13]), "=f"(d[14]), "=f"(d[15]), "=f"(d[16]), "=f"(d[17]), "=f"(d[18]), "=f"(d[19])
    : "r"(a[0]), "r"(a[1]), "r"(a[2]), "r"(a[3]), "r"(blo), "n"(BO), "n"(BH));
}
template<uint32_t AO, uint32_t AH, uint32_t BO, uint32_t BH> __device__ __forceinline__ void mma40_tt(float (&d)[20], uint32_t alo, uint32_t blo) {
  asm volatile("{\n.reg .pred p;\n.reg .b32 ta, tb;\n.reg .b64 da, db;\nadd.u32 ta, %20, %21;\nmov.b64 da, {ta, %22};\nadd.u32 tb, %23, %24;\nmov.b64 db, {tb, %25};\nsetp.ne.b32 p, 1, 0;\n"
    "wgmma.mma_async.sync.aligned.m64n40k16.f32.bf16.bf16 {%0, %1, %2, %3, %4, %5, %6, %7, %8, %9, %10, %11, %12, %13, %14, %15, %16, %17, %18, %19}, da, db, p, 1, 1, 1, 1;\n}\n"
    : "+f"(d[0]), "+f"(d[1]), "+f"(d[2]), "+f"(d[3]), "+f"(d[4]), "+f"(d[5]), "+f"(d[6]), "+f"(d[7]), "+f"(d[8]), "+f"(d[9]), "+f"(d[10]), "+f"(d[11]), "+f"(d[12]), "+f"(d[13]), "+f"(d[14]), "+f"(d[15]), "+f"(d[16]), "+f"(d[17]), "+f"(d[18]), "+f"(d[19])
    : "r"(alo), "n"(AO), "n"(AH), "r"(blo), "n"(BO), "n"(BH));
}
template<uint32_t AO, uint32_t AH, uint32_t BO, uint32_t BH> __device__ __forceinline__ void mma40_tt0(float (&d)[20], uint32_t alo, uint32_t blo) {
  asm volatile("{\n.reg .pred p;\n.reg .b32 ta, tb;\n.reg .b64 da, db;\nadd.u32 ta, %20, %21;\nmov.b64 da, {ta, %22};\nadd.u32 tb, %23, %24;\nmov.b64 db, {tb, %25};\nsetp.ne.b32 p, 0, 0;\n"
    "wgmma.mma_async.sync.aligned.m64n40k16.f32.bf16.bf16 {%0, %1, %2, %3, %4, %5, %6, %7, %8, %9, %10, %11, %12, %13, %14, %15, %16, %17, %18, %19}, da, db, p, 1, 1, 1, 1;\n}\n"
    : "=f"(d[0]), "=f"(d[1]), "=f"(d[2]), "=f"(d[3]), "=f"(d[4]), "=f"(d[5]), "=f"(d[6]), "=f"(d[7]), "=f"(d[8]), "=f"(d[9]), "=f"(d[10]), "=f"(d[11]), "=f"(d[12]), "=f"(d[13]), "=f"(d[14]), "=f"(d[15]), "=f"(d[16]), "=f"(d[17]), "=f"(d[18]), "=f"(d[19])
    : "r"(alo), "n"(AO), "n"(AH), "r"(blo), "n"(BO), "n"(BH));
}
template<uint32_t AO, uint32_t AH, uint32_t BO, uint32_t BH> __device__ __forceinline__ void mma8_tn(float (&d)[4], uint32_t alo, uint32_t blo) {
  asm volatile("{\n.reg .pred p;\n.reg .b32 ta, tb;\n.reg .b64 da, db;\nadd.u32 ta, %4, %5;\nmov.b64 da, {ta, %6};\nadd.u32 tb, %7, %8;\nmov.b64 db, {tb, %9};\nsetp.ne.b32 p, 1, 0;\n"
    "wgmma.mma_async.sync.aligned.m64n8k16.f32.bf16.bf16 {%0, %1, %2, %3}, da, db, p, 1, 1, 1, 0;\n}\n"
    : "+f"(d[0]), "+f"(d[1]), "+f"(d[2]), "+f"(d[3])
    : "r"(alo), "n"(AO), "n"(AH), "r"(blo), "n"(BO), "n"(BH));
}
template<uint32_t AO, uint32_t AH, uint32_t BO, uint32_t BH> __device__ __forceinline__ void mma8_tn0(float (&d)[4], uint32_t alo, uint32_t blo) {
  asm volatile("{\n.reg .pred p;\n.reg .b32 ta, tb;\n.reg .b64 da, db;\nadd.u32 ta, %4, %5;\nmov.b64 da, {ta, %6};\nadd.u32 tb, %7, %8;\nmov.b64 db, {tb, %9};\nsetp.ne.b32 p, 0, 0;\n"
    "wgmma.mma_async.sync.aligned.m64n8k16.f32.bf16.bf16 {%0, %1, %2, %3}, da, db, p, 1, 1, 1, 0;\n}\n"
    : "=f"(d[0]), "=f"(d[1]), "=f"(d[2]), "=f"(d[3])
    : "r"(alo), "n"(AO), "n"(AH), "r"(blo), "n"(BO), "n"(BH));
}
template<uint32_t AO, uint32_t AH, uint32_t BO, uint32_t BH> __device__ __forceinline__ void mma128_ss(float (&d)[64], uint32_t alo, uint32_t blo) {
  asm volatile("{\n.reg .pred p;\n.reg .b32 ta, tb;\n.reg .b64 da, db;\nadd.u32 ta, %64, %65;\nmov.b64 da, {ta, %66};\nadd.u32 tb, %67, %68;\nmov.b64 db, {tb, %69};\nsetp.ne.b32 p, 1, 0;\n"
    "wgmma.mma_async.sync.aligned.m64n128k16.f32.bf16.bf16 {%0, %1, %2, %3, %4, %5, %6, %7, %8, %9, %10, %11, %12, %13, %14, %15, %16, %17, %18, %19, %20, %21, %22, %23, %24, %25, %26, %27, %28, %29, %30, %31, %32, %33, %34, %35, %36, %37, %38, %39, %40, %41, %42, %43, %44, %45, %46, %47, %48, %49, %50, %51, %52, %53, %54, %55, %56, %57, %58, %59, %60, %61, %62, %63}, da, db, p, 1, 1, 0, 1;\n}\n"
    : "+f"(d[0]), "+f"(d[1]), "+f"(d[2]), "+f"(d[3]), "+f"(d[4]), "+f"(d[5]), "+f"(d[6]), "+f"(d[7]), "+f"(d[8]), "+f"(d[9]), "+f"(d[10]), "+f"(d[11]), "+f"(d[12]), "+f"(d[13]), "+f"(d[14]), "+f"(d[15]), "+f"(d[16]), "+f"(d[17]), "+f"(d[18]), "+f"(d[19]), "+f"(d[20]), "+f"(d[21]), "+f"(d[22]), "+f"(d[23]), "+f"(d[24]), "+f"(d[25]), "+f"(d[26]), "+f"(d[27]), "+f"(d[28]), "+f"(d[29]), "+f"(d[30]), "+f"(d[31]), "+f"(d[32]), "+f"(d[33]), "+f"(d[34]), "+f"(d[35]), "+f"(d[36]), "+f"(d[37]), "+f"(d[38]), "+f"(d[39]), "+f"(d[40]), "+f"(d[41]), "+f"(d[42]), "+f"(d[43]), "+f"(d[44]), "+f"(d[45]), "+f"(d[46]), "+f"(d[47]), "+f"(d[48]), "+f"(d[49]), "+f"(d[50]), "+f"(d[51]), "+f"(d[52]), "+f"(d[53]), "+f"(d[54]), "+f"(d[55]), "+f"(d[56]), "+f"(d[57]), "+f"(d[58]), "+f"(d[59]), "+f"(d[60]), "+f"(d[61]), "+f"(d[62]), "+f"(d[63])
    : "r"(alo), "n"(AO), "n"(AH), "r"(blo), "n"(BO), "n"(BH));
}
template<uint32_t AO, uint32_t AH, uint32_t BO, uint32_t BH> __device__ __forceinline__ void mma128_ss0(float (&d)[64], uint32_t alo, uint32_t blo) {
  asm volatile("{\n.reg .pred p;\n.reg .b32 ta, tb;\n.reg .b64 da, db;\nadd.u32 ta, %64, %65;\nmov.b64 da, {ta, %66};\nadd.u32 tb, %67, %68;\nmov.b64 db, {tb, %69};\nsetp.ne.b32 p, 0, 0;\n"
    "wgmma.mma_async.sync.aligned.m64n128k16.f32.bf16.bf16 {%0, %1, %2, %3, %4, %5, %6, %7, %8, %9, %10, %11, %12, %13, %14, %15, %16, %17, %18, %19, %20, %21, %22, %23, %24, %25, %26, %27, %28, %29, %30, %31, %32, %33, %34, %35, %36, %37, %38, %39, %40, %41, %42, %43, %44, %45, %46, %47, %48, %49, %50, %51, %52, %53, %54, %55, %56, %57, %58, %59, %60, %61, %62, %63}, da, db, p, 1, 1, 0, 1;\n}\n"
    : "=f"(d[0]), "=f"(d[1]), "=f"(d[2]), "=f"(d[3]), "=f"(d[4]), "=f"(d[5]), "=f"(d[6]), "=f"(d[7]), "=f"(d[8]), "=f"(d[9]), "=f"(d[10]), "=f"(d[11]), "=f"(d[12]), "=f"(d[13]), "=f"(d[14]), "=f"(d[15]), "=f"(d[16]), "=f"(d[17]), "=f"(d[18]), "=f"(d[19]), "=f"(d[20]), "=f"(d[21]), "=f"(d[22]), "=f"(d[23]), "=f"(d[24]), "=f"(d[25]), "=f"(d[26]), "=f"(d[27]), "=f"(d[28]), "=f"(d[29]), "=f"(d[30]), "=f"(d[31]), "=f"(d[32]), "=f"(d[33]), "=f"(d[34]), "=f"(d[35]), "=f"(d[36]), "=f"(d[37]), "=f"(d[38]), "=f"(d[39]), "=f"(d[40]), "=f"(d[41]), "=f"(d[42]), "=f"(d[43]), "=f"(d[44]), "=f"(d[45]), "=f"(d[46]), "=f"(d[47]), "=f"(d[48]), "=f"(d[49]), "=f"(d[50]), "=f"(d[51]), "=f"(d[52]), "=f"(d[53]), "=f"(d[54]), "=f"(d[55]), "=f"(d[56]), "=f"(d[57]), "=f"(d[58]), "=f"(d[59]), "=f"(d[60]), "=f"(d[61]), "=f"(d[62]), "=f"(d[63])
    : "r"(alo), "n"(AO), "n"(AH), "r"(blo), "n"(BO), "n"(BH));
}

#define XD 600
#define XSTEP 300
#define XPD 450
#define XPB 8192
#define SPG 5600
#define WL0 1800
#define WLS 350
#define NB0 2
#define WP1 2000
#define PF_START 5600
#define PFP 126
#define GPERM 0x76543210u
#define NM0 3
#define PWAIT 600
#define RDV 1
#define MSTEP 1200
#define MSLP 1000
#define MPOLL 3200
#define LMP 8
#define WOGAP 200
#define CLR0 22000
#define UPGAP 450
#define OUTGAP 150
#define MPROMO P128
#define MLOAD tma_load_ef
struct Ptrs { const bf16 *x, *wmod, *c, *wr, *wqkv; int by_sm; Scratch* s; const bf16 *wg, *wu, *wd, *wo; bf16* out; };

#define BAR(i) (sb + OFF_BAR + 8u * (i))

__device__ __forceinline__ uint32_t get_tag(uint32_t sb) { mbar_wait(BAR(B_TAG), 0); return __shfl_sync(0xffffffffu, lds32(sb + OFF_CST + 32), 0) + 1; }
__device__ __forceinline__ int d_kb(int n, int hg) {
    if (n < 2) return 2 * hg + n;
    const int h = n >= 9, q = n - 2 - 7 * h;
    return 2 * (q + (q >= hg)) + h;
}

__global__ void __launch_bounds__(NTHREADS, 1)
fused_kernel(const Ptrs p, const __grid_constant__ CUtensorMap tmM, const __grid_constant__ CUtensorMap tmX, const __grid_constant__ CUtensorMap tmW,
             const __grid_constant__ CUtensorMap tmWo, const __grid_constant__ CUtensorMap tmPhi, const __grid_constant__ CUtensorMap tmG,
             const __grid_constant__ CUtensorMap tmU, const __grid_constant__ CUtensorMap tmD, const __grid_constant__ CUtensorMap tmO)
{
    extern __shared__ __align__(1024) uint8_t smem_raw[];
    const uint32_t sb = smem_u32(smem_raw);
    const uint32_t cstart = __shfl_sync(0xffffffffu, clk32(), 0);
    const int tid = threadIdx.x, lane = tid & 31, warp = __shfl_sync(0xffffffffu, tid >> 5, 0);
    if (blockIdx.x < 128) {
        if (warp == 8) asm volatile("prefetch.global.L2 [%0];" :: "l"(p.wmod + (size_t)(blockIdx.x * 8 + (lane >> 2)) * 6144 + (lane & 1) * 64 + (lane & 2) * 512));
        if (warp == 13 && (lane & 1) < NM0 - 2) asm volatile("prefetch.global.L2 [%0];" :: "l"(p.wmod + (size_t)(blockIdx.x * 8 + (lane >> 2)) * 6144 + 128 + (lane & 1) * 64 + (lane & 2) * 512));
        if (warp == 12) l2_prefetch(p.wqkv + (size_t)blockIdx.x * 1536, 3072);
        if (warp == 9) { spin_until(cstart + XPD); l2_prefetch(p.x + (size_t)blockIdx.x * 16384, XPB); }
    }
    if (warp == 10) { tmap_prefetch(&tmM); tmap_prefetch(&tmX); tmap_prefetch(&tmW); }
    if (warp == 11) asm volatile("prefetch.global.L2 [%0];" :: "l"((lane < 16 ? p.c : p.wr) + (lane & 15) * 64));
    #pragma unroll
    for (int i = 0; i < 5; i++) e_init(BAR(5 * warp + i), warp < 5 ? 1 : warp < 7 ? 2 : warp < 9 ? 4 : 8);
    mbar_init_fence();
    if (warp == B_TAG / 5) { e_arrive_tx(BAR(B_TAG), 16); bulk_load(sb + OFF_CST + 32, p.s->done, 16, BAR(B_TAG)); }
    int b;
    {
        uint32_t sm;
        asm("mov.u32 %0, %%smid;" : "=r"(sm));
        const int tp = sm >> 1, u = tp - 32, q = (u * 37) >> 8;
        const int gp = (GPERM >> (4 * (tp < 32 ? tp & 7 : tp < 60 ? 1 + u - 7 * q : 0))) & 7;
        const int sl = 2 * (tp < 32 ? tp >> 3 : tp < 60 ? 4 + q : tp - 58) + (sm & 1);
        b = (tp >> 1) == 30 ? (int)sm + 8 : ((gp >> 1) * 4 + (sl & 3)) * 8 + (gp & 1) * 4 + (sl >> 2);
        if (!p.by_sm) b = blockIdx.x;
    }
    if (b >= 128 && warp == 0) {
        #pragma unroll
        for (int i = 0; i < 2; i++) { e_arrive_tx(BAR(i), 32768); MLOAD(sb + i * 32768u, &tmM, (b & 1) * 1024, (b & 2) * 256 + i * 256, BAR(i)); }
    }
    __syncthreads();

    if (b >= 128) {
        const int sp = b & 3;
        if (warp == 8) {
            #pragma unroll 1
            for (int j = 2, st = 2, ph = 1; j < 64; j++) {
                if (j == 2 * NM0) spin_until(cstart + SPG);
                mbar_wait(BAR(B_EA + st), ph);
                e_arrive_tx(BAR(st), 32768);
                MLOAD(sb + st * 32768u, &tmM, j < 32 ? (sp & 1) * 1024 + (j >> 1) * 64 : 2560 + sp * 512 + (j >> 2) * 64, (j < 32 ? (sp & 2) + (j & 1) : j & 3) * 256, BAR(st));
                if (++st == 6) { st = 0; ph ^= 1; }
            }
        } else if (warp < 8) {
            const int g = lane >> 2, c = lane & 3;
            {
                const bf16* cp = p.c + (tid >> 3) * 32 + (tid & 1) * 16 + (tid & 6);
                const uint32_t c0 = ldg32(cp), c1 = ldg32(cp + 8);
                stg_zero(p.s->llm1 + (tid >> 4) * 64 + sp * 16 + (tid & 15));
                if (tid < 128) stg_zero(p.s->llmod2 + sp * 128 + tid);
                sts64(sb + 200704u + tid * 8, silu2(c0), silu2(c1));
                bar_sync(1, 256);
                TR(57);
            }
            const uint32_t tag = get_tag(sb);
            const uint32_t wa = sb + (warp * 32 + (lane & 7) + (lane >> 4) * 8) * 128u + ((((lane >> 3) & 1) ^ (lane & 7)) << 4);
            float m[4][4];
            #pragma unroll
            for (int i = 0; i < 4; i++) m[i][0] = m[i][1] = m[i][2] = m[i][3] = 0.f;
            #pragma unroll 1
            for (int r = 0, st = 0, ph = 0; r < 32; r++) {
                const int n = r < 16 ? r : (r >> 1) + 8;
                const bf16* wr = p.wr + (sp & 1) * 512 + (n & 7) * 64 + (g & 3) * 16 + 2 * c;
                const uint32_t wr0 = ldg32(wr), wr1 = ldg32(wr + 8);
                const uint32_t sa = sb + 200704u + ((r < 16 ? sp >> 1 : r & 1) * 16 + warp) * 64 + c * 16;
                const uint4 sv0 = lds128(sa), sv1 = lds128(sa + 512);
                uint32_t f[16][4];
                #pragma unroll
                for (int q = 0; q < 2; q++) {
                    mbar_wait(BAR(st + q), ph);
                    if (r == 0 && warp == 0) TR(60 + q);
                    #pragma unroll
                    for (int i = 0; i < 8; i++) ldsm4t(f[8 * q + i], (wa + (st + q) * 32768u + (i >> 2) * 2048u) ^ ((i & 3) << 5));
                }
                #pragma unroll
                for (int i = 0; i < 16; i++) {
                    const uint4& sv = i < 8 ? sv0 : sv1;
                    mma16816(m[i & 3], f[i][0], f[i][1], f[i][2], f[i][3], (i & 4) ? sv.z : sv.x, (i & 4) ? sv.w : sv.y);
                    if ((i & 7) == 7) e_arrive(BAR(B_EA + st + (i >> 3)));
                }
                st += 2; if (st == 6) { st = 0; ph ^= 1; }
                if (r >= 16 && !(r & 1)) continue;
                const uint32_t red = sb + 196608u + (n & 1) * 2048u;
                const uint32_t a = red + warp * 256u + (c * 16 + (g >> 1) * 4 + (g & 1)) * 4u;
                stsf(a, sel4(c, m[0][0], m[1][0], m[2][0], m[3][0])); stsf(a + 8, sel4(c, m[0][2], m[1][2], m[2][2], m[3][2]));
                #pragma unroll
                for (int i = 0; i < 4; i++) m[i][0] = m[i][1] = m[i][2] = m[i][3] = 0.f;
                bar_sync(1, 256);
                if (warp == (n & 7)) {
                    const uint32_t ra = red + (lane >> 4) * 1024u + (lane & 15) * 16u;
                    const uint4 r0 = lds128(ra), r1 = lds128(ra + 256), r2 = lds128(ra + 512), r3 = lds128(ra + 768);
                    #define F4(f) ((u2f(r0.f) + u2f(r1.f)) + (u2f(r2.f) + u2f(r3.f)))
                    float x = F4(x), y = F4(y), z = F4(z), w = F4(w);
                    #undef F4
                    x += shfl_x(x, 16); y += shfl_x(y, 16); z += shfl_x(z, 16); w += shfl_x(w, 16);
                    if (n < 16) {
                        if (lane < 16) st_ll4(p.s->llm1 + n * 64 + sp * 16 + lane, x, y, z, w, tag);
                    } else {
                        uint32_t lo = pack2(x, y), hi2 = pack2(z, w);
                        float d = fmaf(bf_lo(lo), bf_lo(wr0), bf_hi(lo) * bf_hi(wr0)) + fmaf(bf_lo(hi2), bf_lo(wr1), bf_hi(hi2) * bf_hi(wr1));
                        if (sp >= 2) {
                            lo = hadd2(lo, ONE2); hi2 = hadd2(hi2, ONE2);
                            const uint32_t r0 = hmul2(lo, wr0), r1 = hmul2(hi2, wr1);
                            d = (bf_lo(r0) + bf_hi(r0)) + (bf_lo(r1) + bf_hi(r1));
                        }
                        #pragma unroll 1
                        for (int k = 1; k < 16; k <<= 1) d += shfl_x(d, k);
                        if (lane < 16) st_ll(p.s->llmod2 + sp * 128 + (n & 7) * 16 + lane, lo, hi2, f2u(d), tag);
                    }
                    TR(n);
                }
            }
        }
    } else if (warp >= 12) {
        reg_dec<24>();
        const int rb = b >> 3, hg = b & 7;
        const bool ffn = b < 112;
        if (warp == 12) {
            #pragma unroll 1
            for (int j = 0, s = 0, ph = 1; j < 16; j++) {
                if (j < 2) mbar_wait(j ? BAR(B_STS) : BAR(B_STP), 0);
                mbar_wait(BAR(B_EA + s), ph);
                e_arrive_tx(BAR(B_FA + s), 16384); tma_load(sb + OFF_A + s * 16384u, &tmX, j * 64, rb * 128, BAR(B_FA + s));
                if (j == 0) TS(2);
                if (++s == 3) { s = 0; ph ^= 1; }
            }
            tmap_prefetch(&tmO);
            const uint32_t tag = get_tag(sb);
            e_arrive(BAR(B_FD)); e_arrive(BAR(B_FD + 1));
            #pragma unroll 1
            for (int q = 0; q < 3; q++) {
                mbar_wait(q < 2 ? BAR(B_KST + 1 + 2 * q) : BAR(B_OWN), 0);
                poll_flags(q < 2 ? p.s->flk + (q + 1) * 256 + (hg * 16 + (lane & 15)) * 2 : p.s->flo + ((rb & 12) * 16 + lane * 2) * 2, tag);
                if (q == 2) break;
                if (q) mbar_wait(BAR(B_KVT), 0);
                e_arrive_tx(BAR(B_KVL + q), 16896); bulk_load(sb + OFF_KL, p.s->kvacc + hg * 2112 + q * 1056, 16896, BAR(B_KVL + q));
                TS(12 + q);
            }
            TS(3);
            const uint4* osrc = p.s->os + (size_t)rb * 16 * 1024;
            #pragma unroll 1
            for (int n = 2; n < 18; n++) {
                const uint32_t s = n & 3, fb = BAR(B_FD + s), dst = sb + OFF_R0 + s * 16384u;
                mbar_wait(BAR(B_ED + s), ((n >> 2) - 1) & 1);
                if (n == 5 || n == 9) mbar_wait(n == 5 ? BAR(B_OST) : BAR(B_O1), 0);
                e_arrive_tx(fb, 16384);
                if (n < 16) bulk_load(dst, osrc + d_kb(n, hg) * 1024, 16384, fb);
                else { e_arrive(fb); tma_load(dst, &tmX, hg * 128 + (n - 16) * 64, rb * 128, fb); }
                TR(32 + n);
            }
            mbar_wait(BAR(B_CAND), 0);
            const uint2 lc = lds64(sb + OFF_CST + 16);
            const uint32_t w0 = __shfl_sync(0xffffffffu, lc.x >> 4, 0), w1 = __shfl_sync(0xffffffffu, lc.y >> 4, 0);
            mbar_wait(BAR(B_SWP), 0);
            fence_async_smem();
            #pragma unroll 1
            for (uint32_t w = 0; w < 8; w++)
                if (w != w0 && w != w1) { tma_store4(&tmO, rb * 128 + w * 16, hg * 2, sb + OFF_OUT + w * 4096u); spin_until(clk32() + OUTGAP); }
            mbar_wait(BAR(B_SEL), 0);
            const uint2 sel = lds64(sb + OFF_CST + 24);
            #pragma unroll 1
            for (uint32_t i = 0; i < (w0 == w1 ? 8u : 16u); i++) {
                const uint32_t w = i < 8 ? w0 : w1, r = (i & 7) * 2 + (lane >> 4), row = rb * 128 + w * 16 + r;
                const uint4 o = lds128(sb + OFF_OUT + w * 4096u + ((lane >> 3) & 1) * 2048u + r * 128u + (((lane ^ r) & 7) << 4));
                if (row != sel.x && row != sel.y) stg128(p.out + (size_t)row * 1024 + hg * 128 + (lane & 15) * 8, o);
            }
            bulk_wait_read();
        } else if (warp == 14) {
            const uint32_t fb = ffn ? 65536 : 0;
            e_arrive_tx(BAR(B_GF), fb); e_arrive_tx(BAR(B_UD), fb); e_arrive_tx(BAR(B_UF), fb); e_arrive_tx(BAR(B_WD), fb);
            uint32_t due = cstart + WP1;
            #pragma unroll 1
            for (int i = -2; i < 26; i++) {
                if (i >= 0) {
                    const bf16* a = i < 8 ? p.wg + (size_t)(i * 128 + b) * 3584 : i < 16 ? p.wu + (size_t)((i - 8) * 128 + b) * 3584
                                  : i < 18 ? p.wo + (size_t)(b * 2 + i - 16) * 4096 : p.wd + (size_t)(b * 8 + i - 18) * 3584;
                    sleep_until(due);
                    l2_prefetch(a, (i >> 1) == 8 ? 8192 : 7168);
                    due += 7 * PFP;
                }
                if (i == 1) { tmap_prefetch(&tmPhi); tmap_prefetch(&tmG); tmap_prefetch(&tmWo); tmap_prefetch(&tmU); tmap_prefetch(&tmD); mbar_wait(BAR(B_STS), 0); }
                if (ffn && (uint32_t)(i - 3) < 8u) tma_load_ef(sb + OFF_R0 + (i - 3) * 8192u, &tmG, b * 32, (i - 3) * 128, BAR(B_GF));
                if (ffn && (uint32_t)(i - 11) < 8u) tma_load(sb + OFF_WPHI, &tmU, b * 32, (i - 11) * 128, BAR(B_UD));
                if (i == 19) { mbar_wait(BAR(B_UD), 0); e_arrive_tx(BAR(B_WPHI), 8192); tma_load(sb + OFF_WPHI, &tmPhi, 0, hg * 128, BAR(B_WPHI)); }
                if (i == LMP + 2 * (b & 3) + (b >> 6)) tma_prefetch(&tmM, 2048 + (b >> 6) * 2048 + (b >> 2) * 64, (b & 3) * 256);
                if (i < 13) {
                    sleep_until(due);
                    l2_prefetch(p.wqkv + (size_t)((i + 3) * 128 + b) * 1536, 3072);
                    due += i == -2 ? PF_START - WP1 : 3 * PFP;
                }
            }
            if (lane < 4) stg_zero(p.s->flo + b * 4 + lane);
            const uint32_t tag = get_tag(sb);
            #pragma unroll 1
            for (int q = 0; q < 2; q++) {
                mbar_wait(BAR(B_OWN + q), 0);
                bulk_store(p.s->os + ((size_t)b * 2 + q) * 1024, sb + OFF_R0 + q * 16384u, 16384);
                bulk_wait();
                __syncwarp();
                if (lane == 0) st_flag(p.s->flo + (b * 2 + q) * 2, tag);
                TS(7 + q);
            }
            e_arrive(BAR(B_OST));
        } else {
            uint4* fk = p.s->flk + (hg * 16 + rb) * 2;
            if (warp == 13) {
                #pragma unroll 1
                for (int i = 0; i < 32; i++) {
                    const uint32_t s = i & 3;
                    if (i < NB0) spin_until(cstart + WL0 + WLS * i); else if (i == NB0) mbar_wait(BAR(B_STS), 0);
                    mbar_wait(BAR(B_EB + s), ((i >> 2) - 1) & 1);
                    e_arrive_tx(BAR(B_FB + s), 24576); tma_load4(sb + OFF_B + s * 24576u, &tmW, i * 32, hg * 2, BAR(B_FB + s));
                    TR(64 + i);
                }
                mbar_wait(BAR(B_EB), 1); mbar_wait(BAR(B_EB + 1), 1);
                e_arrive_tx(BAR(B_LMF), 32768); tma_load_ef(sb + OFF_B, &tmM, 2048 + (b >> 6) * 2048 + (b >> 2) * 64, (b & 3) * 256, BAR(B_LMF));
                mbar_wait(BAR(B_LMD), 0);
                #pragma unroll 1
                for (int n = 0; n < 4; n++) {
                    e_arrive_tx(BAR(B_FD + n), 16384); tma_load4(sb + OFF_DB + n * 16384u, &tmWo, d_kb(n, hg) * 64, hg * 2, BAR(B_FD + n));
                    spin_until(clk32() + WOGAP);
                }
            } else {
                sleep_until(cstart + CLR0);
                const uint32_t tag = get_tag(sb);
                #pragma unroll 1
                for (int i = lane; i < 132; i += 32) stg_zero(p.s->kvacc + hg * 2112 + rb * 132 + i);
                if (lane < 4) stg_zero(fk + 256 + (lane >> 1) * 256 + (lane & 1));
                fence_gpu();
                __syncwarp();
                if (lane < 2) st_ll(fk + lane, tag, 0, 0, 0);
                sleep_until(clk32() + 2000);
                poll_flags(p.s->flk + (hg * 16 + (lane & 15)) * 2, tag);
                e_arrive(BAR(B_KZ));
            }
            const int q = warp == 13;
            const uint32_t tag = get_tag(sb);
            mbar_wait(BAR(B_KZ), 0);
            #pragma unroll 1
            for (int h = 2 * q; h < 2 * q + 2; h++) {
                mbar_wait(BAR(B_KST + h), 0);
                uint4* acc = p.s->kvacc + (hg * 4 + h) * 528;
                bulk_reduce(acc, sb + OFF_V + h * 8192u, 8192); bulk_reduce(acc + 512, sb + OFF_ZS + h * 256u, 256);
            }
            bulk_wait();
            TR(158 + q);
            fence_gpu();
            __syncwarp();
            if (lane == 0) st_flag(fk + 256 + q * 256, tag);
            TS(10 + q);
            if (q) {
                if (ffn) {
                    mbar_wait(BAR(B_KVL), 0);
                    #pragma unroll 1
                    for (int i = 0; i < 8; i++) { tma_load_ef(sb + OFF_F2 + i * 8192u, &tmU, b * 32, i * 128, BAR(B_UF)); sleep_until(clk32() + UPGAP); }
                }
                #pragma unroll 1
                for (int n = 4; n < 16; n++) {
                    const uint32_t s = n & 3;
                    mbar_wait(BAR(B_ED + s), ((n >> 2) - 1) & 1);
                    e_arrive_tx(BAR(B_FD + s), 16384);
                    tma_load4(sb + OFF_DB + s * 16384u, &tmWo, d_kb(n, hg) * 64, hg * 2, BAR(B_FD + s));
                    TR(96 + n);
                    if (ffn && n >= 8) {
                        const int z = 8 * (n & 1) + ((n - 8) >> 1);
                        tma_load_ef(sb + OFF_F2 + z * 4096u, &tmD, z * 64, b * 32, BAR(B_WD));
                        tma_load_ef(sb + OFF_F2 + z * 4096u + 16384u, &tmD, z * 64 + 256, b * 32, BAR(B_WD));
                    }
                }
            } else {
                mbar_wait(BAR(B_OST), 0);
                poll_flags(p.s->flo + ((rb & 12) * 16 + lane * 2 + 1) * 2, tag);
                e_arrive(BAR(B_O1));
                TS(4);
            }
        }
    } else if (warp >= 8) {
        reg_dec<24>();
        const int rb = b >> 3, hg = b & 7, w4 = warp & 3, g = lane >> 2, c = lane & 3, t = tid & 127;
        const uint32_t sv = silu2(ldg32(p.c + (b & 3) * 256 + 2 * t)), tag = get_tag(sb);
        if (w4 < 3) {
            spin_until(cstart + MPOLL + MSTEP * w4);
            #pragma unroll 1
            for (int j = w4, ph = 1; j < 16; j += 3, ph ^= 1) {
                uint4 w[2];
                poll_words4<2>(w, p.s->llm1 + j * 64 + lane, 32, tag);
                uint32_t lo = pack2(u2f(w[0].x) + u2f(w[1].x), u2f(w[0].y) + u2f(w[1].y)), hi = pack2(u2f(w[0].z) + u2f(w[1].z), u2f(w[0].w) + u2f(w[1].w));
                if (lane >= 16) { lo = hadd2(lo, ONE2); hi = hadd2(hi, ONE2); }
                sts64(sb + OFF_TAB + j * 256 + (lane & 15) * 16 + (lane < 16 ? 8 : 0), lo, hi);
                __syncwarp();
                if (j == 0) TS(5);
                TR(16 + j);
                mbar_wait(BAR(B_EA + w4), ph);
                e_arrive(BAR(B_FA + w4));
                __nanosleep(MSLP);
            }
        }
        mbar_wait(BAR(B_QE), 0);
        sts32(sb + OFF_KL + w4 * 1024u + lane * 4, sv);
        fence_async_smem();
        bar_sync(2, 128);
        reg_inc<56>();
        {
            float m0[4], m1[4];
            const uint32_t da = desc_lo(sb + OFF_B, 16), db = desc_lo(sb + OFF_KL, 16);
            mbar_wait(BAR(B_LMF), 0);
            wg_fence();
            #define LMS(f, i) f<(i) * 256, H128, ((i) >> 1) * 64 + ((i) & 1) * 4, H128>(m0, da, db); f<(i) * 256 + 128, H128, ((i) >> 1) * 64 + ((i) & 1) * 4 + 2, H128>(m1, da, db)
            LMS(mma8_tn0, 0); LMS(mma8_tn, 1); LMS(mma8_tn, 2); LMS(mma8_tn, 3); LMS(mma8_tn, 4); LMS(mma8_tn, 5); LMS(mma8_tn, 6); LMS(mma8_tn, 7);
            #undef LMS
            wg_commit();
            wg_wait<0>();
            acc_fence(m0); acc_fence(m1);
            e_arrive(BAR(B_LMD));
            const float v0 = m0[0] + m1[0], v1 = m0[2] + m1[2], u0 = shfl_x(v0, 4), u1 = shfl_x(v1, 4);
            if (!(lane & 7)) st_ll4(p.s->llg + (b >> 6) * 1024 + (b & 3) * 256 + ((b >> 2) & 15) * 16 + w4 * 4 + (lane >> 3), v0, u0, v1, u1, tag);
            if (warp == 8) TR(150);
        }
        #pragma unroll 1
        for (int h = 0; h < 4; h++) {
            float okv[20];
            const uint32_t vb = OFF_V + h * 8192u, dp = desc_lo(sb + OFF_PHI + (h & 1) * 16384u, 16), dv = desc_lo(sb + vb, OFF_ONES - vb);
            mbar_wait(BAR(B_PF + h), 0);
            fence_async_smem();
            wg_fence();
            #define KVS(i) mma40_tt<(i) * 128, H128, (i) * (64u - (64u << 16)), H64>(okv, dp, dv)
            mma40_tt0<0, H128, 0, H64>(okv, dp, dv); KVS(1); KVS(2); KVS(3); KVS(4); KVS(5); KVS(6); KVS(7);
            #undef KVS
            wg_commit();
            wg_wait<0>();
            acc_fence(okv);
            if (h < 2) e_arrive(BAR(B_PE + h));
            bar_sync(2, 128);
            #pragma unroll
            for (int k = 0; k < 4; k++) sts128(sb + vb + (k * 128 + t) * 16u, make_uint4(f2u(okv[4 * k]), f2u(okv[4 * k + 1]), f2u(okv[4 * k + 2]), f2u(okv[4 * k + 3])));
            if (c == 0) sts64(sb + OFF_ZS + h * 256u + (w4 * 8 + g) * 8u, f2u(okv[16]), f2u(okv[18]));
            fence_async_smem();
            __syncwarp();
            e_arrive(BAR(B_KST + h));
            if (warp == 8) TR(151 + h);
        }
        reg_dec<24>();
        #pragma unroll 1
        for (int q = 0; q < 2; q++) {
            mbar_wait(q ? BAR(B_OWN) : BAR(B_STP), q ^ 1);
            mbar_wait(BAR(B_KVL + q), 0);
            const uint32_t f = w4 * 16 + g;
            #pragma unroll 1
            for (int hh = 0; hh < 2; hh++) {
                const uint32_t kl = sb + OFF_KL + hh * 8448u, a = sb + OFF_KVT + hh * 4096u + f * 64u + ((g >> 1) << 4) + 4 * c;
                #pragma unroll
                for (int k = 0; k < 4; k += 2) {
                    const uint4 v0 = lds128(kl + (k * 128 + t) * 16u), v1 = lds128(kl + (k * 128 + 128 + t) * 16u);
                    sts32(a ^ (k << 4), pack2(u2f(v0.x), u2f(v0.y))); sts32((a ^ (k << 4)) + 512, pack2(u2f(v0.z), u2f(v0.w)));
                    sts32(a ^ ((k + 1) << 4), pack2(u2f(v1.x), u2f(v1.y))); sts32((a ^ ((k + 1) << 4)) + 512, pack2(u2f(v1.z), u2f(v1.w)));
                }
                const float z = ldsf(kl + 8192u + (w4 * 8 + g) * 8u + (c & 1) * 4);
                const uint32_t zz = pack2(z, z);
                sts64(sb + OFF_Z + (f + 8 * (c & 1)) * 64u + ((hh ^ (g >> 1)) << 4) + (c >> 1) * 8, zz, zz);
            }
            fence_async_smem();
            __syncwarp();
            e_arrive(BAR(B_KVT + q));
            if (warp == 8) TR(155 + q);
        }
        mbar_wait(BAR(B_O1), 0);
        stg_zero(p.s->llln2 + b * 128 + t);
        stg_zero(p.s->llrowh + (w4 >> 1) * 8192 + (rb * 2 + (w4 & 1)) * 256 + hg * 32 + lane);
        #pragma unroll
        for (int k = 0; k < 4; k++) stg_zero(p.s->lly + b * 512 + k * 128 + t);
        if (t < 2 && hg == 0) stg_zero(p.s->llcand + rb * 2 + t);
        if (w4 == 0 || w4 == 3) {
            float s[4] = {0.f, 0.f, 0.f, 0.f};
            #pragma unroll 1
            for (int k = 0; k < 2; k++) {
                uint4 w[2];
                poll_words4<2>(w, p.s->llg + (w4 & 1) * 1024 + k * 512 + hg * 32 + lane, 256, tag);
                s[0] += u2f(w[0].x) + u2f(w[1].x); s[1] += u2f(w[0].y) + u2f(w[1].y); s[2] += u2f(w[0].z) + u2f(w[1].z); s[3] += u2f(w[0].w) + u2f(w[1].w);
            }
            sts64(w4 ? sb + OFF_T3 + lane * 8 : sb + OFF_T1 + lane * 16, pack2(s[0], s[1]), pack2(s[2], s[3]));
        } else {
            const bf16* wr = p.wr + hg * 128 + g * 16 + 2 * c;
            const uint32_t wr0 = ldg32(wr), wr1 = ldg32(wr + 8);
            uint4 w[2];
            poll_words<2, 1>(w, p.s->llmod2 + (w4 - 1) * 256 + hg * 32 + lane, (lane & 15) * 16 - hg * 32 - lane, tag);
            sts64(sb + OFF_T2 + lane * 16 + (w4 & 1) * 8, w[0].x, w[0].y);
            if (w4 == 2) sts64(sb + OFF_T1 + lane * 16 + 8, hmul2(w[0].x, wr0), hmul2(w[0].y, wr1));
            float d = u2f(w[1].z);
            #pragma unroll 1
            for (int k = 1; k < 16; k <<= 1) d += shfl_x(d, k);
            stsf(sb + OFF_CST + 8 + (w4 & 1) * 4, d);
        }
        __syncwarp();
        e_arrive(BAR(B_PAR));
        if (warp == 9) TS(6);
        if (w4 < 2) {
            mbar_wait(BAR(B_KEYS), 0);
            const uint4 kk = lds128(sb + OFF_KEY + lane * 16);
            uint32_t k[4] = {kk.x, kk.y, kk.z, kk.w}, b0, b1;
            top2<4>(k, b0, b1);
            const uint32_t key = w4 ? b1 : b0, cd = 127 - (key & 127u), slot = rb * 2 + w4;
            const uint4 st = lds128(sb + OFF_ST2 + cd * 16), ta = lds128(sb + OFF_T2 + lane * 16);
            const uint2 gb = lds64(sb + OFF_T3 + lane * 8);
            const uint32_t xa = sb + OFF_R0 + (g >> 2) * 16384u + cd * 128u + ((((g & 3) * 2) ^ (cd & 7)) << 4) + c * 4;
            const uint32_t x0 = lds32(xa), x1 = lds32(xa ^ 16);
            if (hg == 0 && lane == 0) st_ll(p.s->llcand + slot, key, rb * 128 + cd, st.w, tag);
            uint4* d = p.s->llrowh + slot * 256 + hg * 32 + lane;
            st_ll(d, lnmod(x0, st.x, st.y, st.z, ta.x, ta.z), lnmod(x1, st.x, st.y, st.z, ta.y, ta.w), gb.x, tag);
            st_ll(d + 8192, x0, x1, gb.y, tag);
            sts32(sb + OFF_CST + 16 + w4 * 4, cd);
            __syncwarp();
            e_arrive(BAR(B_CAND));
            if (warp == 8) TS(9);
        }
    } else {
        reg_inc<232>();
        float a0[96], a1[96];
        {
            const int g = lane >> 2, c = lane & 3;
            uint4* stp = p.s->llstat + b * 16 + warp * 2 + (lane >> 4);
            if ((lane & 15) == 0) stg_zero(stp);
            spin_until(cstart + XD + XSTEP * warp);
            e_arrive_tx(BAR(B_XP + warp), 4096);
            bulk_load(sb + OFF_R0 + warp * 4096u, p.x + (size_t)(b * 16 + 2 * warp) * 1024, 4096, BAR(B_XP + warp));
            const uint32_t tag = get_tag(sb);
            if (tid < 64) sts128(sb + OFF_ONES + tid * 16, make_uint4(ONE2, ONE2, ONE2, ONE2));
            if (tid == 64) sts64(sb + OFF_CST, b, tag);
            mbar_wait(BAR(B_XP + warp), 0);
            e_arrive(BAR(B_STP));
            if (warp == 7) TS(14);
            float s[2][4], q0[2][4], q1[2][4];
            #pragma unroll
            for (int i = 0; i < 4; i++) s[0][i] = s[1][i] = q0[0][i] = q0[1][i] = q1[0][i] = q1[1][i] = 0.f;
            #pragma unroll
            for (int i = 0; i < 4; i++) {
                const uint4 x0 = lds128(sb + OFF_R0 + warp * 4096u + (lane + 32 * i) * 16u), x1 = lds128(sb + OFF_R0 + warp * 4096u + 2048u + (lane + 32 * i) * 16u);
                mma16816(s[0], x0.x, x1.x, x0.y, x1.y, ONE2, ONE2); mma16816(s[1], x0.z, x1.z, x0.w, x1.w, ONE2, ONE2);
                mma16816(q0[0], x0.x, x1.x, x0.y, x1.y, x0.x, x0.y); mma16816(q0[1], x0.z, x1.z, x0.w, x1.w, x0.z, x0.w);
                mma16816(q1[0], x0.x, x1.x, x0.y, x1.y, x1.x, x1.y); mma16816(q1[1], x0.z, x1.z, x0.w, x1.w, x1.z, x1.w);
            }
            const bool dg = c == (g >> 1);
            const float s0 = dg ? s[0][0] + s[1][0] : 0.f, s1 = dg ? s[0][2] + s[1][2] : 0.f;
            const float sq0 = dg ? ((g & 1) ? q0[0][1] + q0[1][1] : q0[0][0] + q0[1][0]) : 0.f, sq1 = dg ? ((g & 1) ? q1[0][3] + q1[1][3] : q1[0][2] + q1[1][2]) : 0.f;
            const bool up = lane >= 16;
            float sm = (up ? s1 : s0) + shfl_x(up ? s0 : s1, 16), sq = (up ? sq1 : sq0) + shfl_x(up ? sq0 : sq1, 16);
            #pragma unroll
            for (int m = 8; m >= 1; m >>= 1) { sm += shfl_x(sm, m); sq += shfl_x(sq, m); }
            uint32_t m2, rh, rl; float rinv;
            ln_final(sm, sq, m2, rinv);
            split_rcp(rinv, rh, rl);
            if ((lane & 15) == 0) st_ll(stp, m2, rh, rl, tag);
            if (warp == 7) TS(15);
            uint4 st[2];
            if (PWAIT) { mbar_wait(BAR(B_STP), 0); if (warp < 7) spin_until(clk32() + PWAIT); }
            #pragma unroll 1
            for (int it = 0; it < POLL_MAX; it++) {
                st[0] = ld_ll(p.s->llstat + (b >> 3) * 128 + warp * 16 + g); st[1] = ld_ll(p.s->llstat + (b >> 3) * 128 + warp * 16 + g + 8);
                const uint32_t o = RDV ? ld_rlx(&p.s->llstat[((b >> 5) * 4 + c) * 128 + warp * 16 + 15].w) : tag;
                if (__all_sync(0xffffffffu, st[0].w == tag && st[1].w == tag && o == tag)) break;
            }
            e_arrive(BAR(B_STS));
            if (warp == 0) TS(16);
            const uint32_t lrow = warp * 16 + (lane & 15);
            uint32_t aad = sb + OFF_A + lrow * 128u + (((lane >> 4) ^ (lrow & 7)) << 4);
            uint32_t tad = sb + OFF_TAB + c * 16, ab = BAR(B_FA), pa = 0;
            uint32_t f0[4], f1[4];
            #define PREP(f, q) do { \
                const uint4 t = lds128(tad + (q) * 64); \
                ldsm4(f, aad ^ ((q) << 5)); \
                f[0] = lnmod(f[0], st[0].x, st[0].y, st[0].z, t.x, t.z); f[1] = lnmod(f[1], st[1].x, st[1].y, st[1].z, t.x, t.z); \
                f[2] = lnmod(f[2], st[0].x, st[0].y, st[0].z, t.y, t.w); f[3] = lnmod(f[3], st[1].x, st[1].y, st[1].z, t.y, t.w); } while (0)
            #define MMA(f, off) do { wg_fence(); mma192_rs<(off), H128>(a0, f, blo); mma192_rs<(off) + 768, H128>(a1, f, blo); wg_commit(); wg_wait<1>(); } while (0)
            mbar_wait(ab, 0);
            PREP(f0, 0);
            if (RDV) mbar_wait(BAR(B_STS), 0);
            #pragma unroll 1
            for (int j = 0; j < 16; j++) {
                const uint32_t bb = BAR(B_FB) + (j & 1) * 16, blo = desc_lo(sb + OFF_B, 4096) + (j & 1) * 3072, pb = (j >> 1) & 1;
                mbar_wait(bb, pb);
                wg_fence(); mma192_rsp<0, H128>(a0, f0, blo, j); mma192_rsp<768, H128>(a1, f0, blo, j); wg_commit(); wg_wait<1>();
                if (j) e_arrive((bb ^ 16) + 8 * (B_EB - B_FB) + 8);
                PREP(f1, 1);
                MMA(f1, 128);
                PREP(f0, 2);
                mbar_wait(bb + 8, pb);
                MMA(f0, 1536);
                e_arrive(bb + 8 * (B_EB - B_FB));
                PREP(f1, 3);
                MMA(f1, 1536 + 128);
                e_arrive(ab + 8 * (B_EA - B_FA));
                ab += 8; aad += 16384; tad += 256;
                if (ab == BAR(B_FA + 3)) { ab -= 24; aad -= 49152; pa ^= 1; }
                if (j < 15) mbar_wait(ab, pa);
                PREP(f0, 0);
            }
            #undef PREP
            #undef MMA
        }
        int tid_o; asm volatile("mov.u32 %0, %%tid.x;" : "=r"(tid_o) :: "memory");
        const int tid = tid_o, lane = tid & 31, warp = __shfl_sync(0xffffffffu, tid >> 5, 0), wgi = warp >> 2, g = lane >> 2, c = lane & 3;
        const uint32_t srow = warp * 16 + (lane & 15);
        const uint32_t t128 = srow * 128u + (((lane >> 4) ^ (srow & 7)) << 4);
        mbar_wait(BAR(B_WPHI), 0);
        mbar_wait(BAR(B_EA), 1);
        wg_wait<0>();
        acc_fence(a0); acc_fence(a1);
        e_arrive(BAR(B_QE));
        if (warp == 0) TS(18);
        uint32_t ph0[16], ph1[16], pk[16], mm[4];
        float ea[32], eb[32];
        #define PIN() do { acc_fence(ea); acc_fence(eb); pin<16>(pk); pin<4>(mm); } while (0)
        {
            uint32_t kq[32];
            float p0[16], p1[16];
            const uint32_t dw = desc_lo(sb + OFF_WPHI, 16);
            #define PMMA(f, o) do { wg_fence(); mma32_rs0<(o), H64>(p0, f, dw); mma32_rs0<(o) + 128, H64>(p1, f + 8, dw); \
                mma32_rs<(o) + 64, H64>(p0, f + 4, dw); mma32_rs<(o) + 192, H64>(p1, f + 12, dw); wg_commit(); } while (0)
            #define V_OUT(lo) _Pragma("unroll") for (int i = lo; i < lo + 4; i++) { const int o = 32 + 8 * i; \
                stsm4(sb + OFF_V + (i >> 1) * 8192u + srow * 64u + (((2 * (i & 1) + (lane >> 4)) ^ ((srow >> 1) & 3)) << 4), \
                      pack2(a1[o], a1[o + 1]), pack2(a1[o + 2], a1[o + 3]), pack2(a1[o + 4], a1[o + 5]), pack2(a1[o + 6], a1[o + 7])); }
            V_OUT(0);
            #pragma unroll
            for (int i = 0; i < 16; i++) ph0[i] = pack2(a0[64 + 2 * i], a0[65 + 2 * i]);
            PMMA(ph0, 0);
            V_OUT(4);
            #undef V_OUT
            wg_wait<0>();
            acc_fence(p0); acc_fence(p1);
            fm_max(p0, pk, mm); fm_max(p1, pk + 8, mm + 2);
            #pragma unroll
            for (int i = 0; i < 16; i++) ph1[i] = pack2(a1[2 * i], a1[2 * i + 1]);
            PMMA(ph1, 256);
            fm_args(pk, mm, ea);
            if (warp == 0) TS(19);
            fm_exp<0, 16>(ea);
            #pragma unroll
            for (int i = 0; i < 32; i++) kq[i] = pack2(a0[2 * i], a0[2 * i + 1]);
            acc_fence(ea); pin<32>(kq);
            wg_wait<0>();
            acc_fence(p0); acc_fence(p1);
            #define PHI_OUT(ph, i) do { if (u < 2) { \
                    mbar_wait(u ? BAR(B_PE + (i)) : (i) ? BAR(B_LMD) : BAR(B_QE), 0);          \
                    _Pragma("unroll") for (int q = 0; q < 4; q++) stsm4((sb + OFF_PHI + (i) * 16384u + t128) ^ (q << 5), ph[4 * q], ph[4 * q + 1], ph[4 * q + 2], ph[4 * q + 3]); \
                    __syncwarp(); \
                    e_arrive(BAR(B_PF + (i)) + u * 16); } } while (0)
            reg_dec<216>();
            #pragma unroll 1
            for (int u = 0; u < 3; u++) {
                fm_exp<16, 32>(ea); fm_args(pk + 8, mm + 2, eb);
                PIN();
                if (warp == 0) TR(129 + u * 6);
                fm_exp<0, 16>(eb); fm_norm(ea, ph0); fm_max(p0, pk, mm);
                acc_fence(eb); pin<8>(pk); pin<2>(mm);
                PHI_OUT(ph0, 0);
                if (warp == 0) TR(130 + u * 6);
                fm_exp<16, 32>(eb); fm_args(pk, mm, ea); fm_max(p1, pk + 8, mm + 2);
                PIN();
                if (warp == 0) TR(131 + u * 6);
                if (u == 0) PMMA(kq, 0); else PMMA(kq + 16, 256);
                fm_exp<0, 16>(ea); fm_norm(eb, ph1);
                acc_fence(ea);
                if (warp == 0) TR(132 + u * 6);
                PHI_OUT(ph1, 1);
                wg_wait<0>();
                acc_fence(p0); acc_fence(p1);
                if (u == 1) e_arrive(BAR(B_STP));
                if (warp == 0) TR(133 + u * 6);
                if (warp == 0) TS(22 + u);
            }
            #undef PHI_OUT
            #undef PMMA
        }
        uint32_t gf[16][4], uf[16][4];
        const uint32_t fo = (warp >> 1) * 16384u + ((lane & 7) + (lane >> 4) * 8) * 64u + (((2 * (warp & 1) + ((lane >> 3) & 1)) ^ ((lane >> 1) & 3)) << 4);
        mbar_wait(BAR(B_GF), 0);
        #pragma unroll
        for (int i = 0; i < 16; i++) ldsm4t(gf[i], sb + OFF_R0 + fo + i * 1024u);
        e_arrive(BAR(B_STS));
        #define O_BLOCK(pp) do { \
            mbar_wait(BAR(B_KVT + (pp)), 0); \
            if (warp == 0) TS(25 + 3 * (pp)); \
            float o0[20], o1[20]; \
            const uint32_t dk = desc_lo(sb + OFF_KVT, OFF_Z - OFF_KVT); \
            constexpr uint32_t K1 = 256u - (255u << 16);          \
            wg_fence(); \
            mma40_rs0<0, H64>(o0, ph0, dk); mma40_rs0<K1, H64>(o1, ph1, dk); \
            mma40_rs<64, H64>(o0, ph0 + 4, dk); mma40_rs<K1 + 64, H64>(o1, ph1 + 4, dk); \
            mma40_rs<128, H64>(o0, ph0 + 8, dk); mma40_rs<K1 + 128, H64>(o1, ph1 + 8, dk); \
            mma40_rs<192, H64>(o0, ph0 + 12, dk); mma40_rs<K1 + 192, H64>(o1, ph1 + 12, dk); \
            wg_commit(); \
            wg_wait<0>(); \
            acc_fence(o0); acc_fence(o1); \
            if (warp == 0) TS(26 + 3 * (pp)); \
            if (!(pp)) mbar_wait(BAR(B_STS), 1);          \
            _Pragma("unroll") for (int hh = 0; hh < 2; hh++) { \
                const float (&o)[20] = hh ? o1 : o0; \
                uint32_t h0, l0, h1, l1; \
                split_rcp(rcp(rbf(rbf(o[16]) + 1e-6f)), h0, l0); split_rcp(rcp(rbf(rbf(o[18]) + 1e-6f)), h1, l1); \
                _Pragma("unroll") for (int q = 0; q < 2; q++) \
                    stsm4((sb + OFF_R0 + (pp) * 16384u + t128) ^ ((2 * hh + q) << 5), hdiv2(pack2(o[8 * q], o[8 * q + 1]), h0, l0), hdiv2(pack2(o[8 * q + 2], o[8 * q + 3]), h1, l1), \
                          hdiv2(pack2(o[8 * q + 4], o[8 * q + 5]), h0, l0), hdiv2(pack2(o[8 * q + 6], o[8 * q + 7]), h1, l1)); \
            } \
            fence_async_smem(); \
            __syncwarp(); \
            e_arrive(BAR(B_OWN + (pp))); \
            if (warp == 0) TS(27 + 3 * (pp)); \
        } while (0)
        float acc[64];
        const uint32_t da = desc_lo(sb + OFF_R0 + wgi * 8192u, 16), db = desc_lo(sb + OFF_DB, 8192);
        #define D_MMA(first, s) do { \
            wg_fence(); \
            first<(s) * 1024, H128, (s) * 1024, H128>(acc, da, db); mma128_ss<(s) * 1024 + 2, H128, (s) * 1024 + 128, H128>(acc, da, db); \
            mma128_ss<(s) * 1024 + 4, H128, (s) * 1024 + 256, H128>(acc, da, db); mma128_ss<(s) * 1024 + 6, H128, (s) * 1024 + 384, H128>(acc, da, db); \
            wg_commit(); } while (0)
        O_BLOCK(0);
        fm_exp<16, 32>(ea); fm_args(pk + 8, mm + 2, eb);
        acc_fence(ea); acc_fence(eb);
        fm_exp<0, 16>(eb); fm_norm(ea, ph0);
        acc_fence(eb); pin<16>(ph0);
        reg_inc<232>();
        mbar_wait(BAR(B_OWN), 0);
        mbar_wait(BAR(B_FD), 0);
        D_MMA(mma128_ss0, 0);
        fm_exp<16, 32>(eb); fm_norm(eb, ph1);
        O_BLOCK(1);
        e_arrive(BAR(B_ED));
        mbar_wait(BAR(B_OWN + 1), 0);
        #undef PIN
        #undef O_BLOCK
        #define D_STEP(n) do { \
            mbar_wait(BAR(B_FD + ((n) & 3)), ((n) >> 2) & 1); \
            if (warp == 0) TR(112 + (n)); \
            D_MMA(mma128_ss, (n) & 3); \
            if ((n) == 3) mbar_wait(BAR(B_UF), 0); \
            if ((n) >= 3 && (n) < 11) { ldsm4t(uf[2 * (((n) + 5) & 7)], sb + OFF_F2 + fo + (((n) + 5) & 7) * 2048u); ldsm4t(uf[2 * (((n) + 5) & 7) + 1], sb + OFF_F2 + fo + (((n) + 5) & 7) * 2048u + 1024u); } \
            wg_wait<1>(); \
            if ((n) > 1) e_arrive(BAR(B_ED + (((n) + 3) & 3))); } while (0)
        D_STEP(1); D_STEP(2);
        if (warp == 0) TS(31);
        D_STEP(3); D_STEP(4); D_STEP(5); D_STEP(6); D_STEP(7); D_STEP(8); D_STEP(9); D_STEP(10); D_STEP(11); D_STEP(12); D_STEP(13); D_STEP(14); D_STEP(15);
        #undef D_STEP
        #undef D_MMA
        mbar_wait(BAR(B_PAR), 0);
        mbar_wait(BAR(B_FD), 0); mbar_wait(BAR(B_FD + 1), 0);
        wg_wait<0>();
        acc_fence(acc);
        e_arrive(BAR(B_ED + 3));
        if (warp == 0) TS(32);
        uint32_t x2[8][4];
        const uint4 cst = lds128(sb + OFF_CST);
        const int b = cst.x;
        const uint32_t tag = cst.y;
        {
            float sd[4] = {0.f, 0.f, 0.f, 0.f}, qa[4] = {0.f, 0.f, 0.f, 0.f}, qb[4] = {0.f, 0.f, 0.f, 0.f};
            #pragma unroll
            for (int i = 0; i < 8; i++) {
                const uint4 t = lds128(sb + OFF_T1 + i * 64 + c * 16);
                ldsm4(x2[i], (sb + OFF_R0 + (i >> 2) * 16384u + t128) ^ ((i & 3) << 5));
                x2[i][0] = hadd2(x2[i][0], hmul2(t.x, pack2(acc[8 * i], acc[8 * i + 1]))); x2[i][1] = hadd2(x2[i][1], hmul2(t.x, pack2(acc[8 * i + 2], acc[8 * i + 3])));
                x2[i][2] = hadd2(x2[i][2], hmul2(t.y, pack2(acc[8 * i + 4], acc[8 * i + 5]))); x2[i][3] = hadd2(x2[i][3], hmul2(t.y, pack2(acc[8 * i + 6], acc[8 * i + 7])));
                mma16816(sd, x2[i][0], x2[i][1], x2[i][2], x2[i][3], (g & 1) ? t.z : ONE2, (g & 1) ? t.w : ONE2);
                mma16816(qa, x2[i][0], x2[i][1], x2[i][2], x2[i][3], x2[i][0], x2[i][2]);
                mma16816(qb, x2[i][0], x2[i][1], x2[i][2], x2[i][3], x2[i][1], x2[i][3]);
            }
            if (c == (g >> 1)) {
                uint4* d = p.s->llln2 + b * 128 + warp * 16 + g;
                st_ll(d, f2u(sd[0]), f2u((g & 1) ? qa[1] : qa[0]), f2u(sd[1]), tag);
                st_ll(d + 8, f2u(sd[2]), f2u((g & 1) ? qb[3] : qb[2]), f2u(sd[3]), tag);
            }
        }
        if (warp == 0) TS(33);
        #pragma unroll
        for (int i = 0; i < 8; i++) stsm4((sb + OFF_R0 + (i >> 2) * 16384u + t128) ^ ((i & 3) << 5), x2[i][0], x2[i][1], x2[i][2], x2[i][3]);
        {
            uint4 w[4];
            const uint32_t rl = warp * 16 + g + 8 * (c & 1);
            poll_words<4, 0>(w, p.s->llln2 + ((b & ~7) + (c >> 1) * 4) * 128 + rl, 128, tag);
            float s1 = (u2f(w[0].x) + u2f(w[1].x)) + (u2f(w[2].x) + u2f(w[3].x));
            float s2 = (u2f(w[0].y) + u2f(w[1].y)) + (u2f(w[2].y) + u2f(w[3].y));
            float dt = (u2f(w[0].z) + u2f(w[1].z)) + (u2f(w[2].z) + u2f(w[3].z));
            s1 += shfl_x(s1, 2); s2 += shfl_x(s2, 2); dt += shfl_x(dt, 2);
            uint32_t m2, rh, rl2; float rinv;
            ln_final(s1, s2, m2, rinv);
            split_rcp(rinv, rh, rl2);
            const float rkey = fmaf(fmaf(-bf_lo(m2), u2f(cst.z), dt), rinv, u2f(cst.w));
            if (c < 2) { sts32(sb + OFF_KEY + rl * 4, (f2key(rkey) & ~127u) | (127 - rl)); sts128(sb + OFF_ST2 + rl * 16, make_uint4(m2, rh, rl2, f2u(rkey))); }
            __syncwarp();
            e_arrive(BAR(B_KEYS));
        }
        if (warp == 0) TS(34);
        {
            const uint4 s0 = lds128(sb + OFF_ST2 + (warp * 16 + g) * 16), s1 = lds128(sb + OFF_ST2 + (warp * 16 + g + 8) * 16);
            mbar_wait(BAR(B_ED + 3), 1);
            const uint32_t oa = sb + OFF_OUT + warp * 2048u + t128;
            #pragma unroll
            for (int i = 0; i < 8; i++) {
                const uint4 t = lds128(sb + OFF_T2 + i * 64 + c * 16);
                const uint2 gb = lds64(sb + OFF_T3 + i * 32 + c * 8);
                stsm4((oa + (i >> 2) * 2048u) ^ ((i & 3) << 5),
                      hadd2(x2[i][0], hmul2(gb.x, lnmod(x2[i][0], s0.x, s0.y, s0.z, t.x, t.z))), hadd2(x2[i][1], hmul2(gb.x, lnmod(x2[i][1], s1.x, s1.y, s1.z, t.x, t.z))),
                      hadd2(x2[i][2], hmul2(gb.y, lnmod(x2[i][2], s0.x, s0.y, s0.z, t.y, t.w))), hadd2(x2[i][3], hmul2(gb.y, lnmod(x2[i][3], s1.x, s1.y, s1.z, t.y, t.w))));
            }
            __syncwarp();
            e_arrive(BAR(B_SWP));
        }
        if (warp == 0) TS(35);
        uint32_t df[16][4];
        mbar_wait(BAR(B_WD), 0);
        #pragma unroll
        for (int i = 0; i < 16; i++)
            ldsm4t(df[i], (sb + OFF_F2 + warp * 8192u + (i >> 3) * 4096u + (i & 1) * 2048u + ((lane & 7) + (lane >> 4) * 8) * 128u + ((((lane >> 3) & 1) ^ (lane & 7)) << 4)) ^ (((i >> 1) & 3) << 5));
        uint32_t fx = 0, fh = 0, fg = 0, frow, fr;
        {
            uint4 v[1];
            poll_words<1, 0>(v, p.s->llcand + lane, 0, tag);
            uint32_t k[1] = {(v[0].x & ~127u) | (63 - lane)}, b0, b1;
            top2<1>(k, b0, b1);
            if (warp == 0) TS(36);
            const uint32_t slot0 = 63 - (b0 & 127u), slot1 = 63 - (b1 & 127u), slot = (g & 1) ? slot1 : slot0;
            frow = __shfl_sync(0xffffffffu, v[0].y, slot); fr = __shfl_sync(0xffffffffu, v[0].z, slot);
            const int wd = b * 2 + (c >> 1);
            uint4 hv[2], fv[2];
            #pragma unroll 1
            for (int it = 0; it < POLL_MAX; it++) {
                hv[0] = ld_ll(p.s->llrowh + slot0 * 256 + tid); hv[1] = ld_ll(p.s->llrowh + slot1 * 256 + tid);
                bool ok = true;
                if (warp == 0) {
                    fv[0] = ld_ll(p.s->llrowx + slot * 256 + wd); fv[1] = ld_ll(p.s->llrowh + slot * 256 + wd);
                    ok = fv[0].w == tag && fv[1].w == tag;
                    fx = (g & 2) ? fv[0].y : fv[0].x; fh = (g & 2) ? fv[1].y : fv[1].x; fg = (g & 2) ? fv[0].z : fv[1].z;
                }
                if (__all_sync(0xffffffffu, ok && ll_ok<1>(hv[0], tag) && ll_ok<1>(hv[1], tag))) break;
            }
            const uint32_t ha = sb + OFF_HSEL + (tid >> 3) * 128u + c * 16u + (g & 1) * 8u;
            sts64(ha, hv[0].x, hv[0].y); sts64(ha + 64, hv[1].x, hv[1].y);
            if (warp == 0) {
                if (lane < 8 && c == 0) sts32(sb + OFF_CST + 24 + g * 4, frow);
                __syncwarp();
                e_arrive(BAR(B_SEL));
            }
        }
        bar_sync(2 + (warp >> 1), 64);
        if (warp == 0) TS(37);
        {
            float ag[2][4], au[2][4];
            #pragma unroll
            for (int i = 0; i < 4; i++) ag[0][i] = ag[1][i] = au[0][i] = au[1][i] = 0.f;
            #pragma unroll
            for (int i = 0; i < 8; i++) {
                const uint4 h = lds128(sb + OFF_HSEL + (warp >> 1) * 1024u + i * 128u + (lane & 7) * 16u);
                mma16816(ag[0], gf[2 * i][0], gf[2 * i][1], gf[2 * i][2], gf[2 * i][3], h.x, h.y);
                mma16816(au[0], uf[2 * i][0], uf[2 * i][1], uf[2 * i][2], uf[2 * i][3], h.x, h.y);
                mma16816(ag[1], gf[2 * i + 1][0], gf[2 * i + 1][1], gf[2 * i + 1][2], gf[2 * i + 1][3], h.z, h.w);
                mma16816(au[1], uf[2 * i + 1][0], uf[2 * i + 1][1], uf[2 * i + 1][2], uf[2 * i + 1][3], h.z, h.w);
            }
            sts64(sb + OFF_RED + (warp >> 1) * 512u + (c & 1) * 256u + ((warp & 1) * 16 + (c >> 1) * 8 + g) * 8u,
                  f2u(sel4(c, ag[0][0], ag[0][1], ag[0][2], ag[0][3]) + sel4(c, ag[1][0], ag[1][1], ag[1][2], ag[1][3])),
                  f2u(sel4(c, au[0][0], au[0][1], au[0][2], au[0][3]) + sel4(c, au[1][0], au[1][1], au[1][2], au[1][3])));
        }
        bar_sync(1, 256);
        {
            const uint32_t ra = sb + OFF_RED + lane * 16u;
            const uint4 r0 = lds128(ra), r1 = lds128(ra + 512), r2 = lds128(ra + 1024), r3 = lds128(ra + 1536);
            #define F4(f) ((u2f(r0.f) + u2f(r1.f)) + (u2f(r2.f) + u2f(r3.f)))
            const uint32_t hid = hmul2(silu2(pack2(F4(x), F4(z))), pack2(F4(y), F4(w)));
            #undef F4
            if (warp == 0) TS(38);
            const int src = (g & 1) * 16 + c;
            const uint32_t b0 = __shfl_sync(0xffffffffu, hid, src), b1 = __shfl_sync(0xffffffffu, hid, src + 4), b2 = __shfl_sync(0xffffffffu, hid, src + 8), b3 = __shfl_sync(0xffffffffu, hid, src + 12);
            float y[8][4];
            #pragma unroll
            for (int i = 0; i < 8; i++) {
                y[i][0] = y[i][1] = y[i][2] = y[i][3] = 0.f;
                mma16816(y[i], df[2 * i][0], df[2 * i][1], df[2 * i][2], df[2 * i][3], b0, b1);
            }
            #pragma unroll
            for (int i = 0; i < 8; i++) mma16816(y[i], df[2 * i + 1][0], df[2 * i + 1][1], df[2 * i + 1][2], df[2 * i + 1][3], b2, b3);
            if (b < 112) {
                #pragma unroll
                for (int h = 0; h < 2; h++) {
                    #define YS(e) sel4(c, y[4 * h][e], y[4 * h + 1][e], y[4 * h + 2][e], y[4 * h + 3][e])
                    st_ll4(p.s->lly + b * 512 + (warp * 8 + 4 * h + c) * 8 + g, YS(0), YS(1), YS(2), YS(3), tag);
                    #undef YS
                }
            }
        }
        if (warp == 0) TS(39);
        if (warp < 7) {
            uint4 v[2];
            poll_words4<2>(v, p.s->lly + (tid >> 2) * 512 + b * 4 + c, 56 * 512, tag);
            float y0 = u2f(v[0].x) + u2f(v[1].x), y1 = u2f(v[0].y) + u2f(v[1].y), y2 = u2f(v[0].z) + u2f(v[1].z), y3 = u2f(v[0].w) + u2f(v[1].w);
            const bool g0 = g & 1, g1 = g & 2;
            const float k0 = (g0 ? y1 : y0) + shfl_x(g0 ? y0 : y1, 4), k1 = (g0 ? y3 : y2) + shfl_x(g0 ? y2 : y3, 4);
            float y = (g1 ? k1 : k0) + shfl_x(g1 ? k0 : k1, 8);
            y += shfl_x(y, 16);
            if (lane < 16) stsf(sb + OFF_RED2 + lane * 32u + warp * 4u, y);
            bar_sync(6, 224);
            if (tid < 16) {
                const uint4 ya = lds128(sb + OFF_RED2 + lane * 32u), yb = lds128(sb + OFF_RED2 + lane * 32u + 16);
                y = ((u2f(ya.x) + u2f(ya.y)) + (u2f(ya.z) + u2f(ya.w))) + ((u2f(yb.x) + u2f(yb.y)) + u2f(yb.z));
                const float sg = sigmoid_f(rbf(u2f(fr)));
                const uint32_t o = hadd2(fx, hmul2(fg, hadd2(fh, hmul2(pack2(y, y), pack2(sg, sg)))));
                ((uint16_t*)p.out)[(size_t)frow * 1024 + (b >> 1) * 16 + (b & 1) * 4 + c + 8 * (g >> 1)] = (c & 1) ? o >> 16 : o;
                if (b == 0 && tid == 0) p.s->done[0] = tag;
                TS(40);
            }
        }
    }
}

typedef CUresult (*EncodeFn)(CUtensorMap*, CUtensorMapDataType, cuuint32_t, void*, const cuuint64_t*, const cuuint64_t*, const cuuint32_t*,
                             const cuuint32_t*, CUtensorMapInterleave, CUtensorMapSwizzle, CUtensorMapL2promotion, CUtensorMapFloatOOBfill);

CUtensorMap make_map(EncodeFn enc, const void* ptr, uint64_t cols, uint64_t rows, uint32_t bc, uint32_t br, CUtensorMapSwizzle swz, CUtensorMapL2promotion promo) {
    CUtensorMap m;
    cuuint64_t dims[2] = {cols, rows}, strides[1] = {cols * 2};
    cuuint32_t box[2] = {bc, br}, es[2] = {1, 1};
    enc(&m, CU_TENSOR_MAP_DATA_TYPE_BFLOAT16, 2, const_cast<void*>(ptr), dims, strides, box, es, CU_TENSOR_MAP_INTERLEAVE_NONE, swz, promo,
        CU_TENSOR_MAP_FLOAT_OOB_FILL_NONE);
    return m;
}
CUtensorMap make_map4(EncodeFn enc, const void* ptr, uint32_t groups, uint64_t rows, uint32_t br, CUtensorMapL2promotion promo) {
    CUtensorMap m;
    cuuint64_t dims[4] = {64, rows, 16, groups}, strides[3] = {groups * 2048ull, 128, 2048};
    cuuint32_t box[4] = {64, br, 2, groups}, es[4] = {1, 1, 1, 1};
    enc(&m, CU_TENSOR_MAP_DATA_TYPE_BFLOAT16, 4, const_cast<void*>(ptr), dims, strides, box, es, CU_TENSOR_MAP_INTERLEAVE_NONE, CU_TENSOR_MAP_SWIZZLE_128B, promo,
        CU_TENSOR_MAP_FLOAT_OOB_FILL_NONE);
    return m;
}

}

extern "C" void kernel_launch(void* const* d_in, const int* in_sizes, int n_in, void* d_out, int out_size) {
    (void)in_sizes; (void)n_in; (void)out_size;
    void* fn = nullptr; cudaDriverEntryPointQueryResult qr;
    cudaGetDriverEntryPoint("cuTensorMapEncodeTiled", &fn, cudaEnableDefault, &qr);
    EncodeFn enc = (EncodeFn)fn;
    void* hs = nullptr;
    cudaGetSymbolAddress(&hs, g_scratch);
    int dev = 0, sms = 0;
    cudaGetDevice(&dev);
    cudaDeviceGetAttribute(&sms, cudaDevAttrMultiProcessorCount, dev);
    const CUtensorMapL2promotion P256 = CU_TENSOR_MAP_L2_PROMOTION_L2_256B, P128 = CU_TENSOR_MAP_L2_PROMOTION_L2_128B, P0 = CU_TENSOR_MAP_L2_PROMOTION_NONE;
    CUtensorMap tmW = make_map4(enc, d_in[1], 3, 1024, 32, P256);
    CUtensorMap tmWo = make_map4(enc, d_in[3], 1, 1024, 64, P256);
    CUtensorMap tmO = make_map4(enc, d_out, 1, 2048, 16, P0);
    CUtensorMap tmPhi = make_map(enc, d_in[2], 32, 1024, 32, 128, CU_TENSOR_MAP_SWIZZLE_64B, P128);
    CUtensorMap tmG = make_map(enc, d_in[6], 3584, 1024, 32, 128, CU_TENSOR_MAP_SWIZZLE_64B, P0);
    CUtensorMap tmU = make_map(enc, d_in[7], 3584, 1024, 32, 128, CU_TENSOR_MAP_SWIZZLE_64B, P0);
    CUtensorMap tmD = make_map(enc, d_in[8], 1024, 3584, 64, 32, CU_TENSOR_MAP_SWIZZLE_128B, P128);
    CUtensorMap tmX = make_map(enc, d_in[0], 1024, 2048, 64, 128, CU_TENSOR_MAP_SWIZZLE_128B, P128);
    CUtensorMap tmM = make_map(enc, d_in[10], 6144, 1024, 64, 256, CU_TENSOR_MAP_SWIZZLE_128B, MPROMO);
    Ptrs p;
    p.x = (const bf16*)d_in[0]; p.c = (const bf16*)d_in[9]; p.wmod = (const bf16*)d_in[10]; p.wr = (const bf16*)d_in[5];
    p.wg = (const bf16*)d_in[6]; p.wu = (const bf16*)d_in[7]; p.wd = (const bf16*)d_in[8]; p.out = (bf16*)d_out; p.s = (Scratch*)hs;
    p.wqkv = (const bf16*)d_in[1]; p.wo = (const bf16*)d_in[3];
    p.by_sm = sms == 132;
    cudaFuncSetAttribute(fused_kernel, cudaFuncAttributeMaxDynamicSharedMemorySize, SMEM_BYTES);
    fused_kernel<<<132, NTHREADS, SMEM_BYTES, cudaStreamPerThread>>>(p, tmM, tmX, tmW, tmWo, tmPhi, tmG, tmU, tmD, tmO);
}
```

```cpp
#include <cuda_runtime.h>
#include <cuda.h>
#include <cuda_bf16.h>
#include <stdint.h>

namespace {

typedef __nv_bfloat16 bf16;

constexpr int NTHREADS = 512;
constexpr int POLL_MAX = 400000;

constexpr uint32_t OFF_R0   = 0;
constexpr uint32_t OFF_A    = 65536;
constexpr uint32_t OFF_B    = 114688;
constexpr uint32_t OFF_V    = 65536;
constexpr uint32_t OFF_PHI  = 98304;
constexpr uint32_t OFF_F2   = 65536;
constexpr uint32_t OFF_DB   = 131072;
constexpr uint32_t OFF_KL   = 196608;
constexpr uint32_t OFF_WPHI = 214016;
constexpr uint32_t OFF_KVT  = OFF_WPHI;
constexpr uint32_t OFF_Z    = 222208;
constexpr uint32_t OFF_TAB  = OFF_Z;
constexpr uint32_t OFF_ONES = 226304;
constexpr uint32_t OFF_BAR  = 227328;
constexpr uint32_t OFF_CST  = OFF_BAR + 640;
constexpr uint32_t OFF_T1   = OFF_CST + 64;
constexpr uint32_t OFF_T2   = OFF_T1 + 512;
constexpr uint32_t OFF_T3   = OFF_T2 + 512;
constexpr uint32_t OFF_KEY  = OFF_T3 + 256;
constexpr uint32_t OFF_ST2  = OFF_KEY + 512;
constexpr uint32_t OFF_ZS   = OFF_ST2;
constexpr uint32_t SMEM_BYTES = 232448;
constexpr uint32_t OFF_OUT  = OFF_R0 + 32768;
constexpr uint32_t OFF_HSEL = OFF_KL;
constexpr uint32_t OFF_RED  = OFF_KL + 4096;
constexpr uint32_t OFF_RED2 = OFF_RED + 2048;
static_assert(OFF_ST2 + 2048 <= SMEM_BYTES, "layout");

enum {
    B_O1 = 0, B_UF = 1, B_UD = 2, B_WPHI = 3, B_FB = 4  , B_OST = 8, B_GF = 9, B_WD = 10, B_KVL = 11  , B_KZ = 13, B_LMF = 14, B_SEL = 15, B_XP = 16  , B_TAG = 24,
    B_FA = 25  , B_FD = 30  , B_CAND = 34,
    B_PE = 35  , B_KST = 37  , B_KVT = 41  , B_LMD = 43, B_PAR = 44,
    B_EA = 45  , B_EB = 48  , B_ED = 52  , B_PF = 56  , B_OWN = 60  , B_QE = 62, B_STP = 63, B_KEYS = 64, B_SWP = 65, B_STS = 66
};

struct Scratch {
    uint4 os[16 * 16 * 1024];
    uint4 kvacc[8 * 4 * 528];
    uint4 flk[3 * 128 * 2];
    uint4 llstat[2048];
    uint4 llm1[16 * 64];
    uint4 flo[16 * 16 * 2];
    uint4 llmod2[2 * 256];
    uint4 llg[2 * 4 * 256];
    uint4 llln2[16 * 8 * 128];
    uint4 llcand[16 * 2];
    uint4 llrowh[32 * 256];
    uint4 llrowx[32 * 256];
    uint4 lly[128 * 512];
    unsigned done[4];
};
__device__ __align__(1024) Scratch g_scratch;
#define GT(i) do {} while (0)
#define TS(i) do {} while (0)
#define TR(i) do {} while (0)

__device__ __forceinline__ uint32_t smem_u32(const void* p) { return (uint32_t)__cvta_generic_to_shared(p); }
__device__ __forceinline__ uint32_t clk32() { uint32_t c; asm volatile("mov.u32 %0, %%clock;" : "=r"(c) :: "memory"); return c; }
__device__ __forceinline__ void spin_until(uint32_t t) { while ((int)(clk32() - t) < 0) {} }
__device__ __forceinline__ void sleep_until(uint32_t t) { while ((int)(clk32() - t) < 0) __nanosleep(40); }
__device__ __forceinline__ void mbar_init_fence() { asm volatile("fence.mbarrier_init.release.cluster;" ::: "memory"); }
__device__ __forceinline__ void mbar_wait(uint32_t bar, uint32_t parity) {
    asm volatile("{\n.reg .pred P1;\nLAB_WAIT:\nmbarrier.try_wait.parity.shared::cta.b64 P1, [%0], %1;\n@!P1 bra LAB_WAIT;\n}" :: "r"(bar), "r"(parity) : "memory");
}
__device__ __forceinline__ uint64_t policy_evict_first() { uint64_t p; asm("createpolicy.fractional.L2::evict_first.b64 %0, 1.0;" : "=l"(p)); return p; }
#define ELECT "{\n.reg .pred e;\nelect.sync _|e, 0xffffffff;\n@e "
__device__ __forceinline__ void e_arrive(uint32_t bar) { asm volatile(ELECT "mbarrier.arrive.shared::cta.b64 _, [%0];\n}" :: "r"(bar) : "memory"); }
__device__ __forceinline__ void e_arrive_tx(uint32_t bar, uint32_t bytes) { asm volatile(ELECT "mbarrier.arrive.expect_tx.shared::cta.b64 _, [%0], %1;\n}" :: "r"(bar), "r"(bytes) : "memory"); }
__device__ __forceinline__ void e_init(uint32_t bar, uint32_t cnt) { asm volatile(ELECT "mbarrier.init.shared::cta.b64 [%0], %1;\n}" :: "r"(bar), "r"(cnt) : "memory"); }
__device__ __forceinline__ void tma_load_ef(uint32_t dst, const CUtensorMap* tm, int c0, int c1, uint32_t bar) {
    asm volatile(ELECT "cp.async.bulk.tensor.2d.shared::cluster.global.mbarrier::complete_tx::bytes.L2::cache_hint [%0], [%1, {%3, %4}], [%2], %5;\n}"
        :: "r"(dst), "l"(tm), "r"(bar), "r"(c0), "r"(c1), "l"(policy_evict_first()) : "memory");
}
__device__ __forceinline__ void tma_load(uint32_t dst, const CUtensorMap* tm, int c0, int c1, uint32_t bar) {
    asm volatile(ELECT "cp.async.bulk.tensor.2d.shared::cluster.global.mbarrier::complete_tx::bytes [%0], [%1, {%3, %4}], [%2];\n}"
        :: "r"(dst), "l"(tm), "r"(bar), "r"(c0), "r"(c1) : "memory");
}
__device__ __forceinline__ void tma_load4(uint32_t dst, const CUtensorMap* tm, int row, int blk, uint32_t bar) {
    asm volatile(ELECT "cp.async.bulk.tensor.4d.shared::cluster.global.mbarrier::complete_tx::bytes [%0], [%1, {0, %3, %4, 0}], [%2];\n}"
        :: "r"(dst), "l"(tm), "r"(bar), "r"(row), "r"(blk) : "memory");
}
__device__ __forceinline__ void tma_store4(const CUtensorMap* tm, int row, int blk, uint32_t src) {
    asm volatile(ELECT "cp.async.bulk.tensor.4d.global.shared::cta.bulk_group [%0, {0, %2, %3, 0}], [%1];\n}" :: "l"(tm), "r"(src), "r"(row), "r"(blk) : "memory");
}
__device__ __forceinline__ void bulk_load(uint32_t dst, const void* src, uint32_t bytes, uint32_t bar) {
    asm volatile(ELECT "cp.async.bulk.shared::cluster.global.mbarrier::complete_tx::bytes [%0], [%1], %2, [%3];\n}" :: "r"(dst), "l"(src), "r"(bytes), "r"(bar) : "memory");
}
__device__ __forceinline__ void bulk_store(void* dst, uint32_t src, uint32_t bytes) {
    asm volatile(ELECT "cp.async.bulk.global.shared::cta.bulk_group [%0], [%1], %2;\n}" :: "l"(dst), "r"(src), "r"(bytes) : "memory");
}
__device__ __forceinline__ void bulk_reduce(void* dst, uint32_t src, uint32_t bytes) {
    asm volatile(ELECT "cp.reduce.async.bulk.global.shared::cta.bulk_group.add.f32 [%0], [%1], %2;\n}" :: "l"(dst), "r"(src), "r"(bytes) : "memory");
}
__device__ __forceinline__ void tma_prefetch(const CUtensorMap* tm, int c0, int c1) {
    asm volatile(ELECT "cp.async.bulk.prefetch.tensor.2d.L2.global [%0, {%1, %2}];\n}" :: "l"(tm), "r"(c0), "r"(c1) : "memory");
}
__device__ __forceinline__ void l2_prefetch(const void* p, uint32_t bytes) {
    asm volatile(ELECT "cp.async.bulk.prefetch.L2.global [%0], %1;\n}" :: "l"(p), "r"(bytes) : "memory");
}
__device__ __forceinline__ void bulk_wait_read() { asm volatile("cp.async.bulk.commit_group;\ncp.async.bulk.wait_group.read 0;" ::: "memory"); }
__device__ __forceinline__ void bulk_wait() { asm volatile("cp.async.bulk.commit_group;\ncp.async.bulk.wait_group 0;" ::: "memory"); }
__device__ __forceinline__ void tmap_prefetch(const CUtensorMap* tm) { asm volatile("prefetch.tensormap [%0];" :: "l"(tm) : "memory"); }
__device__ __forceinline__ void wg_fence() { asm volatile("wgmma.fence.sync.aligned;" ::: "memory"); }
__device__ __forceinline__ void wg_commit() { asm volatile("wgmma.commit_group.sync.aligned;" ::: "memory"); }
template<int N> __device__ __forceinline__ void wg_wait() { asm volatile("wgmma.wait_group.sync.aligned %0;" :: "n"(N) : "memory"); }
template<int N> __device__ __forceinline__ void acc_fence(float (&d)[N]) {
    #pragma unroll
    for (int i = 0; i < N; i++) asm volatile("" : "+f"(d[i]) :: "memory");
}
__device__ __forceinline__ uint32_t desc_lo(uint32_t addr, uint32_t lbo) { return (addr >> 4) | ((lbo >> 4) << 16); }
constexpr uint32_t H128 = 0x40000040u;
constexpr uint32_t H64 = 0x80000020u;
__device__ __forceinline__ void fence_async_smem() { asm volatile("fence.proxy.async.shared::cta;" ::: "memory"); }
__device__ __forceinline__ void bar_sync(int id, int n) { asm volatile("bar.sync %0, %1;" :: "r"(id), "r"(n) : "memory"); }
template<int R> __device__ __forceinline__ void reg_inc() { asm volatile("setmaxnreg.inc.sync.aligned.u32 %0;" :: "n"(R)); }
template<int R> __device__ __forceinline__ void reg_dec() { asm volatile("setmaxnreg.dec.sync.aligned.u32 %0;" :: "n"(R)); }

__device__ __forceinline__ void stsm4(uint32_t addr, uint32_t r0, uint32_t r1, uint32_t r2, uint32_t r3) {
    asm volatile("stmatrix.sync.aligned.m8n8.x4.shared.b16 [%0], {%1,%2,%3,%4};" :: "r"(addr), "r"(r0), "r"(r1), "r"(r2), "r"(r3) : "memory");
}
__device__ __forceinline__ void ldsm4(uint32_t* r, uint32_t addr) {
    asm volatile("ldmatrix.sync.aligned.m8n8.x4.shared.b16 {%0,%1,%2,%3}, [%4];" : "=r"(r[0]), "=r"(r[1]), "=r"(r[2]), "=r"(r[3]) : "r"(addr) : "memory");
}
__device__ __forceinline__ void ldsm4t(uint32_t* r, uint32_t addr) {
    asm volatile("ldmatrix.sync.aligned.m8n8.x4.trans.shared.b16 {%0,%1,%2,%3}, [%4];" : "=r"(r[0]), "=r"(r[1]), "=r"(r[2]), "=r"(r[3]) : "r"(addr) : "memory");
}
__device__ __forceinline__ void mma16816(float (&d)[4], uint32_t a0, uint32_t a1, uint32_t a2, uint32_t a3, uint32_t b0, uint32_t b1) {
    asm volatile("mma.sync.aligned.m16n8k16.row.col.f32.bf16.bf16.f32 {%0,%1,%2,%3}, {%4,%5,%6,%7}, {%8,%9}, {%0,%1,%2,%3};"
        : "+f"(d[0]), "+f"(d[1]), "+f"(d[2]), "+f"(d[3]) : "r"(a0), "r"(a1), "r"(a2), "r"(a3), "r"(b0), "r"(b1));
}
__device__ __forceinline__ uint32_t awake_zero() {
    uint32_t r;
    asm volatile("{\n.reg .f32 d<4>;\nmma.sync.aligned.m16n8k8.row.col.f32.bf16.bf16.f32 {d0,d1,d2,d3}, {%1,%1}, {%1}, {%2,%2,%2,%2};\nmov.b32 %0, d0;\n}" : "=r"(r) : "r"(0), "f"(0.f));
    return r;
}
__device__ __forceinline__ void mbar_wait_awake(uint32_t bar, uint32_t parity) {
    #pragma unroll 1
    for (int it = 0; it < POLL_MAX; it++) {
        uint32_t ok;
        asm volatile("{\n.reg .pred p;\nmbarrier.try_wait.parity.shared::cta.b64 p, [%1], %2;\nselp.u32 %0, 0, 1, p;\n}" : "=r"(ok) : "r"(bar), "r"(parity) : "memory");
        if (__all_sync(0xffffffffu, ok == 0)) break;
        it += awake_zero();
    }
}
__device__ __forceinline__ uint4 lds128(uint32_t a) { uint4 v; asm volatile("ld.shared.v4.b32 {%0,%1,%2,%3}, [%4];" : "=r"(v.x), "=r"(v.y), "=r"(v.z), "=r"(v.w) : "r"(a) : "memory"); return v; }
__device__ __forceinline__ uint32_t lds32(uint32_t a) { uint32_t v; asm volatile("ld.shared.b32 %0, [%1];" : "=r"(v) : "r"(a) : "memory"); return v; }
__device__ __forceinline__ uint2 lds64(uint32_t a) { uint2 v; asm volatile("ld.shared.v2.b32 {%0,%1}, [%2];" : "=r"(v.x), "=r"(v.y) : "r"(a) : "memory"); return v; }
__device__ __forceinline__ float ldsf(uint32_t a) { float v; asm volatile("ld.shared.f32 %0, [%1];" : "=f"(v) : "r"(a) : "memory"); return v; }
__device__ __forceinline__ void sts128(uint32_t a, uint4 v) { asm volatile("st.shared.v4.b32 [%0], {%1,%2,%3,%4};" :: "r"(a), "r"(v.x), "r"(v.y), "r"(v.z), "r"(v.w) : "memory"); }
__device__ __forceinline__ void sts64(uint32_t a, uint32_t x, uint32_t y) { asm volatile("st.shared.v2.b32 [%0], {%1,%2};" :: "r"(a), "r"(x), "r"(y) : "memory"); }
__device__ __forceinline__ void sts32(uint32_t a, uint32_t x) { asm volatile("st.shared.b32 [%0], %1;" :: "r"(a), "r"(x) : "memory"); }
__device__ __forceinline__ void stsf(uint32_t a, float x) { asm volatile("st.shared.f32 [%0], %1;" :: "r"(a), "f"(x) : "memory"); }
__device__ __forceinline__ float u2f(uint32_t v) { return __uint_as_float(v); }
__device__ __forceinline__ uint32_t f2u(float v) { return __float_as_uint(v); }

__device__ __forceinline__ uint32_t ldg32(const void* p) { uint32_t v; asm volatile("ld.global.nc.b32 %0, [%1];" : "=r"(v) : "l"(p)); return v; }
__device__ __forceinline__ void stg128(void* p, uint4 v) { asm volatile("st.global.v4.b32 [%0], {%1,%2,%3,%4};" :: "l"(p), "r"(v.x), "r"(v.y), "r"(v.z), "r"(v.w) : "memory"); }
__device__ __forceinline__ void stg_zero(void* p) { stg128(p, make_uint4(0, 0, 0, 0)); }
__device__ __forceinline__ void fence_gpu() { asm volatile("fence.acq_rel.gpu;" ::: "memory"); }
__device__ __forceinline__ void st_ll(uint4* p, uint32_t x, uint32_t y, uint32_t z, uint32_t w) {
    asm volatile("st.relaxed.gpu.global.v4.b32 [%0], {%1,%2,%3,%4};" :: "l"(p), "r"(x), "r"(y), "r"(z), "r"(w) : "memory");
}
__device__ __forceinline__ uint4 ld_ll(const uint4* p) {
    uint4 v;
    asm volatile("ld.relaxed.gpu.global.v4.b32 {%0,%1,%2,%3}, [%4];" : "=r"(v.x), "=r"(v.y), "=r"(v.z), "=r"(v.w) : "l"(p) : "memory");
    return v;
}
template<uint32_t LUT> __device__ __forceinline__ uint32_t lop3(uint32_t a, uint32_t b, uint32_t c) { uint32_t d; asm("lop3.b32 %0, %1, %2, %3, %4;" : "=r"(d) : "r"(a), "r"(b), "r"(c), "n"(LUT)); return d; }
__device__ __forceinline__ uint32_t tag_bad(uint32_t bad, uint32_t w, uint32_t tag) { return lop3<0xF6>(bad, w, tag); }
__device__ __forceinline__ void st_ll4(uint4* p, float a, float b, float c, float d, uint32_t tag) { st_ll(p, f2u(a), f2u(b), f2u(c), lop3<0xD8>(f2u(d), tag, 3u)); }
__device__ __forceinline__ unsigned ld_rlx(const void* p) { unsigned v; asm volatile("ld.relaxed.gpu.global.u32 %0, [%1];" : "=r"(v) : "l"(p) : "memory"); return v; }
__device__ __forceinline__ void st_flag(void* p, unsigned v) { asm volatile("st.relaxed.gpu.global.u32 [%0], %1;" :: "l"(p), "r"(v) : "memory"); }
__device__ __forceinline__ void poll_flags(const uint4* f, uint32_t tag) {
    unsigned v0 = ld_rlx(f), v1;
    spin_until(clk32() + 140);
    #pragma unroll 1
    for (int it = 0; it < POLL_MAX; it++) {
        v1 = ld_rlx(f);
        if (__all_sync(0xffffffffu, v0 == tag)) break;
        v0 = ld_rlx(f);
        if (__all_sync(0xffffffffu, v1 == tag)) break;
    }
}
template<int Z> __device__ __forceinline__ uint32_t ll_bad(uint32_t bad, const uint4& v, uint32_t tag) {
    bad = tag_bad(bad, v.w, tag);
    return Z && lop3<0x80>(v.x, v.y, v.z) == ~0u ? 1u : bad;
}
template<int N, int Z, uint32_t M = ~0u, int AW = 0> __device__ __forceinline__ void poll_words(uint4 (&v)[N], const uint4* p, int stride, uint32_t tag) {
    #pragma unroll 1
    for (int it = 0; it < POLL_MAX; it++) {
        uint32_t bad = 0;
        #pragma unroll
        for (int i = 0; i < N; i++) v[i] = ld_ll(p + i * stride);
        #pragma unroll
        for (int i = 0; i < N; i++) bad = ll_bad<Z>(bad, v[i], tag);
        if (__all_sync(0xffffffffu, !(bad & M))) break;
        if (AW) it += awake_zero();
    }
}
constexpr uint32_t ONE2 = 0x3F803F80u;
__device__ __forceinline__ uint32_t pack2(float lo, float hi) { uint32_t d; asm("cvt.rn.bf16x2.f32 %0, %1, %2;" : "=r"(d) : "f"(hi), "f"(lo)); return d; }
__device__ __forceinline__ float bf_lo(uint32_t v) { return u2f(v << 16); }
__device__ __forceinline__ float bf_hi(uint32_t v) { return u2f(v & 0xffff0000u); }
__device__ __forceinline__ float rbf(float x) { return bf_lo(pack2(x, 0.f)); }
__device__ __forceinline__ uint32_t hsub2(uint32_t a, uint32_t b) { uint32_t d; asm("sub.rn.bf16x2 %0, %1, %2;" : "=r"(d) : "r"(a), "r"(b)); return d; }
__device__ __forceinline__ uint32_t hadd2(uint32_t a, uint32_t b) { uint32_t d; asm("add.rn.bf16x2 %0, %1, %2;" : "=r"(d) : "r"(a), "r"(b)); return d; }
__device__ __forceinline__ uint32_t hmul2(uint32_t a, uint32_t b) { uint32_t d; asm("mul.rn.bf16x2 %0, %1, %2;" : "=r"(d) : "r"(a), "r"(b)); return d; }
__device__ __forceinline__ uint32_t hfma2(uint32_t a, uint32_t b, uint32_t c) { uint32_t d; asm("fma.rn.bf16x2 %0, %1, %2, %3;" : "=r"(d) : "r"(a), "r"(b), "r"(c)); return d; }
__device__ __forceinline__ uint32_t hmax2(uint32_t a, uint32_t b) { uint32_t d; asm("max.bf16x2 %0, %1, %2;" : "=r"(d) : "r"(a), "r"(b)); return d; }
__device__ __forceinline__ uint32_t hmin2(uint32_t a, uint32_t b) { uint32_t d; asm("min.bf16x2 %0, %1, %2;" : "=r"(d) : "r"(a), "r"(b)); return d; }
__device__ __forceinline__ float ex2(float x) { float y; asm("ex2.approx.ftz.f32 %0, %1;" : "=f"(y) : "f"(x)); return y; }
__device__ __forceinline__ float rcp(float x) { float y; asm("rcp.approx.ftz.f32 %0, %1;" : "=f"(y) : "f"(x)); return y; }
__device__ __forceinline__ float shfl_x(float v, int m) { return __shfl_xor_sync(0xffffffffu, v, m); }
__device__ __forceinline__ uint32_t hdiv2(uint32_t d, uint32_t rh, uint32_t rl) { return hfma2(d, rh, hmul2(d, rl)); }
__device__ __forceinline__ void split_rcp(float r, uint32_t& rh, uint32_t& rl) { rh = pack2(r, r); const float l = r - bf_lo(rh); rl = pack2(l, l); }
__device__ __forceinline__ uint32_t lnmod(uint32_t x, uint32_t m, uint32_t rh, uint32_t rl, uint32_t a, uint32_t s) { return hadd2(hmul2(hdiv2(hsub2(x, m), rh, rl), a), s); }
__device__ __forceinline__ void ln_final(float s1, float s2, uint32_t& m2, float& rinv) {
    const float mean = s1 * (1.0f / 1024.0f), var = fmaf(-mean, mean, s2 * (1.0f / 1024.0f));
    m2 = pack2(mean, mean);
    float sd;
    asm("sqrt.approx.ftz.f32 %0, %1;" : "=f"(sd) : "f"(rbf(rbf(fmaxf(var, 0.f)) + 1e-5f)));
    rinv = rcp(rbf(sd));
}
__device__ __forceinline__ float sigmoid_f(float x) { return rcp(1.0f + ex2(-1.4426950408889634f * x)); }
__device__ __forceinline__ uint32_t silu2(uint32_t v) { return pack2(bf_lo(v) * sigmoid_f(bf_lo(v)), bf_hi(v) * sigmoid_f(bf_hi(v))); }
__device__ __forceinline__ uint32_t f2key(float f) { uint32_t u = f2u(f); return (u & 0x80000000u) ? ~u : (u | 0x80000000u); }
template<int N> __device__ __forceinline__ void top2(uint32_t (&k)[N], uint32_t& b0, uint32_t& b1) {
    uint32_t m = k[0];
    #pragma unroll
    for (int i = 1; i < N; i++) m = max(m, k[i]);
    b0 = __reduce_max_sync(0xffffffffu, m);
    m = 0;
    #pragma unroll
    for (int i = 0; i < N; i++) m = max(m, k[i] == b0 ? 0u : k[i]);
    b1 = __reduce_max_sync(0xffffffffu, m);
}
template<class T> __device__ __forceinline__ T sel4(int c, T a0, T a1, T a2, T a3) { return (c & 2) ? ((c & 1) ? a3 : a2) : ((c & 1) ? a1 : a0); }

__device__ __forceinline__ void fm_max(const float (&a)[16], uint32_t* p, uint32_t* mm) {
    #pragma unroll
    for (int i = 0; i < 8; i++) p[i] = pack2(a[2 * i], a[2 * i + 1]);
    #pragma unroll
    for (int h = 0; h < 2; h++) {
        const uint32_t mx = hmax2(hmax2(p[h], p[2 + h]), hmax2(p[4 + h], p[6 + h]));
        const uint32_t mn = hmin2(hmin2(p[h], p[2 + h]), hmin2(p[4 + h], p[6 + h])) ^ 0x80008000u;
        mm[h] = hmax2(__byte_perm(mx, mn, 0x5410), __byte_perm(mx, mn, 0x7632));
    }
    #pragma unroll
    for (int d = 1; d <= 2; d++) { mm[0] = hmax2(mm[0], __shfl_xor_sync(0xffffffffu, mm[0], d)); mm[1] = hmax2(mm[1], __shfl_xor_sync(0xffffffffu, mm[1], d)); }
}
__device__ __forceinline__ void fm_args(const uint32_t* p, const uint32_t* mm, float (&e)[32]) {
    const float L = 1.4426950408889634f;
    #pragma unroll
    for (int h = 0; h < 2; h++) {
        const float cp = -bf_lo(mm[h]) * L, cn = -bf_hi(mm[h]) * L;
        #pragma unroll
        for (int j = 0; j < 4; j++) {
            const float f0 = bf_lo(p[2 * j + h]), f1 = bf_hi(p[2 * j + h]);
            e[8 * h + 2 * j] = fmaf(f0, L, cp); e[8 * h + 2 * j + 1] = fmaf(f1, L, cp);
            e[16 + 8 * h + 2 * j] = fmaf(f0, -L, cn); e[16 + 8 * h + 2 * j + 1] = fmaf(f1, -L, cn);
        }
    }
}
template<int LO, int HI> __device__ __forceinline__ void fm_exp(float (&e)[32]) {
    #pragma unroll
    for (int i = LO; i < HI; i++) e[i] = ex2(e[i]);
}
__device__ __forceinline__ void fm_norm(const float (&e)[32], uint32_t* ph) {
    float s[4];
    #pragma unroll
    for (int k = 0; k < 4; k++) s[k] = ((e[8 * k] + e[8 * k + 1]) + (e[8 * k + 2] + e[8 * k + 3])) + ((e[8 * k + 4] + e[8 * k + 5]) + (e[8 * k + 6] + e[8 * k + 7]));
    #pragma unroll
    for (int k = 0; k < 4; k++) s[k] += shfl_x(s[k], 1);
    #pragma unroll
    for (int k = 0; k < 4; k++) s[k] = rcp(s[k] + shfl_x(s[k], 2));
    #pragma unroll
    for (int k = 0; k < 4; k++)
        #pragma unroll
        for (int j = 0; j < 4; j++) ph[8 * (k >> 1) + 2 * j + (k & 1)] = pack2(e[8 * k + 2 * j] * s[k], e[8 * k + 2 * j + 1] * s[k]);
}
template<int N> __device__ __forceinline__ void pin(uint32_t* d) {
    #pragma unroll
    for (int i = 0; i < N; i++) asm volatile("" : "+r"(d[i]) :: "memory");
}

template<uint32_t BO, uint32_t BH> __device__ __forceinline__ void mma192_rs(float (&d)[96], const uint32_t* a, uint32_t blo) {
  asm volatile("{\n.reg .pred p;\n.reg .b32 ta, tb;\n.reg .b64 da, db;\nadd.u32 tb, %100, %101;\nmov.b64 db, {tb, %102};\nsetp.ne.b32 p, 1, 0;\n"
    "wgmma.mma_async.sync.aligned.m64n192k16.f32.bf16.bf16 {%0, %1, %2, %3, %4, %5, %6, %7, %8, %9, %10, %11, %12, %13, %14, %15, %16, %17, %18, %19, %20, %21, %22, %23, %24, %25, %26, %27, %28, %29, %30, %31, %32, %33, %34, %35, %36, %37, %38, %39, %40, %41, %42, %43, %44, %45, %46, %47, %48, %49, %50, %51, %52, %53, %54, %55, %56, %57, %58, %59, %60, %61, %62, %63, %64, %65, %66, %67, %68, %69, %70, %71, %72, %73, %74, %75, %76, %77, %78, %79, %80, %81, %82, %83, %84, %85, %86, %87, %88, %89, %90, %91, %92, %93, %94, %95}, {%96,%97,%98,%99}, db, p, 1, 1, 1;\n}\n"
    : "+f"(d[0]), "+f"(d[1]), "+f"(d[2]), "+f"(d[3]), "+f"(d[4]), "+f"(d[5]), "+f"(d[6]), "+f"(d[7]), "+f"(d[8]), "+f"(d[9]), "+f"(d[10]), "+f"(d[11]), "+f"(d[12]), "+f"(d[13]), "+f"(d[14]), "+f"(d[15]), "+f"(d[16]), "+f"(d[17]), "+f"(d[18]), "+f"(d[19]), "+f"(d[20]), "+f"(d[21]), "+f"(d[22]), "+f"(d[23]), "+f"(d[24]), "+f"(d[25]), "+f"(d[26]), "+f"(d[27]), "+f"(d[28]), "+f"(d[29]), "+f"(d[30]), "+f"(d[31]), "+f"(d[32]), "+f"(d[33]), "+f"(d[34]), "+f"(d[35]), "+f"(d[36]), "+f"(d[37]), "+f"(d[38]), "+f"(d[39]), "+f"(d[40]), "+f"(d[41]), "+f"(d[42]), "+f"(d[43]), "+f"(d[44]), "+f"(d[45]), "+f"(d[46]), "+f"(d[47]), "+f"(d[48]), "+f"(d[49]), "+f"(d[50]), "+f"(d[51]), "+f"(d[52]), "+f"(d[53]), "+f"(d[54]), "+f"(d[55]), "+f"(d[56]), "+f"(d[57]), "+f"(d[58]), "+f"(d[59]), "+f"(d[60]), "+f"(d[61]), "+f"(d[62]), "+f"(d[63]), "+f"(d[64]), "+f"(d[65]), "+f"(d[66]), "+f"(d[67]), "+f"(d[68]), "+f"(d[69]), "+f"(d[70]), "+f"(d[71]), "+f"(d[72]), "+f"(d[73]), "+f"(d[74]), "+f"(d[75]), "+f"(d[76]), "+f"(d[77]), "+f"(d[78]), "+f"(d[79]), "+f"(d[80]), "+f"(d[81]), "+f"(d[82]), "+f"(d[83]), "+f"(d[84]), "+f"(d[85]), "+f"(d[86]), "+f"(d[87]), "+f"(d[88]), "+f"(d[89]), "+f"(d[90]), "+f"(d[91]), "+f"(d[92]), "+f"(d[93]), "+f"(d[94]), "+f"(d[95])
    : "r"(a[0]), "r"(a[1]), "r"(a[2]), "r"(a[3]), "r"(blo), "n"(BO), "n"(BH));
}
template<uint32_t BO, uint32_t BH> __device__ __forceinline__ void mma192_rsp(float (&d)[96], const uint32_t* a, uint32_t blo, int sc) {
  asm volatile("{\n.reg .pred p;\n.reg .b32 ta, tb;\n.reg .b64 da, db;\nadd.u32 tb, %100, %101;\nmov.b64 db, {tb, %102};\nsetp.ne.b32 p, %103, 0;\n"
    "wgmma.mma_async.sync.aligned.m64n192k16.f32.bf16.bf16 {%0, %1, %2, %3, %4, %5, %6, %7, %8, %9, %10, %11, %12, %13, %14, %15, %16, %17, %18, %19, %20, %21, %22, %23, %24, %25, %26, %27, %28, %29, %30, %31, %32, %33, %34, %35, %36, %37, %38, %39, %40, %41, %42, %43, %44, %45, %46, %47, %48, %49, %50, %51, %52, %53, %54, %55, %56, %57, %58, %59, %60, %61, %62, %63, %64, %65, %66, %67, %68, %69, %70, %71, %72, %73, %74, %75, %76, %77, %78, %79, %80, %81, %82, %83, %84, %85, %86, %87, %88, %89, %90, %91, %92, %93, %94, %95}, {%96,%97,%98,%99}, db, p, 1, 1, 1;\n}\n"
    : "+f"(d[0]), "+f"(d[1]), "+f"(d[2]), "+f"(d[3]), "+f"(d[4]), "+f"(d[5]), "+f"(d[6]), "+f"(d[7]), "+f"(d[8]), "+f"(d[9]), "+f"(d[10]), "+f"(d[11]), "+f"(d[12]), "+f"(d[13]), "+f"(d[14]), "+f"(d[15]), "+f"(d[16]), "+f"(d[17]), "+f"(d[18]), "+f"(d[19]), "+f"(d[20]), "+f"(d[21]), "+f"(d[22]), "+f"(d[23]), "+f"(d[24]), "+f"(d[25]), "+f"(d[26]), "+f"(d[27]), "+f"(d[28]), "+f"(d[29]), "+f"(d[30]), "+f"(d[31]), "+f"(d[32]), "+f"(d[33]), "+f"(d[34]), "+f"(d[35]), "+f"(d[36]), "+f"(d[37]), "+f"(d[38]), "+f"(d[39]), "+f"(d[40]), "+f"(d[41]), "+f"(d[42]), "+f"(d[43]), "+f"(d[44]), "+f"(d[45]), "+f"(d[46]), "+f"(d[47]), "+f"(d[48]), "+f"(d[49]), "+f"(d[50]), "+f"(d[51]), "+f"(d[52]), "+f"(d[53]), "+f"(d[54]), "+f"(d[55]), "+f"(d[56]), "+f"(d[57]), "+f"(d[58]), "+f"(d[59]), "+f"(d[60]), "+f"(d[61]), "+f"(d[62]), "+f"(d[63]), "+f"(d[64]), "+f"(d[65]), "+f"(d[66]), "+f"(d[67]), "+f"(d[68]), "+f"(d[69]), "+f"(d[70]), "+f"(d[71]), "+f"(d[72]), "+f"(d[73]), "+f"(d[74]), "+f"(d[75]), "+f"(d[76]), "+f"(d[77]), "+f"(d[78]), "+f"(d[79]), "+f"(d[80]), "+f"(d[81]), "+f"(d[82]), "+f"(d[83]), "+f"(d[84]), "+f"(d[85]), "+f"(d[86]), "+f"(d[87]), "+f"(d[88]), "+f"(d[89]), "+f"(d[90]), "+f"(d[91]), "+f"(d[92]), "+f"(d[93]), "+f"(d[94]), "+f"(d[95])
    : "r"(a[0]), "r"(a[1]), "r"(a[2]), "r"(a[3]), "r"(blo), "n"(BO), "n"(BH), "r"(sc));
}
template<uint32_t BO, uint32_t BH> __device__ __forceinline__ void mma32_rs(float (&d)[16], const uint32_t* a, uint32_t blo) {
  asm volatile("{\n.reg .pred p;\n.reg .b32 ta, tb;\n.reg .b64 da, db;\nadd.u32 tb, %20, %21;\nmov.b64 db, {tb, %22};\nsetp.ne.b32 p, 1, 0;\n"
    "wgmma.mma_async.sync.aligned.m64n32k16.f32.bf16.bf16 {%0, %1, %2, %3, %4, %5, %6, %7, %8, %9, %10, %11, %12, %13, %14, %15}, {%16,%17,%18,%19}, db, p, 1, 1, 1;\n}\n"
    : "+f"(d[0]), "+f"(d[1]), "+f"(d[2]), "+f"(d[3]), "+f"(d[4]), "+f"(d[5]), "+f"(d[6]), "+f"(d[7]), "+f"(d[8]), "+f"(d[9]), "+f"(d[10]), "+f"(d[11]), "+f"(d[12]), "+f"(d[13]), "+f"(d[14]), "+f"(d[15])
    : "r"(a[0]), "r"(a[1]), "r"(a[2]), "r"(a[3]), "r"(blo), "n"(BO), "n"(BH));
}
template<uint32_t BO, uint32_t BH> __device__ __forceinline__ void mma32_rs0(float (&d)[16], const uint32_t* a, uint32_t blo) {
  asm volatile("{\n.reg .pred p;\n.reg .b32 ta, tb;\n.reg .b64 da, db;\nadd.u32 tb, %20, %21;\nmov.b64 db, {tb, %22};\nsetp.ne.b32 p, 0, 0;\n"
    "wgmma.mma_async.sync.aligned.m64n32k16.f32.bf16.bf16 {%0, %1, %2, %3, %4, %5, %6, %7, %8, %9, %10, %11, %12, %13, %14, %15}, {%16,%17,%18,%19}, db, p, 1, 1, 1;\n}\n"
    : "=f"(d[0]), "=f"(d[1]), "=f"(d[2]), "=f"(d[3]), "=f"(d[4]), "=f"(d[5]), "=f"(d[6]), "=f"(d[7]), "=f"(d[8]), "=f"(d[9]), "=f"(d[10]), "=f"(d[11]), "=f"(d[12]), "=f"(d[13]), "=f"(d[14]), "=f"(d[15])
    : "r"(a[0]), "r"(a[1]), "r"(a[2]), "r"(a[3]), "r"(blo), "n"(BO), "n"(BH));
}
template<uint32_t BO, uint32_t BH> __device__ __forceinline__ void mma40_rs(float (&d)[20], const uint32_t* a, uint32_t blo) {
  asm volatile("{\n.reg .pred p;\n.reg .b32 ta, tb;\n.reg .b64 da, db;\nadd.u32 tb, %24, %25;\nmov.b64 db, {tb, %26};\nsetp.ne.b32 p, 1, 0;\n"
    "wgmma.mma_async.sync.aligned.m64n40k16.f32.bf16.bf16 {%0, %1, %2, %3, %4, %5, %6, %7, %8, %9, %10, %11, %12, %13, %14, %15, %16, %17, %18, %19}, {%20,%21,%22,%23}, db, p, 1, 1, 1;\n}\n"
    : "+f"(d[0]), "+f"(d[1]), "+f"(d[2]), "+f"(d[3]), "+f"(d[4]), "+f"(d[5]), "+f"(d[6]), "+f"(d[7]), "+f"(d[8]), "+f"(d[9]), "+f"(d[10]), "+f"(d[11]), "+f"(d[12]), "+f"(d[13]), "+f"(d[14]), "+f"(d[15]), "+f"(d[16]), "+f"(d[17]), "+f"(d[18]), "+f"(d[19])
    : "r"(a[0]), "r"(a[1]), "r"(a[2]), "r"(a[3]), "r"(blo), "n"(BO), "n"(BH));
}
template<uint32_t BO, uint32_t BH> __device__ __forceinline__ void mma40_rs0(float (&d)[20], const uint32_t* a, uint32_t blo) {
  asm volatile("{\n.reg .pred p;\n.reg .b32 ta, tb;\n.reg .b64 da, db;\nadd.u32 tb, %24, %25;\nmov.b64 db, {tb, %26};\nsetp.ne.b32 p, 0, 0;\n"
    "wgmma.mma_async.sync.aligned.m64n40k16.f32.bf16.bf16 {%0, %1, %2, %3, %4, %5, %6, %7, %8, %9, %10, %11, %12, %13, %14, %15, %16, %17, %18, %19}, {%20,%21,%22,%23}, db, p, 1, 1, 1;\n}\n"
    : "=f"(d[0]), "=f"(d[1]), "=f"(d[2]), "=f"(d[3]), "=f"(d[4]), "=f"(d[5]), "=f"(d[6]), "=f"(d[7]), "=f"(d[8]), "=f"(d[9]), "=f"(d[10]), "=f"(d[11]), "=f"(d[12]), "=f"(d[13]), "=f"(d[14]), "=f"(d[15]), "=f"(d[16]), "=f"(d[17]), "=f"(d[18]), "=f"(d[19])
    : "r"(a[0]), "r"(a[1]), "r"(a[2]), "r"(a[3]), "r"(blo), "n"(BO), "n"(BH));
}
template<uint32_t AO, uint32_t AH, uint32_t BO, uint32_t BH> __device__ __forceinline__ void mma40_tt(float (&d)[20], uint32_t alo, uint32_t blo) {
  asm volatile("{\n.reg .pred p;\n.reg .b32 ta, tb;\n.reg .b64 da, db;\nadd.u32 ta, %20, %21;\nmov.b64 da, {ta, %22};\nadd.u32 tb, %23, %24;\nmov.b64 db, {tb, %25};\nsetp.ne.b32 p, 1, 0;\n"
    "wgmma.mma_async.sync.aligned.m64n40k16.f32.bf16.bf16 {%0, %1, %2, %3, %4, %5, %6, %7, %8, %9, %10, %11, %12, %13, %14, %15, %16, %17, %18, %19}, da, db, p, 1, 1, 1, 1;\n}\n"
    : "+f"(d[0]), "+f"(d[1]), "+f"(d[2]), "+f"(d[3]), "+f"(d[4]), "+f"(d[5]), "+f"(d[6]), "+f"(d[7]), "+f"(d[8]), "+f"(d[9]), "+f"(d[10]), "+f"(d[11]), "+f"(d[12]), "+f"(d[13]), "+f"(d[14]), "+f"(d[15]), "+f"(d[16]), "+f"(d[17]), "+f"(d[18]), "+f"(d[19])
    : "r"(alo), "n"(AO), "n"(AH), "r"(blo), "n"(BO), "n"(BH));
}
template<uint32_t AO, uint32_t AH, uint32_t BO, uint32_t BH> __device__ __forceinline__ void mma40_tt0(float (&d)[20], uint32_t alo, uint32_t blo) {
  asm volatile("{\n.reg .pred p;\n.reg .b32 ta, tb;\n.reg .b64 da, db;\nadd.u32 ta, %20, %21;\nmov.b64 da, {ta, %22};\nadd.u32 tb, %23, %24;\nmov.b64 db, {tb, %25};\nsetp.ne.b32 p, 0, 0;\n"
    "wgmma.mma_async.sync.aligned.m64n40k16.f32.bf16.bf16 {%0, %1, %2, %3, %4, %5, %6, %7, %8, %9, %10, %11, %12, %13, %14, %15, %16, %17, %18, %19}, da, db, p, 1, 1, 1, 1;\n}\n"
    : "=f"(d[0]), "=f"(d[1]), "=f"(d[2]), "=f"(d[3]), "=f"(d[4]), "=f"(d[5]), "=f"(d[6]), "=f"(d[7]), "=f"(d[8]), "=f"(d[9]), "=f"(d[10]), "=f"(d[11]), "=f"(d[12]), "=f"(d[13]), "=f"(d[14]), "=f"(d[15]), "=f"(d[16]), "=f"(d[17]), "=f"(d[18]), "=f"(d[19])
    : "r"(alo), "n"(AO), "n"(AH), "r"(blo), "n"(BO), "n"(BH));
}
template<uint32_t AO, uint32_t AH, uint32_t BO, uint32_t BH> __device__ __forceinline__ void mma8_tn(float (&d)[4], uint32_t alo, uint32_t blo) {
  asm volatile("{\n.reg .pred p;\n.reg .b32 ta, tb;\n.reg .b64 da, db;\nadd.u32 ta, %4, %5;\nmov.b64 da, {ta, %6};\nadd.u32 tb, %7, %8;\nmov.b64 db, {tb, %9};\nsetp.ne.b32 p, 1, 0;\n"
    "wgmma.mma_async.sync.aligned.m64n8k16.f32.bf16.bf16 {%0, %1, %2, %3}, da, db, p, 1, 1, 1, 0;\n}\n"
    : "+f"(d[0]), "+f"(d[1]), "+f"(d[2]), "+f"(d[3])
    : "r"(alo), "n"(AO), "n"(AH), "r"(blo), "n"(BO), "n"(BH));
}
template<uint32_t AO, uint32_t AH, uint32_t BO, uint32_t BH> __device__ __forceinline__ void mma8_tn0(float (&d)[4], uint32_t alo, uint32_t blo) {
  asm volatile("{\n.reg .pred p;\n.reg .b32 ta, tb;\n.reg .b64 da, db;\nadd.u32 ta, %4, %5;\nmov.b64 da, {ta, %6};\nadd.u32 tb, %7, %8;\nmov.b64 db, {tb, %9};\nsetp.ne.b32 p, 0, 0;\n"
    "wgmma.mma_async.sync.aligned.m64n8k16.f32.bf16.bf16 {%0, %1, %2, %3}, da, db, p, 1, 1, 1, 0;\n}\n"
    : "=f"(d[0]), "=f"(d[1]), "=f"(d[2]), "=f"(d[3])
    : "r"(alo), "n"(AO), "n"(AH), "r"(blo), "n"(BO), "n"(BH));
}
template<uint32_t AO, uint32_t AH, uint32_t BO, uint32_t BH> __device__ __forceinline__ void mma128_ss(float (&d)[64], uint32_t alo, uint32_t blo) {
  asm volatile("{\n.reg .pred p;\n.reg .b32 ta, tb;\n.reg .b64 da, db;\nadd.u32 ta, %64, %65;\nmov.b64 da, {ta, %66};\nadd.u32 tb, %67, %68;\nmov.b64 db, {tb, %69};\nsetp.ne.b32 p, 1, 0;\n"
    "wgmma.mma_async.sync.aligned.m64n128k16.f32.bf16.bf16 {%0, %1, %2, %3, %4, %5, %6, %7, %8, %9, %10, %11, %12, %13, %14, %15, %16, %17, %18, %19, %20, %21, %22, %23, %24, %25, %26, %27, %28, %29, %30, %31, %32, %33, %34, %35, %36, %37, %38, %39, %40, %41, %42, %43, %44, %45, %46, %47, %48, %49, %50, %51, %52, %53, %54, %55, %56, %57, %58, %59, %60, %61, %62, %63}, da, db, p, 1, 1, 0, 1;\n}\n"
    : "+f"(d[0]), "+f"(d[1]), "+f"(d[2]), "+f"(d[3]), "+f"(d[4]), "+f"(d[5]), "+f"(d[6]), "+f"(d[7]), "+f"(d[8]), "+f"(d[9]), "+f"(d[10]), "+f"(d[11]), "+f"(d[12]), "+f"(d[13]), "+f"(d[14]), "+f"(d[15]), "+f"(d[16]), "+f"(d[17]), "+f"(d[18]), "+f"(d[19]), "+f"(d[20]), "+f"(d[21]), "+f"(d[22]), "+f"(d[23]), "+f"(d[24]), "+f"(d[25]), "+f"(d[26]), "+f"(d[27]), "+f"(d[28]), "+f"(d[29]), "+f"(d[30]), "+f"(d[31]), "+f"(d[32]), "+f"(d[33]), "+f"(d[34]), "+f"(d[35]), "+f"(d[36]), "+f"(d[37]), "+f"(d[38]), "+f"(d[39]), "+f"(d[40]), "+f"(d[41]), "+f"(d[42]), "+f"(d[43]), "+f"(d[44]), "+f"(d[45]), "+f"(d[46]), "+f"(d[47]), "+f"(d[48]), "+f"(d[49]), "+f"(d[50]), "+f"(d[51]), "+f"(d[52]), "+f"(d[53]), "+f"(d[54]), "+f"(d[55]), "+f"(d[56]), "+f"(d[57]), "+f"(d[58]), "+f"(d[59]), "+f"(d[60]), "+f"(d[61]), "+f"(d[62]), "+f"(d[63])
    : "r"(alo), "n"(AO), "n"(AH), "r"(blo), "n"(BO), "n"(BH));
}
template<uint32_t AO, uint32_t AH, uint32_t BO, uint32_t BH> __device__ __forceinline__ void mma128_ss0(float (&d)[64], uint32_t alo, uint32_t blo) {
  asm volatile("{\n.reg .pred p;\n.reg .b32 ta, tb;\n.reg .b64 da, db;\nadd.u32 ta, %64, %65;\nmov.b64 da, {ta, %66};\nadd.u32 tb, %67, %68;\nmov.b64 db, {tb, %69};\nsetp.ne.b32 p, 0, 0;\n"
    "wgmma.mma_async.sync.aligned.m64n128k16.f32.bf16.bf16 {%0, %1, %2, %3, %4, %5, %6, %7, %8, %9, %10, %11, %12, %13, %14, %15, %16, %17, %18, %19, %20, %21, %22, %23, %24, %25, %26, %27, %28, %29, %30, %31, %32, %33, %34, %35, %36, %37, %38, %39, %40, %41, %42, %43, %44, %45, %46, %47, %48, %49, %50, %51, %52, %53, %54, %55, %56, %57, %58, %59, %60, %61, %62, %63}, da, db, p, 1, 1, 0, 1;\n}\n"
    : "=f"(d[0]), "=f"(d[1]), "=f"(d[2]), "=f"(d[3]), "=f"(d[4]), "=f"(d[5]), "=f"(d[6]), "=f"(d[7]), "=f"(d[8]), "=f"(d[9]), "=f"(d[10]), "=f"(d[11]), "=f"(d[12]), "=f"(d[13]), "=f"(d[14]), "=f"(d[15]), "=f"(d[16]), "=f"(d[17]), "=f"(d[18]), "=f"(d[19]), "=f"(d[20]), "=f"(d[21]), "=f"(d[22]), "=f"(d[23]), "=f"(d[24]), "=f"(d[25]), "=f"(d[26]), "=f"(d[27]), "=f"(d[28]), "=f"(d[29]), "=f"(d[30]), "=f"(d[31]), "=f"(d[32]), "=f"(d[33]), "=f"(d[34]), "=f"(d[35]), "=f"(d[36]), "=f"(d[37]), "=f"(d[38]), "=f"(d[39]), "=f"(d[40]), "=f"(d[41]), "=f"(d[42]), "=f"(d[43]), "=f"(d[44]), "=f"(d[45]), "=f"(d[46]), "=f"(d[47]), "=f"(d[48]), "=f"(d[49]), "=f"(d[50]), "=f"(d[51]), "=f"(d[52]), "=f"(d[53]), "=f"(d[54]), "=f"(d[55]), "=f"(d[56]), "=f"(d[57]), "=f"(d[58]), "=f"(d[59]), "=f"(d[60]), "=f"(d[61]), "=f"(d[62]), "=f"(d[63])
    : "r"(alo), "n"(AO), "n"(AH), "r"(blo), "n"(BO), "n"(BH));
}

#define XD 600
#define XSTEP 300
#define XPD 450
#define XPB 8192
#define SPG 5600
#define WL0 1800
#define WLS 350
#define NB0 2
#define WP1 2000
#define PF_START 5600
#define PFP 126
#define GPERM 0x76543210u
#define NM0 3
#define PWAIT 600
#define AWAKE 1
#define UPW 0
#define O1ALL 0
#define RDV 1
#define MSTEP 1200
#define MSLP 1000
#define MPOLL 3200
#define LMP 8
#define WOGAP 200
#define CLR0 22000
#define UPGAP 300
#define OUTGAP 150
#define MPROMO P128
#define MLOAD tma_load_ef
struct Ptrs { const bf16 *x, *wmod, *c, *wr, *wqkv; int by_sm; Scratch* s; const bf16 *wg, *wu, *wd, *wo; bf16* out; };

#define BAR(i) (sb + OFF_BAR + 8u * (i))

__device__ __forceinline__ uint32_t get_tag(uint32_t sb) { mbar_wait(BAR(B_TAG), 0); const uint32_t d = __shfl_sync(0xffffffffu, lds32(sb + OFF_CST + 32), 0); return d + 1 + (d & 2); }
__device__ __forceinline__ int d_kb(int n, int hg) {
    if (n < 2) return 2 * hg + n;
    const int h = n >= 9, q = n - 2 - 7 * h;
    return 2 * (q + (q >= hg)) + h;
}

__global__ void __launch_bounds__(NTHREADS, 1)
fused_kernel(const Ptrs p, const __grid_constant__ CUtensorMap tmM, const __grid_constant__ CUtensorMap tmX, const __grid_constant__ CUtensorMap tmW,
             const __grid_constant__ CUtensorMap tmWo, const __grid_constant__ CUtensorMap tmPhi, const __grid_constant__ CUtensorMap tmG,
             const __grid_constant__ CUtensorMap tmU, const __grid_constant__ CUtensorMap tmD, const __grid_constant__ CUtensorMap tmO)
{
    extern __shared__ __align__(1024) uint8_t smem_raw[];
    const uint32_t sb = smem_u32(smem_raw);
    const uint32_t cstart = __shfl_sync(0xffffffffu, clk32(), 0);
    const int tid = threadIdx.x, lane = tid & 31, warp = __shfl_sync(0xffffffffu, tid >> 5, 0);
    if (blockIdx.x < 128) {
        if (warp == 8) asm volatile("prefetch.global.L2 [%0];" :: "l"(p.wmod + (size_t)(blockIdx.x * 8 + (lane >> 2)) * 6144 + (lane & 1) * 64 + (lane & 2) * 512));
        if (warp == 13 && (lane & 1) < NM0 - 2) asm volatile("prefetch.global.L2 [%0];" :: "l"(p.wmod + (size_t)(blockIdx.x * 8 + (lane >> 2)) * 6144 + 128 + (lane & 1) * 64 + (lane & 2) * 512));
        if (warp == 12) l2_prefetch(p.wqkv + (size_t)blockIdx.x * 1536, 3072);
        if (warp == 9) { spin_until(cstart + XPD); l2_prefetch(p.x + (size_t)blockIdx.x * 16384, XPB); }
    }
    if (warp == 10) { tmap_prefetch(&tmM); tmap_prefetch(&tmX); tmap_prefetch(&tmW); }
    if (warp == 11) asm volatile("prefetch.global.L2 [%0];" :: "l"((lane < 16 ? p.c : p.wr) + (lane & 15) * 64));
    #pragma unroll
    for (int i = 0; i < 5; i++) e_init(BAR(5 * warp + i), warp < 5 ? 1 : warp < 7 ? 2 : warp < 9 ? 4 : 8);
    mbar_init_fence();
    if (warp == B_TAG / 5) { e_arrive_tx(BAR(B_TAG), 16); bulk_load(sb + OFF_CST + 32, p.s->done, 16, BAR(B_TAG)); }
    int b;
    {
        uint32_t sm;
        asm("mov.u32 %0, %%smid;" : "=r"(sm));
        const int tp = sm >> 1, u = tp - 32, q = (u * 37) >> 8;
        const int gp = (GPERM >> (4 * (tp < 32 ? tp & 7 : tp < 60 ? 1 + u - 7 * q : 0))) & 7;
        const int sl = 2 * (tp < 32 ? tp >> 3 : tp < 60 ? 4 + q : tp - 58) + (sm & 1);
        b = (tp >> 1) == 30 ? (int)sm + 8 : ((gp >> 1) * 4 + (sl & 3)) * 8 + (gp & 1) * 4 + (sl >> 2);
        if (!p.by_sm) b = blockIdx.x;
    }
    if (b >= 128 && warp == 0) {
        #pragma unroll
        for (int i = 0; i < 2; i++) { e_arrive_tx(BAR(i), 32768); MLOAD(sb + i * 32768u, &tmM, (b & 1) * 1024, (b & 2) * 256 + i * 256, BAR(i)); }
    }
    __syncthreads();

    if (b >= 128) {
        const int sp = b & 3;
        if (warp == 8) {
            #pragma unroll 1
            for (int j = 2, st = 2, ph = 1; j < 64; j++) {
                if (j == 2 * NM0) spin_until(cstart + SPG);
                mbar_wait(BAR(B_EA + st), ph);
                e_arrive_tx(BAR(st), 32768);
                MLOAD(sb + st * 32768u, &tmM, j < 32 ? (sp & 1) * 1024 + (j >> 1) * 64 : 2560 + sp * 512 + (j >> 2) * 64, (j < 32 ? (sp & 2) + (j & 1) : j & 3) * 256, BAR(st));
                if (++st == 6) { st = 0; ph ^= 1; }
            }
        } else if (warp < 8) {
            const int g = lane >> 2, c = lane & 3;
            {
                const bf16* cp = p.c + (tid >> 3) * 32 + (tid & 1) * 16 + (tid & 6);
                const uint32_t c0 = ldg32(cp), c1 = ldg32(cp + 8);
                stg_zero(p.s->llm1 + (tid >> 4) * 64 + sp * 16 + (tid & 15));
                if (tid < 128) stg_zero(p.s->llmod2 + sp * 128 + tid);
                sts64(sb + 200704u + tid * 8, silu2(c0), silu2(c1));
                bar_sync(1, 256);
                TR(57);
            }
            const uint32_t tag = get_tag(sb);
            const uint32_t wa = sb + (warp * 32 + (lane & 7) + (lane >> 4) * 8) * 128u + ((((lane >> 3) & 1) ^ (lane & 7)) << 4);
            float m[4][4];
            #pragma unroll
            for (int i = 0; i < 4; i++) m[i][0] = m[i][1] = m[i][2] = m[i][3] = 0.f;
            #pragma unroll 1
            for (int r = 0, st = 0, ph = 0; r < 32; r++) {
                const int n = r < 16 ? r : (r >> 1) + 8;
                const bf16* wr = p.wr + (sp & 1) * 512 + (n & 7) * 64 + (g & 3) * 16 + 2 * c;
                const uint32_t wr0 = ldg32(wr), wr1 = ldg32(wr + 8);
                const uint32_t sa = sb + 200704u + ((r < 16 ? sp >> 1 : r & 1) * 16 + warp) * 64 + c * 16;
                const uint4 sv0 = lds128(sa), sv1 = lds128(sa + 512);
                uint32_t f[16][4];
                #pragma unroll
                for (int q = 0; q < 2; q++) {
                    mbar_wait(BAR(st + q), ph);
                    if (r == 0 && warp == 0) TR(60 + q);
                    #pragma unroll
                    for (int i = 0; i < 8; i++) ldsm4t(f[8 * q + i], (wa + (st + q) * 32768u + (i >> 2) * 2048u) ^ ((i & 3) << 5));
                }
                #pragma unroll
                for (int i = 0; i < 16; i++) {
                    const uint4& sv = i < 8 ? sv0 : sv1;
                    mma16816(m[i & 3], f[i][0], f[i][1], f[i][2], f[i][3], (i & 4) ? sv.z : sv.x, (i & 4) ? sv.w : sv.y);
                    if ((i & 7) == 7) e_arrive(BAR(B_EA + st + (i >> 3)));
                }
                st += 2; if (st == 6) { st = 0; ph ^= 1; }
                if (r >= 16 && !(r & 1)) continue;
                const uint32_t red = sb + 196608u + (n & 1) * 2048u;
                const uint32_t a = red + warp * 256u + (c * 16 + (g >> 1) * 4 + (g & 1)) * 4u;
                stsf(a, sel4(c, m[0][0], m[1][0], m[2][0], m[3][0])); stsf(a + 8, sel4(c, m[0][2], m[1][2], m[2][2], m[3][2]));
                #pragma unroll
                for (int i = 0; i < 4; i++) m[i][0] = m[i][1] = m[i][2] = m[i][3] = 0.f;
                bar_sync(1, 256);
                if (warp == (n & 7)) {
                    const uint32_t ra = red + (lane >> 4) * 1024u + (lane & 15) * 16u;
                    const uint4 r0 = lds128(ra), r1 = lds128(ra + 256), r2 = lds128(ra + 512), r3 = lds128(ra + 768);
                    #define F4(f) ((u2f(r0.f) + u2f(r1.f)) + (u2f(r2.f) + u2f(r3.f)))
                    float x = F4(x), y = F4(y), z = F4(z), w = F4(w);
                    #undef F4
                    x += shfl_x(x, 16); y += shfl_x(y, 16); z += shfl_x(z, 16); w += shfl_x(w, 16);
                    if (n < 16) {
                        if (lane < 16) st_ll4(p.s->llm1 + n * 64 + sp * 16 + lane, x, y, z, w, tag);
                    } else {
                        uint32_t lo = pack2(x, y), hi2 = pack2(z, w);
                        float d = fmaf(bf_lo(lo), bf_lo(wr0), bf_hi(lo) * bf_hi(wr0)) + fmaf(bf_lo(hi2), bf_lo(wr1), bf_hi(hi2) * bf_hi(wr1));
                        if (sp >= 2) {
                            lo = hadd2(lo, ONE2); hi2 = hadd2(hi2, ONE2);
                            const uint32_t r0 = hmul2(lo, wr0), r1 = hmul2(hi2, wr1);
                            d = (bf_lo(r0) + bf_hi(r0)) + (bf_lo(r1) + bf_hi(r1));
                        }
                        #pragma unroll 1
                        for (int k = 1; k < 16; k <<= 1) d += shfl_x(d, k);
                        if (lane < 16) st_ll(p.s->llmod2 + sp * 128 + (n & 7) * 16 + lane, lo, hi2, f2u(d), tag);
                    }
                    TR(n);
                }
            }
        }
    } else if (warp >= 12) {
        reg_dec<24>();
        const int rb = b >> 3, hg = b & 7;
        const bool ffn = b < 112;
        if (warp == 12) {
            #pragma unroll 1
            for (int j = 0, s = 0, ph = 1; j < 16; j++) {
                if (j < 2) mbar_wait(j ? BAR(B_STS) : BAR(B_STP), 0);
                mbar_wait(BAR(B_EA + s), ph);
                e_arrive_tx(BAR(B_FA + s), 16384); tma_load(sb + OFF_A + s * 16384u, &tmX, j * 64, rb * 128, BAR(B_FA + s));
                if (j == 0) TS(2);
                if (j == 1) GT(0);
                if (j == 6) GT(1);
                if (j == 11) GT(2);
                if (++s == 3) { s = 0; ph ^= 1; }
            }
            tmap_prefetch(&tmO);
            const uint32_t tag = get_tag(sb);
            e_arrive(BAR(B_FD)); e_arrive(BAR(B_FD + 1));
            #pragma unroll 1
            for (int q = 0; q < 3; q++) {
                mbar_wait(q < 2 ? BAR(B_KST + 1 + 2 * q) : BAR(B_OWN), 0);
                poll_flags(q < 2 ? p.s->flk + (q + 1) * 256 + (hg * 16 + (lane & 15)) * 2 : p.s->flo + ((rb & 12) * 16 + lane * 2) * 2, tag);
                if (q == 2) break;
                if (q) mbar_wait(BAR(B_KVT), 0);
                e_arrive_tx(BAR(B_KVL + q), 16896); bulk_load(sb + OFF_KL, p.s->kvacc + hg * 2112 + q * 1056, 16896, BAR(B_KVL + q));
                TS(12 + q);
                if (!q) GT(4);
            }
            TS(3); GT(5);
            const uint4* osrc = p.s->os + (size_t)rb * 16 * 1024;
            #pragma unroll 1
            for (int n = 2; n < 18; n++) {
                const uint32_t s = n & 3, fb = BAR(B_FD + s), dst = sb + OFF_R0 + s * 16384u;
                mbar_wait(BAR(B_ED + s), ((n >> 2) - 1) & 1);
                if (n == 5 || n == 9) mbar_wait(n == 5 ? BAR(B_OST) : BAR(B_O1), 0);
                e_arrive_tx(fb, 16384);
                if (n < 16) bulk_load(dst, osrc + d_kb(n, hg) * 1024, 16384, fb);
                else { e_arrive(fb); tma_load(dst, &tmX, hg * 128 + (n - 16) * 64, rb * 128, fb); }
                TR(32 + n);
            }
            GT(6);
            mbar_wait(BAR(B_CAND), 0);
            GT(7);
            const uint2 lc = lds64(sb + OFF_CST + 16);
            const uint32_t w0 = __shfl_sync(0xffffffffu, lc.x >> 4, 0), w1 = __shfl_sync(0xffffffffu, lc.y >> 4, 0);
            mbar_wait(BAR(B_SWP), 0);
            fence_async_smem();
            #pragma unroll 1
            for (uint32_t w = 0; w < 8; w++)
                if (w != w0 && w != w1) { tma_store4(&tmO, rb * 128 + w * 16, hg * 2, sb + OFF_OUT + w * 4096u); spin_until(clk32() + OUTGAP); }
            mbar_wait(BAR(B_SEL), 0);
            const uint2 sel = lds64(sb + OFF_CST + 24);
            #pragma unroll 1
            for (uint32_t i = 0; i < (w0 == w1 ? 8u : 16u); i++) {
                const uint32_t w = i < 8 ? w0 : w1, r = (i & 7) * 2 + (lane >> 4), row = rb * 128 + w * 16 + r;
                const uint4 o = lds128(sb + OFF_OUT + w * 4096u + ((lane >> 3) & 1) * 2048u + r * 128u + (((lane ^ r) & 7) << 4));
                if (row != sel.x && row != sel.y) stg128(p.out + (size_t)row * 1024 + hg * 128 + (lane & 15) * 8, o);
            }
            bulk_wait_read();
        } else if (warp == 14) {
            const uint32_t fb = ffn ? 65536 : 0;
            e_arrive_tx(BAR(B_GF), fb); e_arrive_tx(BAR(B_UD), fb); e_arrive_tx(BAR(B_UF), fb); e_arrive_tx(BAR(B_WD), fb);
            uint32_t due = cstart + WP1;
            #pragma unroll 1
            for (int i = -2; i < 26; i++) {
                if (i >= 0) {
                    const bf16* a = i < 8 ? p.wg + (size_t)(i * 128 + b) * 3584 : i < 16 ? p.wu + (size_t)((i - 8) * 128 + b) * 3584
                                  : i < 18 ? p.wo + (size_t)(b * 2 + i - 16) * 4096 : p.wd + (size_t)(b * 8 + i - 18) * 3584;
                    sleep_until(due);
                    l2_prefetch(a, (i >> 1) == 8 ? 8192 : 7168);
                    due += 7 * PFP;
                }
                if (i == 1) { tmap_prefetch(&tmPhi); tmap_prefetch(&tmG); tmap_prefetch(&tmWo); tmap_prefetch(&tmU); tmap_prefetch(&tmD); mbar_wait(BAR(B_STS), 0); }
                if (ffn && (uint32_t)(i - 3) < 8u) tma_load_ef(sb + OFF_R0 + (i - 3) * 8192u, &tmG, b * 32, (i - 3) * 128, BAR(B_GF));
                if (ffn && (uint32_t)(i - 11) < 8u) tma_load(sb + OFF_WPHI, &tmU, b * 32, (i - 11) * 128, BAR(B_UD));
                if (i == 19) { mbar_wait(BAR(B_UD), 0); e_arrive_tx(BAR(B_WPHI), 8192); tma_load(sb + OFF_WPHI, &tmPhi, 0, hg * 128, BAR(B_WPHI)); }
                if (i == LMP + 2 * (b & 3) + (b >> 6)) tma_prefetch(&tmM, 2048 + (b >> 6) * 2048 + (b >> 2) * 64, (b & 3) * 256);
                if (i < 13) {
                    sleep_until(due);
                    l2_prefetch(p.wqkv + (size_t)((i + 3) * 128 + b) * 1536, 3072);
                    due += i == -2 ? PF_START - WP1 : 3 * PFP;
                }
            }
            if (lane < 4) stg_zero(p.s->flo + b * 4 + lane);
            const uint32_t tag = get_tag(sb);
            #pragma unroll 1
            for (int q = 0; q < 2; q++) {
                mbar_wait(BAR(B_OWN + q), 0);
                bulk_store(p.s->os + ((size_t)b * 2 + q) * 1024, sb + OFF_R0 + q * 16384u, 16384);
                bulk_wait();
                __syncwarp();
                if (lane == 0) st_flag(p.s->flo + (b * 2 + q) * 2, tag);
                TS(7 + q);
            }
            e_arrive(BAR(B_OST));
        } else {
            uint4* fk = p.s->flk + (hg * 16 + rb) * 2;
            if (warp == 13) {
                #pragma unroll 1
                for (int i = 0; i < 32; i++) {
                    const uint32_t s = i & 3;
                    if (i < NB0) spin_until(cstart + WL0 + WLS * i); else if (i == NB0) mbar_wait(BAR(B_STS), 0);
                    mbar_wait(BAR(B_EB + s), ((i >> 2) - 1) & 1);
                    e_arrive_tx(BAR(B_FB + s), 24576); tma_load4(sb + OFF_B + s * 24576u, &tmW, i * 32, hg * 2, BAR(B_FB + s));
                    TR(64 + i);
                }
                mbar_wait(BAR(B_EB), 1); mbar_wait(BAR(B_EB + 1), 1);
                e_arrive_tx(BAR(B_LMF), 32768); tma_load_ef(sb + OFF_B, &tmM, 2048 + (b >> 6) * 2048 + (b >> 2) * 64, (b & 3) * 256, BAR(B_LMF));
                mbar_wait(BAR(B_LMD), 0);
                #pragma unroll 1
                for (int n = 0; n < 4; n++) {
                    e_arrive_tx(BAR(B_FD + n), 16384); tma_load4(sb + OFF_DB + n * 16384u, &tmWo, d_kb(n, hg) * 64, hg * 2, BAR(B_FD + n));
                    spin_until(clk32() + WOGAP);
                }
            } else {
                sleep_until(cstart + CLR0);
                const uint32_t tag = get_tag(sb);
                #pragma unroll 1
                for (int i = lane; i < 132; i += 32) stg_zero(p.s->kvacc + hg * 2112 + rb * 132 + i);
                if (lane < 4) stg_zero(fk + 256 + (lane >> 1) * 256 + (lane & 1));
                fence_gpu();
                __syncwarp();
                if (lane < 2) st_ll(fk + lane, tag, 0, 0, 0);
                sleep_until(clk32() + 2000);
                poll_flags(p.s->flk + (hg * 16 + (lane & 15)) * 2, tag);
                mbar_wait(BAR(B_QE), 0);
                #pragma unroll 1
                for (int i = 0; i < 4; i++) {
                    stg_zero(p.s->llln2 + b * 128 + i * 32 + lane);
                    stg_zero(p.s->llrowh + (i >> 1) * 8192 + (rb * 2 + (i & 1)) * 256 + hg * 32 + lane);
                    #pragma unroll
                    for (int k = 0; k < 4; k++) stg_zero(p.s->lly + b * 512 + i * 128 + k * 32 + lane);
                }
                if (lane < 2 && hg == 0) stg_zero(p.s->llcand + rb * 2 + lane);
                __syncwarp();
                e_arrive(BAR(B_KZ));
            }
            const int q = warp == 13;
            const uint32_t tag = get_tag(sb);
            mbar_wait(BAR(B_KZ), 0);
            #pragma unroll 1
            for (int h = 2 * q; h < 2 * q + 2; h++) {
                mbar_wait(BAR(B_KST + h), 0);
                uint4* acc = p.s->kvacc + (hg * 4 + h) * 528;
                bulk_reduce(acc, sb + OFF_V + h * 8192u, 8192); bulk_reduce(acc + 512, sb + OFF_ZS + h * 256u, 256);
            }
            bulk_wait();
            if (q) e_arrive(BAR(B_KZ));
            TR(158 + q);
            fence_gpu();
            __syncwarp();
            if (lane == 0) st_flag(fk + 256 + q * 256, tag);
            TS(10 + q);
            if (q) {
                #pragma unroll 1
                for (int n = 4; n < 16; n++) {
                    const uint32_t s = n & 3;
                    mbar_wait(BAR(B_ED + s), ((n >> 2) - 1) & 1);
                    e_arrive_tx(BAR(B_FD + s), 16384);
                    tma_load4(sb + OFF_DB + s * 16384u, &tmWo, d_kb(n, hg) * 64, hg * 2, BAR(B_FD + s));
                    TR(96 + n);
                    if (ffn && n >= 8) {
                        const int z = 8 * (n & 1) + ((n - 8) >> 1);
                        tma_load_ef(sb + OFF_F2 + z * 4096u, &tmD, z * 64, b * 32, BAR(B_WD));
                        tma_load_ef(sb + OFF_F2 + z * 4096u + 16384u, &tmD, z * 64 + 256, b * 32, BAR(B_WD));
                    }
                }
            } else {
                if (ffn) {
                    mbar_wait(UPW ? BAR(B_KVL) : BAR(B_KZ), UPW ? 0 : 1); mbar_wait(BAR(B_KZ), 1);
                    #pragma unroll 1
                    for (int i = 0; i < 8; i++) { tma_load_ef(sb + OFF_F2 + i * 8192u, &tmU, b * 32, i * 128, BAR(B_UF)); sleep_until(clk32() + UPGAP); }
                }
                mbar_wait(BAR(B_OST), 0);
                poll_flags(p.s->flo + (O1ALL ? (rb & 12) * 16 + lane * 2 + 1 : rb * 16 + (lane & 7) * 2 + 1) * 2, tag);
                e_arrive(BAR(B_O1));
                TS(4);
            }
        }
    } else if (warp >= 8) {
        reg_dec<24>();
        const int rb = b >> 3, hg = b & 7, w4 = warp & 3, g = lane >> 2, c = lane & 3, t = tid & 127;
        const uint32_t sv = silu2(ldg32(p.c + (b & 3) * 256 + 2 * t)), tag = get_tag(sb);
        if (w4 < 3) {
            spin_until(cstart + MPOLL + MSTEP * w4);
            #pragma unroll 1
            for (int j = w4, ph = 1; j < 16; j += 3, ph ^= 1) {
                uint4 w[2];
                poll_words<2, 0, 3>(w, p.s->llm1 + j * 64 + lane, 32, tag);
                uint32_t lo = pack2(u2f(w[0].x) + u2f(w[1].x), u2f(w[0].y) + u2f(w[1].y)), hi = pack2(u2f(w[0].z) + u2f(w[1].z), u2f(w[0].w) + u2f(w[1].w));
                if (lane >= 16) { lo = hadd2(lo, ONE2); hi = hadd2(hi, ONE2); }
                sts64(sb + OFF_TAB + j * 256 + (lane & 15) * 16 + (lane < 16 ? 8 : 0), lo, hi);
                __syncwarp();
                if (j == 0) TS(5);
                TR(16 + j);
                mbar_wait(BAR(B_EA + w4), ph);
                e_arrive(BAR(B_FA + w4));
                __nanosleep(MSLP);
            }
        }
        mbar_wait(BAR(B_QE), 0);
        if (warp == 8) GT(3);
        sts32(sb + OFF_KL + w4 * 1024u + lane * 4, sv);
        fence_async_smem();
        bar_sync(2, 128);
        reg_inc<56>();
        {
            float m0[4], m1[4];
            const uint32_t da = desc_lo(sb + OFF_B, 16), db = desc_lo(sb + OFF_KL, 16);
            mbar_wait(BAR(B_LMF), 0);
            wg_fence();
            #define LMS(f, i) f<(i) * 256, H128, ((i) >> 1) * 64 + ((i) & 1) * 4, H128>(m0, da, db); f<(i) * 256 + 128, H128, ((i) >> 1) * 64 + ((i) & 1) * 4 + 2, H128>(m1, da, db)
            LMS(mma8_tn0, 0); LMS(mma8_tn, 1); LMS(mma8_tn, 2); LMS(mma8_tn, 3); LMS(mma8_tn, 4); LMS(mma8_tn, 5); LMS(mma8_tn, 6); LMS(mma8_tn, 7);
            #undef LMS
            wg_commit();
            wg_wait<0>();
            acc_fence(m0); acc_fence(m1);
            e_arrive(BAR(B_LMD));
            const float v0 = m0[0] + m1[0], v1 = m0[2] + m1[2], u0 = shfl_x(v0, 4), u1 = shfl_x(v1, 4);
            if (!(lane & 7)) st_ll4(p.s->llg + (b >> 6) * 1024 + (b & 3) * 256 + ((b >> 2) & 15) * 16 + w4 * 4 + (lane >> 3), v0, u0, v1, u1, tag);
            if (warp == 8) TR(150);
        }
        #pragma unroll 1
        for (int h = 0; h < 4; h++) {
            float okv[20];
            const uint32_t vb = OFF_V + h * 8192u, dp = desc_lo(sb + OFF_PHI + (h & 1) * 16384u, 16), dv = desc_lo(sb + vb, OFF_ONES - vb);
            mbar_wait(BAR(B_PF + h), 0);
            fence_async_smem();
            wg_fence();
            #define KVS(i) mma40_tt<(i) * 128, H128, (i) * (64u - (64u << 16)), H64>(okv, dp, dv)
            mma40_tt0<0, H128, 0, H64>(okv, dp, dv); KVS(1); KVS(2); KVS(3); KVS(4); KVS(5); KVS(6); KVS(7);
            #undef KVS
            wg_commit();
            wg_wait<0>();
            acc_fence(okv);
            if (h < 2) e_arrive(BAR(B_PE + h));
            bar_sync(2, 128);
            #pragma unroll
            for (int k = 0; k < 4; k++) sts128(sb + vb + (k * 128 + t) * 16u, make_uint4(f2u(okv[4 * k]), f2u(okv[4 * k + 1]), f2u(okv[4 * k + 2]), f2u(okv[4 * k + 3])));
            if (c == 0) sts64(sb + OFF_ZS + h * 256u + (w4 * 8 + g) * 8u, f2u(okv[16]), f2u(okv[18]));
            fence_async_smem();
            __syncwarp();
            e_arrive(BAR(B_KST + h));
            if (warp == 8) TR(151 + h);
        }
        reg_dec<24>();
        #pragma unroll 1
        for (int q = 0; q < 2; q++) {
            mbar_wait(q ? BAR(B_OWN) : BAR(B_STP), q ^ 1);
            mbar_wait(BAR(B_KVL + q), 0);
            const uint32_t f = w4 * 16 + g;
            #pragma unroll 1
            for (int hh = 0; hh < 2; hh++) {
                const uint32_t kl = sb + OFF_KL + hh * 8448u, a = sb + OFF_KVT + hh * 4096u + f * 64u + ((g >> 1) << 4) + 4 * c;
                #pragma unroll
                for (int k = 0; k < 4; k += 2) {
                    const uint4 v0 = lds128(kl + (k * 128 + t) * 16u), v1 = lds128(kl + (k * 128 + 128 + t) * 16u);
                    sts32(a ^ (k << 4), pack2(u2f(v0.x), u2f(v0.y))); sts32((a ^ (k << 4)) + 512, pack2(u2f(v0.z), u2f(v0.w)));
                    sts32(a ^ ((k + 1) << 4), pack2(u2f(v1.x), u2f(v1.y))); sts32((a ^ ((k + 1) << 4)) + 512, pack2(u2f(v1.z), u2f(v1.w)));
                }
                const float z = ldsf(kl + 8192u + (w4 * 8 + g) * 8u + (c & 1) * 4);
                const uint32_t zz = pack2(z, z);
                sts64(sb + OFF_Z + (f + 8 * (c & 1)) * 64u + ((hh ^ (g >> 1)) << 4) + (c >> 1) * 8, zz, zz);
            }
            fence_async_smem();
            __syncwarp();
            e_arrive(BAR(B_KVT + q));
            if (warp == 8) TR(155 + q);
        }
        mbar_wait(BAR(B_O1), 0);
        if (w4 == 0 || w4 == 3) {
            float s[4] = {0.f, 0.f, 0.f, 0.f};
            #pragma unroll 1
            for (int k = 0; k < 2; k++) {
                uint4 w[2];
                poll_words<2, 0, 3>(w, p.s->llg + (w4 & 1) * 1024 + k * 512 + hg * 32 + lane, 256, tag);
                s[0] += u2f(w[0].x) + u2f(w[1].x); s[1] += u2f(w[0].y) + u2f(w[1].y); s[2] += u2f(w[0].z) + u2f(w[1].z); s[3] += u2f(w[0].w) + u2f(w[1].w);
            }
            sts64(w4 ? sb + OFF_T3 + lane * 8 : sb + OFF_T1 + lane * 16, pack2(s[0], s[1]), pack2(s[2], s[3]));
        } else {
            const bf16* wr = p.wr + hg * 128 + g * 16 + 2 * c;
            const uint32_t wr0 = ldg32(wr), wr1 = ldg32(wr + 8);
            uint4 w[2];
            poll_words<2, 1>(w, p.s->llmod2 + (w4 - 1) * 256 + hg * 32 + lane, (lane & 15) * 16 - hg * 32 - lane, tag);
            sts64(sb + OFF_T2 + lane * 16 + (w4 & 1) * 8, w[0].x, w[0].y);
            if (w4 == 2) sts64(sb + OFF_T1 + lane * 16 + 8, hmul2(w[0].x, wr0), hmul2(w[0].y, wr1));
            float d = u2f(w[1].z);
            #pragma unroll 1
            for (int k = 1; k < 16; k <<= 1) d += shfl_x(d, k);
            stsf(sb + OFF_CST + 8 + (w4 & 1) * 4, d);
        }
        __syncwarp();
        e_arrive(BAR(B_PAR));
        if (warp == 9) TS(6);
        if (w4 < 2) {
            mbar_wait(BAR(B_KEYS), 0);
            const uint4 kk = lds128(sb + OFF_KEY + lane * 16);
            uint32_t k[4] = {kk.x, kk.y, kk.z, kk.w}, b0, b1;
            top2<4>(k, b0, b1);
            const uint32_t key = w4 ? b1 : b0, cd = 127 - (key & 127u), slot = rb * 2 + w4;
            const uint4 st = lds128(sb + OFF_ST2 + cd * 16), ta = lds128(sb + OFF_T2 + lane * 16);
            const uint2 gb = lds64(sb + OFF_T3 + lane * 8);
            const uint32_t xa = sb + OFF_R0 + (g >> 2) * 16384u + cd * 128u + ((((g & 3) * 2) ^ (cd & 7)) << 4) + c * 4;
            const uint32_t x0 = lds32(xa), x1 = lds32(xa ^ 16);
            if (hg == 0 && lane == 0) st_ll(p.s->llcand + slot, key, rb * 128 + cd, st.w, tag);
            uint4* d = p.s->llrowh + slot * 256 + hg * 32 + lane;
            st_ll(d, lnmod(x0, st.x, st.y, st.z, ta.x, ta.z), lnmod(x1, st.x, st.y, st.z, ta.y, ta.w), gb.x, tag);
            st_ll(d + 8192, x0, x1, gb.y, tag);
            sts32(sb + OFF_CST + 16 + w4 * 4, cd);
            __syncwarp();
            e_arrive(BAR(B_CAND));
            if (warp == 8) TS(9);
        }
    } else {
        reg_inc<232>();
        float a0[96], a1[96];
        {
            const int g = lane >> 2, c = lane & 3;
            uint4* stp = p.s->llstat + b * 16 + warp * 2 + (lane >> 4);
            if ((lane & 15) == 0) stg_zero(stp);
            spin_until(cstart + XD + XSTEP * warp);
            e_arrive_tx(BAR(B_XP + warp), 4096);
            bulk_load(sb + OFF_R0 + warp * 4096u, p.x + (size_t)(b * 16 + 2 * warp) * 1024, 4096, BAR(B_XP + warp));
            const uint32_t tag = get_tag(sb);
            if (tid < 64) sts128(sb + OFF_ONES + tid * 16, make_uint4(ONE2, ONE2, ONE2, ONE2));
            if (tid == 64) sts64(sb + OFF_CST, b, tag);
            if (AWAKE & 1) mbar_wait_awake(BAR(B_XP + warp), 0); else mbar_wait(BAR(B_XP + warp), 0);
            e_arrive(BAR(B_STP));
            if (warp == 7) TS(14);
            float s[2][4], q0[2][4], q1[2][4];
            #pragma unroll
            for (int i = 0; i < 4; i++) s[0][i] = s[1][i] = q0[0][i] = q0[1][i] = q1[0][i] = q1[1][i] = 0.f;
            #pragma unroll
            for (int i = 0; i < 4; i++) {
                const uint4 x0 = lds128(sb + OFF_R0 + warp * 4096u + (lane + 32 * i) * 16u), x1 = lds128(sb + OFF_R0 + warp * 4096u + 2048u + (lane + 32 * i) * 16u);
                mma16816(s[0], x0.x, x1.x, x0.y, x1.y, ONE2, ONE2); mma16816(s[1], x0.z, x1.z, x0.w, x1.w, ONE2, ONE2);
                mma16816(q0[0], x0.x, x1.x, x0.y, x1.y, x0.x, x0.y); mma16816(q0[1], x0.z, x1.z, x0.w, x1.w, x0.z, x0.w);
                mma16816(q1[0], x0.x, x1.x, x0.y, x1.y, x1.x, x1.y); mma16816(q1[1], x0.z, x1.z, x0.w, x1.w, x1.z, x1.w);
            }
            const bool dg = c == (g >> 1);
            const float s0 = dg ? s[0][0] + s[1][0] : 0.f, s1 = dg ? s[0][2] + s[1][2] : 0.f;
            const float sq0 = dg ? ((g & 1) ? q0[0][1] + q0[1][1] : q0[0][0] + q0[1][0]) : 0.f, sq1 = dg ? ((g & 1) ? q1[0][3] + q1[1][3] : q1[0][2] + q1[1][2]) : 0.f;
            const bool up = lane >= 16;
            float sm = (up ? s1 : s0) + shfl_x(up ? s0 : s1, 16), sq = (up ? sq1 : sq0) + shfl_x(up ? sq0 : sq1, 16);
            #pragma unroll
            for (int m = 8; m >= 1; m >>= 1) { sm += shfl_x(sm, m); sq += shfl_x(sq, m); }
            uint32_t m2, rh, rl; float rinv;
            ln_final(sm, sq, m2, rinv);
            split_rcp(rinv, rh, rl);
            if ((lane & 15) == 0) st_ll(stp, m2, rh, rl, tag);
            if (warp == 7) TS(15);
            uint4 st[2];
            if (PWAIT) { mbar_wait(BAR(B_STP), 0); if (warp < 7) spin_until(clk32() + PWAIT); }
            #pragma unroll 1
            for (int it = 0; it < POLL_MAX; it++) {
                st[0] = ld_ll(p.s->llstat + (b >> 3) * 128 + warp * 16 + g); st[1] = ld_ll(p.s->llstat + (b >> 3) * 128 + warp * 16 + g + 8);
                const uint32_t o = RDV ? ld_rlx(&p.s->llstat[((b >> 5) * 4 + c) * 128 + warp * 16 + 15].w) : tag;
                if (__all_sync(0xffffffffu, !tag_bad(tag_bad(o ^ tag, st[0].w, tag), st[1].w, tag))) break;
                if (AWAKE & 1) it += awake_zero();
            }
            e_arrive(BAR(B_STS));
            if (warp == 0) TS(16);
            const uint32_t lrow = warp * 16 + (lane & 15);
            uint32_t aad = sb + OFF_A + lrow * 128u + (((lane >> 4) ^ (lrow & 7)) << 4);
            uint32_t tad = sb + OFF_TAB + c * 16, ab = BAR(B_FA), pa = 0;
            uint32_t f0[4], f1[4];
            #define PREP(f, q) do { \
                const uint4 t = lds128(tad + (q) * 64); \
                ldsm4(f, aad ^ ((q) << 5)); \
                f[0] = lnmod(f[0], st[0].x, st[0].y, st[0].z, t.x, t.z); f[1] = lnmod(f[1], st[1].x, st[1].y, st[1].z, t.x, t.z); \
                f[2] = lnmod(f[2], st[0].x, st[0].y, st[0].z, t.y, t.w); f[3] = lnmod(f[3], st[1].x, st[1].y, st[1].z, t.y, t.w); } while (0)
            #define MMA(f, off) do { wg_fence(); mma192_rs<(off), H128>(a0, f, blo); mma192_rs<(off) + 768, H128>(a1, f, blo); wg_commit(); wg_wait<1>(); } while (0)
            mbar_wait(ab, 0);
            PREP(f0, 0);
            if (RDV) mbar_wait(BAR(B_STS), 0);
            #pragma unroll 1
            for (int j = 0; j < 16; j++) {
                const uint32_t bb = BAR(B_FB) + (j & 1) * 16, blo = desc_lo(sb + OFF_B, 4096) + (j & 1) * 3072, pb = (j >> 1) & 1;
                mbar_wait(bb, pb);
                wg_fence(); mma192_rsp<0, H128>(a0, f0, blo, j); mma192_rsp<768, H128>(a1, f0, blo, j); wg_commit(); wg_wait<1>();
                if (j) e_arrive((bb ^ 16) + 8 * (B_EB - B_FB) + 8);
                PREP(f1, 1);
                MMA(f1, 128);
                PREP(f0, 2);
                mbar_wait(bb + 8, pb);
                MMA(f0, 1536);
                e_arrive(bb + 8 * (B_EB - B_FB));
                PREP(f1, 3);
                MMA(f1, 1536 + 128);
                e_arrive(ab + 8 * (B_EA - B_FA));
                ab += 8; aad += 16384; tad += 256;
                if (ab == BAR(B_FA + 3)) { ab -= 24; aad -= 49152; pa ^= 1; }
                if (j < 15) mbar_wait(ab, pa);
                PREP(f0, 0);
            }
            #undef PREP
            #undef MMA
        }
        int tid_o; asm volatile("mov.u32 %0, %%tid.x;" : "=r"(tid_o) :: "memory");
        const int tid = tid_o, lane = tid & 31, warp = __shfl_sync(0xffffffffu, tid >> 5, 0), wgi = warp >> 2, g = lane >> 2, c = lane & 3;
        const uint32_t srow = warp * 16 + (lane & 15);
        const uint32_t t128 = srow * 128u + (((lane >> 4) ^ (srow & 7)) << 4);
        mbar_wait(BAR(B_WPHI), 0);
        mbar_wait(BAR(B_EA), 1);
        wg_wait<0>();
        acc_fence(a0); acc_fence(a1);
        e_arrive(BAR(B_QE));
        if (warp == 0) TS(18);
        uint32_t ph0[16], ph1[16], pk[16], mm[4];
        float ea[32], eb[32];
        #define PIN() do { acc_fence(ea); acc_fence(eb); pin<16>(pk); pin<4>(mm); } while (0)
        {
            uint32_t kq[32];
            float p0[16], p1[16];
            const uint32_t dw = desc_lo(sb + OFF_WPHI, 16);
            #define PMMA(f, o) do { wg_fence(); mma32_rs0<(o), H64>(p0, f, dw); mma32_rs0<(o) + 128, H64>(p1, f + 8, dw); \
                mma32_rs<(o) + 64, H64>(p0, f + 4, dw); mma32_rs<(o) + 192, H64>(p1, f + 12, dw); wg_commit(); } while (0)
            #define V_OUT(lo) _Pragma("unroll") for (int i = lo; i < lo + 4; i++) { const int o = 32 + 8 * i; \
                stsm4(sb + OFF_V + (i >> 1) * 8192u + srow * 64u + (((2 * (i & 1) + (lane >> 4)) ^ ((srow >> 1) & 3)) << 4), \
                      pack2(a1[o], a1[o + 1]), pack2(a1[o + 2], a1[o + 3]), pack2(a1[o + 4], a1[o + 5]), pack2(a1[o + 6], a1[o + 7])); }
            V_OUT(0);
            #pragma unroll
            for (int i = 0; i < 16; i++) ph0[i] = pack2(a0[64 + 2 * i], a0[65 + 2 * i]);
            PMMA(ph0, 0);
            V_OUT(4);
            #undef V_OUT
            wg_wait<0>();
            acc_fence(p0); acc_fence(p1);
            fm_max(p0, pk, mm); fm_max(p1, pk + 8, mm + 2);
            #pragma unroll
            for (int i = 0; i < 16; i++) ph1[i] = pack2(a1[2 * i], a1[2 * i + 1]);
            PMMA(ph1, 256);
            fm_args(pk, mm, ea);
            if (warp == 0) TS(19);
            fm_exp<0, 16>(ea);
            #pragma unroll
            for (int i = 0; i < 32; i++) kq[i] = pack2(a0[2 * i], a0[2 * i + 1]);
            acc_fence(ea); pin<32>(kq);
            wg_wait<0>();
            acc_fence(p0); acc_fence(p1);
            #define PHI_OUT(ph, i) do { if (u < 2) { \
                    mbar_wait(u ? BAR(B_PE + (i)) : (i) ? BAR(B_LMD) : BAR(B_QE), 0);          \
                    _Pragma("unroll") for (int q = 0; q < 4; q++) stsm4((sb + OFF_PHI + (i) * 16384u + t128) ^ (q << 5), ph[4 * q], ph[4 * q + 1], ph[4 * q + 2], ph[4 * q + 3]); \
                    __syncwarp(); \
                    e_arrive(BAR(B_PF + (i)) + u * 16); } } while (0)
            reg_dec<216>();
            #pragma unroll 1
            for (int u = 0; u < 3; u++) {
                fm_exp<16, 32>(ea); fm_args(pk + 8, mm + 2, eb);
                PIN();
                if (warp == 0) TR(129 + u * 6);
                fm_exp<0, 16>(eb); fm_norm(ea, ph0); fm_max(p0, pk, mm);
                acc_fence(eb); pin<8>(pk); pin<2>(mm);
                PHI_OUT(ph0, 0);
                if (warp == 0) TR(130 + u * 6);
                fm_exp<16, 32>(eb); fm_args(pk, mm, ea); fm_max(p1, pk + 8, mm + 2);
                PIN();
                if (warp == 0) TR(131 + u * 6);
                if (u == 0) PMMA(kq, 0); else PMMA(kq + 16, 256);
                fm_exp<0, 16>(ea); fm_norm(eb, ph1);
                acc_fence(ea);
                if (warp == 0) TR(132 + u * 6);
                PHI_OUT(ph1, 1);
                wg_wait<0>();
                acc_fence(p0); acc_fence(p1);
                if (u == 1) e_arrive(BAR(B_STP));
                if (warp == 0) TR(133 + u * 6);
                if (warp == 0) TS(22 + u);
            }
            #undef PHI_OUT
            #undef PMMA
        }
        uint32_t gf[16][4], uf[16][4];
        const uint32_t fo = (warp >> 1) * 16384u + ((lane & 7) + (lane >> 4) * 8) * 64u + (((2 * (warp & 1) + ((lane >> 3) & 1)) ^ ((lane >> 1) & 3)) << 4);
        mbar_wait(BAR(B_GF), 0);
        #pragma unroll
        for (int i = 0; i < 16; i++) ldsm4t(gf[i], sb + OFF_R0 + fo + i * 1024u);
        e_arrive(BAR(B_STS));
        #define O_BLOCK(pp) do { \
            if ((AWAKE & 2) && !(pp)) mbar_wait_awake(BAR(B_KVT + (pp)), 0); else mbar_wait(BAR(B_KVT + (pp)), 0); \
            if (warp == 0) TS(25 + 3 * (pp)); \
            float o0[20], o1[20]; \
            const uint32_t dk = desc_lo(sb + OFF_KVT, OFF_Z - OFF_KVT); \
            constexpr uint32_t K1 = 256u - (255u << 16);          \
            wg_fence(); \
            mma40_rs0<0, H64>(o0, ph0, dk); mma40_rs0<K1, H64>(o1, ph1, dk); \
            mma40_rs<64, H64>(o0, ph0 + 4, dk); mma40_rs<K1 + 64, H64>(o1, ph1 + 4, dk); \
            mma40_rs<128, H64>(o0, ph0 + 8, dk); mma40_rs<K1 + 128, H64>(o1, ph1 + 8, dk); \
            mma40_rs<192, H64>(o0, ph0 + 12, dk); mma40_rs<K1 + 192, H64>(o1, ph1 + 12, dk); \
            wg_commit(); \
            wg_wait<0>(); \
            acc_fence(o0); acc_fence(o1); \
            if (warp == 0) TS(26 + 3 * (pp)); \
            if (!(pp)) mbar_wait(BAR(B_STS), 1);          \
            _Pragma("unroll") for (int hh = 0; hh < 2; hh++) { \
                const float (&o)[20] = hh ? o1 : o0; \
                uint32_t h0, l0, h1, l1; \
                split_rcp(rcp(rbf(rbf(o[16]) + 1e-6f)), h0, l0); split_rcp(rcp(rbf(rbf(o[18]) + 1e-6f)), h1, l1); \
                _Pragma("unroll") for (int q = 0; q < 2; q++) \
                    stsm4((sb + OFF_R0 + (pp) * 16384u + t128) ^ ((2 * hh + q) << 5), hdiv2(pack2(o[8 * q], o[8 * q + 1]), h0, l0), hdiv2(pack2(o[8 * q + 2], o[8 * q + 3]), h1, l1), \
                          hdiv2(pack2(o[8 * q + 4], o[8 * q + 5]), h0, l0), hdiv2(pack2(o[8 * q + 6], o[8 * q + 7]), h1, l1)); \
            } \
            fence_async_smem(); \
            __syncwarp(); \
            e_arrive(BAR(B_OWN + (pp))); \
            if (warp == 0) TS(27 + 3 * (pp)); \
        } while (0)
        float acc[64];
        const uint32_t da = desc_lo(sb + OFF_R0 + wgi * 8192u, 16), db = desc_lo(sb + OFF_DB, 8192);
        #define D_MMA(first, s) do { \
            wg_fence(); \
            first<(s) * 1024, H128, (s) * 1024, H128>(acc, da, db); mma128_ss<(s) * 1024 + 2, H128, (s) * 1024 + 128, H128>(acc, da, db); \
            mma128_ss<(s) * 1024 + 4, H128, (s) * 1024 + 256, H128>(acc, da, db); mma128_ss<(s) * 1024 + 6, H128, (s) * 1024 + 384, H128>(acc, da, db); \
            wg_commit(); } while (0)
        O_BLOCK(0);
        fm_exp<16, 32>(ea); fm_args(pk + 8, mm + 2, eb);
        acc_fence(ea); acc_fence(eb);
        fm_exp<0, 16>(eb); fm_norm(ea, ph0);
        acc_fence(eb); pin<16>(ph0);
        reg_inc<232>();
        mbar_wait(BAR(B_OWN), 0);
        mbar_wait(BAR(B_FD), 0);
        D_MMA(mma128_ss0, 0);
        fm_exp<16, 32>(eb); fm_norm(eb, ph1);
        O_BLOCK(1);
        e_arrive(BAR(B_ED));
        mbar_wait(BAR(B_OWN + 1), 0);
        #undef PIN
        #undef O_BLOCK
        #define D_STEP(n) do { \
            mbar_wait(BAR(B_FD + ((n) & 3)), ((n) >> 2) & 1); \
            if (warp == 0) TR(112 + (n)); \
            D_MMA(mma128_ss, (n) & 3); \
            if ((n) == 3) mbar_wait(BAR(B_UF), 0); \
            if ((n) >= 3 && (n) < 11) { ldsm4t(uf[2 * (((n) + 5) & 7)], sb + OFF_F2 + fo + (((n) + 5) & 7) * 2048u); ldsm4t(uf[2 * (((n) + 5) & 7) + 1], sb + OFF_F2 + fo + (((n) + 5) & 7) * 2048u + 1024u); } \
            wg_wait<1>(); \
            if ((n) > 1) e_arrive(BAR(B_ED + (((n) + 3) & 3))); } while (0)
        D_STEP(1); D_STEP(2);
        if (warp == 0) TS(31);
        D_STEP(3); D_STEP(4); D_STEP(5); D_STEP(6); D_STEP(7); D_STEP(8); D_STEP(9); D_STEP(10); D_STEP(11); D_STEP(12); D_STEP(13); D_STEP(14); D_STEP(15);
        #undef D_STEP
        #undef D_MMA
        mbar_wait(BAR(B_PAR), 0);
        mbar_wait(BAR(B_FD), 0); mbar_wait(BAR(B_FD + 1), 0);
        wg_wait<0>();
        acc_fence(acc);
        e_arrive(BAR(B_ED + 3));
        if (warp == 0) TS(32);
        uint32_t x2[8][4];
        const uint4 cst = lds128(sb + OFF_CST);
        const int b = cst.x;
        const uint32_t tag = cst.y;
        {
            float sd[4] = {0.f, 0.f, 0.f, 0.f}, qa[4] = {0.f, 0.f, 0.f, 0.f}, qb[4] = {0.f, 0.f, 0.f, 0.f};
            #pragma unroll
            for (int i = 0; i < 8; i++) {
                const uint4 t = lds128(sb + OFF_T1 + i * 64 + c * 16);
                ldsm4(x2[i], (sb + OFF_R0 + (i >> 2) * 16384u + t128) ^ ((i & 3) << 5));
                x2[i][0] = hadd2(x2[i][0], hmul2(t.x, pack2(acc[8 * i], acc[8 * i + 1]))); x2[i][1] = hadd2(x2[i][1], hmul2(t.x, pack2(acc[8 * i + 2], acc[8 * i + 3])));
                x2[i][2] = hadd2(x2[i][2], hmul2(t.y, pack2(acc[8 * i + 4], acc[8 * i + 5]))); x2[i][3] = hadd2(x2[i][3], hmul2(t.y, pack2(acc[8 * i + 6], acc[8 * i + 7])));
                mma16816(sd, x2[i][0], x2[i][1], x2[i][2], x2[i][3], (g & 1) ? t.z : ONE2, (g & 1) ? t.w : ONE2);
                mma16816(qa, x2[i][0], x2[i][1], x2[i][2], x2[i][3], x2[i][0], x2[i][2]);
                mma16816(qb, x2[i][0], x2[i][1], x2[i][2], x2[i][3], x2[i][1], x2[i][3]);
            }
            if (c == (g >> 1)) {
                uint4* d = p.s->llln2 + b * 128 + warp * 16 + g;
                st_ll(d, f2u(sd[0]), f2u((g & 1) ? qa[1] : qa[0]), f2u(sd[1]), tag);
                st_ll(d + 8, f2u(sd[2]), f2u((g & 1) ? qb[3] : qb[2]), f2u(sd[3]), tag);
            }
        }
        if (warp == 0) TS(33);
        #pragma unroll
        for (int i = 0; i < 8; i++) stsm4((sb + OFF_R0 + (i >> 2) * 16384u + t128) ^ ((i & 3) << 5), x2[i][0], x2[i][1], x2[i][2], x2[i][3]);
        {
            uint4 w[4];
            const uint32_t rl = warp * 16 + g + 8 * (c & 1);
            poll_words<4, 0, ~0u, AWAKE & 4>(w, p.s->llln2 + ((b & ~7) + (c >> 1) * 4) * 128 + rl, 128, tag);
            float s1 = (u2f(w[0].x) + u2f(w[1].x)) + (u2f(w[2].x) + u2f(w[3].x));
            float s2 = (u2f(w[0].y) + u2f(w[1].y)) + (u2f(w[2].y) + u2f(w[3].y));
            float dt = (u2f(w[0].z) + u2f(w[1].z)) + (u2f(w[2].z) + u2f(w[3].z));
            s1 += shfl_x(s1, 2); s2 += shfl_x(s2, 2); dt += shfl_x(dt, 2);
            uint32_t m2, rh, rl2; float rinv;
            ln_final(s1, s2, m2, rinv);
            split_rcp(rinv, rh, rl2);
            const float rkey = fmaf(fmaf(-bf_lo(m2), u2f(cst.z), dt), rinv, u2f(cst.w));
            if (c < 2) { sts32(sb + OFF_KEY + rl * 4, (f2key(rkey) & ~127u) | (127 - rl)); sts128(sb + OFF_ST2 + rl * 16, make_uint4(m2, rh, rl2, f2u(rkey))); }
            __syncwarp();
            e_arrive(BAR(B_KEYS));
        }
        if (warp == 0) TS(34);
        {
            const uint4 s0 = lds128(sb + OFF_ST2 + (warp * 16 + g) * 16), s1 = lds128(sb + OFF_ST2 + (warp * 16 + g + 8) * 16);
            mbar_wait(BAR(B_ED + 3), 1);
            const uint32_t oa = sb + OFF_OUT + warp * 2048u + t128;
            #pragma unroll
            for (int i = 0; i < 8; i++) {
                const uint4 t = lds128(sb + OFF_T2 + i * 64 + c * 16);
                const uint2 gb = lds64(sb + OFF_T3 + i * 32 + c * 8);
                stsm4((oa + (i >> 2) * 2048u) ^ ((i & 3) << 5),
                      hadd2(x2[i][0], hmul2(gb.x, lnmod(x2[i][0], s0.x, s0.y, s0.z, t.x, t.z))), hadd2(x2[i][1], hmul2(gb.x, lnmod(x2[i][1], s1.x, s1.y, s1.z, t.x, t.z))),
                      hadd2(x2[i][2], hmul2(gb.y, lnmod(x2[i][2], s0.x, s0.y, s0.z, t.y, t.w))), hadd2(x2[i][3], hmul2(gb.y, lnmod(x2[i][3], s1.x, s1.y, s1.z, t.y, t.w))));
            }
            __syncwarp();
            e_arrive(BAR(B_SWP));
        }
        if (warp == 0) TS(35);
        uint32_t df[16][4];
        mbar_wait(BAR(B_WD), 0);
        #pragma unroll
        for (int i = 0; i < 16; i++)
            ldsm4t(df[i], (sb + OFF_F2 + warp * 8192u + (i >> 3) * 4096u + (i & 1) * 2048u + ((lane & 7) + (lane >> 4) * 8) * 128u + ((((lane >> 3) & 1) ^ (lane & 7)) << 4)) ^ (((i >> 1) & 3) << 5));
        uint32_t fx = 0, fh = 0, fg = 0, frow, fr;
        {
            uint4 v[1];
            poll_words<1, 0, ~0u, AWAKE & 4>(v, p.s->llcand + lane, 0, tag);
            uint32_t k[1] = {(v[0].x & ~127u) | (63 - lane)}, b0, b1;
            top2<1>(k, b0, b1);
            if (warp == 0) TS(36);
            const uint32_t slot0 = 63 - (b0 & 127u), slot1 = 63 - (b1 & 127u), slot = (g & 1) ? slot1 : slot0;
            frow = __shfl_sync(0xffffffffu, v[0].y, slot); fr = __shfl_sync(0xffffffffu, v[0].z, slot);
            const int wd = b * 2 + (c >> 1);
            uint4 hv[2], fv[2];
            #pragma unroll 1
            for (int it = 0; it < POLL_MAX; it++) {
                hv[0] = ld_ll(p.s->llrowh + slot0 * 256 + tid); hv[1] = ld_ll(p.s->llrowh + slot1 * 256 + tid);
                uint32_t bad = 0;
                if (warp == 0) {
                    fv[0] = ld_ll(p.s->llrowx + slot * 256 + wd); fv[1] = ld_ll(p.s->llrowh + slot * 256 + wd);
                    bad = tag_bad(fv[0].w ^ tag, fv[1].w, tag);
                    fx = (g & 2) ? fv[0].y : fv[0].x; fh = (g & 2) ? fv[1].y : fv[1].x; fg = (g & 2) ? fv[0].z : fv[1].z;
                }
                if (__all_sync(0xffffffffu, !ll_bad<1>(ll_bad<1>(bad, hv[0], tag), hv[1], tag))) break;
            }
            const uint32_t ha = sb + OFF_HSEL + (tid >> 3) * 128u + c * 16u + (g & 1) * 8u;
            sts64(ha, hv[0].x, hv[0].y); sts64(ha + 64, hv[1].x, hv[1].y);
            if (warp == 0) {
                if (lane < 8 && c == 0) sts32(sb + OFF_CST + 24 + g * 4, frow);
                __syncwarp();
                e_arrive(BAR(B_SEL));
            }
        }
        bar_sync(2 + (warp >> 1), 64);
        if (warp == 0) TS(37);
        {
            float ag[2][4], au[2][4];
            #pragma unroll
            for (int i = 0; i < 4; i++) ag[0][i] = ag[1][i] = au[0][i] = au[1][i] = 0.f;
            #pragma unroll
            for (int i = 0; i < 8; i++) {
                const uint4 h = lds128(sb + OFF_HSEL + (warp >> 1) * 1024u + i * 128u + (lane & 7) * 16u);
                mma16816(ag[0], gf[2 * i][0], gf[2 * i][1], gf[2 * i][2], gf[2 * i][3], h.x, h.y);
                mma16816(au[0], uf[2 * i][0], uf[2 * i][1], uf[2 * i][2], uf[2 * i][3], h.x, h.y);
                mma16816(ag[1], gf[2 * i + 1][0], gf[2 * i + 1][1], gf[2 * i + 1][2], gf[2 * i + 1][3], h.z, h.w);
                mma16816(au[1], uf[2 * i + 1][0], uf[2 * i + 1][1], uf[2 * i + 1][2], uf[2 * i + 1][3], h.z, h.w);
            }
            sts64(sb + OFF_RED + (warp >> 1) * 512u + (c & 1) * 256u + ((warp & 1) * 16 + (c >> 1) * 8 + g) * 8u,
                  f2u(sel4(c, ag[0][0], ag[0][1], ag[0][2], ag[0][3]) + sel4(c, ag[1][0], ag[1][1], ag[1][2], ag[1][3])),
                  f2u(sel4(c, au[0][0], au[0][1], au[0][2], au[0][3]) + sel4(c, au[1][0], au[1][1], au[1][2], au[1][3])));
        }
        bar_sync(1, 256);
        {
            const uint32_t ra = sb + OFF_RED + lane * 16u;
            const uint4 r0 = lds128(ra), r1 = lds128(ra + 512), r2 = lds128(ra + 1024), r3 = lds128(ra + 1536);
            #define F4(f) ((u2f(r0.f) + u2f(r1.f)) + (u2f(r2.f) + u2f(r3.f)))
            const uint32_t hid = hmul2(silu2(pack2(F4(x), F4(z))), pack2(F4(y), F4(w)));
            #undef F4
            if (warp == 0) TS(38);
            const int src = (g & 1) * 16 + c;
            const uint32_t b0 = __shfl_sync(0xffffffffu, hid, src), b1 = __shfl_sync(0xffffffffu, hid, src + 4), b2 = __shfl_sync(0xffffffffu, hid, src + 8), b3 = __shfl_sync(0xffffffffu, hid, src + 12);
            float y[8][4];
            #pragma unroll
            for (int i = 0; i < 8; i++) {
                y[i][0] = y[i][1] = y[i][2] = y[i][3] = 0.f;
                mma16816(y[i], df[2 * i][0], df[2 * i][1], df[2 * i][2], df[2 * i][3], b0, b1);
            }
            #pragma unroll
            for (int i = 0; i < 8; i++) mma16816(y[i], df[2 * i + 1][0], df[2 * i + 1][1], df[2 * i + 1][2], df[2 * i + 1][3], b2, b3);
            if (b < 112) {
                #pragma unroll
                for (int h = 0; h < 2; h++) {
                    #define YS(e) sel4(c, y[4 * h][e], y[4 * h + 1][e], y[4 * h + 2][e], y[4 * h + 3][e])
                    st_ll4(p.s->lly + b * 512 + (warp * 8 + 4 * h + c) * 8 + g, YS(0), YS(1), YS(2), YS(3), tag);
                    #undef YS
                }
            }
        }
        if (warp == 0) TS(39);
        if (warp < 7) {
            uint4 v[2];
            poll_words<2, 0, 3>(v, p.s->lly + (tid >> 2) * 512 + b * 4 + c, 56 * 512, tag);
            float y0 = u2f(v[0].x) + u2f(v[1].x), y1 = u2f(v[0].y) + u2f(v[1].y), y2 = u2f(v[0].z) + u2f(v[1].z), y3 = u2f(v[0].w) + u2f(v[1].w);
            const bool g0 = g & 1, g1 = g & 2;
            const float k0 = (g0 ? y1 : y0) + shfl_x(g0 ? y0 : y1, 4), k1 = (g0 ? y3 : y2) + shfl_x(g0 ? y2 : y3, 4);
            float y = (g1 ? k1 : k0) + shfl_x(g1 ? k0 : k1, 8);
            y += shfl_x(y, 16);
            if (lane < 16) stsf(sb + OFF_RED2 + lane * 32u + warp * 4u, y);
            bar_sync(6, 224);
            if (tid < 16) {
                const uint4 ya = lds128(sb + OFF_RED2 + lane * 32u), yb = lds128(sb + OFF_RED2 + lane * 32u + 16);
                y = ((u2f(ya.x) + u2f(ya.y)) + (u2f(ya.z) + u2f(ya.w))) + ((u2f(yb.x) + u2f(yb.y)) + u2f(yb.z));
                const float sg = sigmoid_f(rbf(u2f(fr)));
                const uint32_t o = hadd2(fx, hmul2(fg, hadd2(fh, hmul2(pack2(y, y), pack2(sg, sg)))));
                ((uint16_t*)p.out)[(size_t)frow * 1024 + (b >> 1) * 16 + (b & 1) * 4 + c + 8 * (g >> 1)] = (c & 1) ? o >> 16 : o;
                if (b == 0 && tid == 0) p.s->done[0] = tag;
                TS(40);
            }
        }
    }
}

typedef CUresult (*EncodeFn)(CUtensorMap*, CUtensorMapDataType, cuuint32_t, void*, const cuuint64_t*, const cuuint64_t*, const cuuint32_t*,
                             const cuuint32_t*, CUtensorMapInterleave, CUtensorMapSwizzle, CUtensorMapL2promotion, CUtensorMapFloatOOBfill);

CUtensorMap make_map(EncodeFn enc, const void* ptr, uint64_t cols, uint64_t rows, uint32_t bc, uint32_t br, CUtensorMapSwizzle swz, CUtensorMapL2promotion promo) {
    CUtensorMap m;
    cuuint64_t dims[2] = {cols, rows}, strides[1] = {cols * 2};
    cuuint32_t box[2] = {bc, br}, es[2] = {1, 1};
    enc(&m, CU_TENSOR_MAP_DATA_TYPE_BFLOAT16, 2, const_cast<void*>(ptr), dims, strides, box, es, CU_TENSOR_MAP_INTERLEAVE_NONE, swz, promo,
        CU_TENSOR_MAP_FLOAT_OOB_FILL_NONE);
    return m;
}
CUtensorMap make_map4(EncodeFn enc, const void* ptr, uint32_t groups, uint64_t rows, uint32_t br, CUtensorMapL2promotion promo) {
    CUtensorMap m;
    cuuint64_t dims[4] = {64, rows, 16, groups}, strides[3] = {groups * 2048ull, 128, 2048};
    cuuint32_t box[4] = {64, br, 2, groups}, es[4] = {1, 1, 1, 1};
    enc(&m, CU_TENSOR_MAP_DATA_TYPE_BFLOAT16, 4, const_cast<void*>(ptr), dims, strides, box, es, CU_TENSOR_MAP_INTERLEAVE_NONE, CU_TENSOR_MAP_SWIZZLE_128B, promo,
        CU_TENSOR_MAP_FLOAT_OOB_FILL_NONE);
    return m;
}

}

extern "C" void kernel_launch(void* const* d_in, const int* in_sizes, int n_in, void* d_out, int out_size) {
    (void)in_sizes; (void)n_in; (void)out_size;
    void* fn = nullptr; cudaDriverEntryPointQueryResult qr;
    cudaGetDriverEntryPoint("cuTensorMapEncodeTiled", &fn, cudaEnableDefault, &qr);
    EncodeFn enc = (EncodeFn)fn;
    void* hs = nullptr;
    cudaGetSymbolAddress(&hs, g_scratch);
    int dev = 0, sms = 0;
    cudaGetDevice(&dev);
    cudaDeviceGetAttribute(&sms, cudaDevAttrMultiProcessorCount, dev);
    const CUtensorMapL2promotion P256 = CU_TENSOR_MAP_L2_PROMOTION_L2_256B, P128 = CU_TENSOR_MAP_L2_PROMOTION_L2_128B, P0 = CU_TENSOR_MAP_L2_PROMOTION_NONE;
    CUtensorMap tmW = make_map4(enc, d_in[1], 3, 1024, 32, P256);
    CUtensorMap tmWo = make_map4(enc, d_in[3], 1, 1024, 64, P256);
    CUtensorMap tmO = make_map4(enc, d_out, 1, 2048, 16, P0);
    CUtensorMap tmPhi = make_map(enc, d_in[2], 32, 1024, 32, 128, CU_TENSOR_MAP_SWIZZLE_64B, P128);
    CUtensorMap tmG = make_map(enc, d_in[6], 3584, 1024, 32, 128, CU_TENSOR_MAP_SWIZZLE_64B, P0);
    CUtensorMap tmU = make_map(enc, d_in[7], 3584, 1024, 32, 128, CU_TENSOR_MAP_SWIZZLE_64B, P0);
    CUtensorMap tmD = make_map(enc, d_in[8], 1024, 3584, 64, 32, CU_TENSOR_MAP_SWIZZLE_128B, P128);
    CUtensorMap tmX = make_map(enc, d_in[0], 1024, 2048, 64, 128, CU_TENSOR_MAP_SWIZZLE_128B, P128);
    CUtensorMap tmM = make_map(enc, d_in[10], 6144, 1024, 64, 256, CU_TENSOR_MAP_SWIZZLE_128B, MPROMO);
    Ptrs p;
    p.x = (const bf16*)d_in[0]; p.c = (const bf16*)d_in[9]; p.wmod = (const bf16*)d_in[10]; p.wr = (const bf16*)d_in[5];
    p.wg = (const bf16*)d_in[6]; p.wu = (const bf16*)d_in[7]; p.wd = (const bf16*)d_in[8]; p.out = (bf16*)d_out; p.s = (Scratch*)hs;
    p.wqkv = (const bf16*)d_in[1]; p.wo = (const bf16*)d_in[3];
    p.by_sm = sms == 132;
    cudaFuncSetAttribute(fused_kernel, cudaFuncAttributeMaxDynamicSharedMemorySize, SMEM_BYTES);
    fused_kernel<<<132, NTHREADS, SMEM_BYTES, cudaStreamPerThread>>>(p, tmM, tmX, tmW, tmWo, tmPhi, tmG, tmU, tmD, tmO);
}
```

```cpp
#include <cuda_runtime.h>
#include <cuda.h>
#include <cuda_bf16.h>
#include <stdint.h>

namespace {

typedef __nv_bfloat16 bf16;

constexpr int NTHREADS = 512;
constexpr int POLL_MAX = 400000;

constexpr uint32_t OFF_R0   = 0;
constexpr uint32_t OFF_A    = 65536;
constexpr uint32_t OFF_B    = 114688;
constexpr uint32_t OFF_V    = 65536;
constexpr uint32_t OFF_PHI  = 98304;
constexpr uint32_t OFF_F2   = 65536;
constexpr uint32_t OFF_DB   = 131072;
constexpr uint32_t OFF_KL   = 196608;
constexpr uint32_t OFF_WPHI = 214016;
constexpr uint32_t OFF_KVT  = OFF_WPHI;
constexpr uint32_t OFF_Z    = 222208;
constexpr uint32_t OFF_TAB  = OFF_Z;
constexpr uint32_t OFF_ONES = 226304;
constexpr uint32_t OFF_BAR  = 227328;
constexpr uint32_t OFF_CST  = OFF_BAR + 640;
constexpr uint32_t OFF_T1   = OFF_ONES;
constexpr uint32_t OFF_T2   = OFF_CST + 64;
constexpr uint32_t OFF_T3   = OFF_T2 + 512;
constexpr uint32_t OFF_KEY  = OFF_T3 + 256;
constexpr uint32_t OFF_ST2  = OFF_KEY + 512;
constexpr uint32_t OFF_ZS   = OFF_ST2;
constexpr uint32_t SMEM_BYTES = 232448;
constexpr uint32_t OFF_X1   = OFF_KL;
constexpr uint32_t OFF_OUT  = OFF_R0 + 32768;
constexpr uint32_t OFF_HSEL = OFF_WPHI;
constexpr uint32_t OFF_RED  = OFF_WPHI + 4096;
constexpr uint32_t OFF_RED2 = OFF_RED + 2048;
static_assert(OFF_ST2 + 2048 <= SMEM_BYTES, "layout");

enum {
    B_O1 = 0, B_UF = 1, B_UD = 2, B_WPHI = 3, B_FB = 4  , B_OST = 8, B_GF = 9, B_WD = 10, B_KVL = 11  , B_KZ = 13, B_LMF = 14, B_SEL = 15, B_XP = 16  , B_TAG = 24,
    B_FA = 25  , B_FD = 30  , B_CAND = 34,
    B_PE = 35  , B_KST = 37  , B_KVT = 41  , B_LMD = 43, B_PAR = 44,
    B_EA = 45  , B_EB = 48  , B_ED = 52  , B_PF = 56  , B_OWN = 60  , B_QE = 62, B_STP = 63, B_KEYS = 64, B_SWP = 65, B_STS = 66
};

struct Scratch {
    uint4 os[16 * 16 * 1024];
    uint4 kvacc[8 * 4 * 528];
    uint4 flk[3 * 128 * 2];
    uint4 llstat[2048];
    uint4 llm1[16 * 64];
    uint4 flo[16 * 16 * 2];
    uint4 llmod2[2 * 256];
    uint4 llg[2 * 4 * 256];
    uint4 llln2[16 * 8 * 128];
    uint4 llcand[16 * 2];
    uint4 llrowh[32 * 256];
    uint4 llrowx[32 * 256];
    uint4 lly[128 * 512];
    unsigned done[4];
};
__device__ __align__(1024) Scratch g_scratch;
#define GT(i) do {} while (0)
#define TS(i) do {} while (0)
#define TR(i) do {} while (0)

__device__ __forceinline__ uint32_t smem_u32(const void* p) { return (uint32_t)__cvta_generic_to_shared(p); }
__device__ __forceinline__ uint32_t clk32() { uint32_t c; asm volatile("mov.u32 %0, %%clock;" : "=r"(c) :: "memory"); return c; }
__device__ __forceinline__ void spin_until(uint32_t t) { while ((int)(clk32() - t) < 0) {} }
__device__ __forceinline__ void sleep_until(uint32_t t) { while ((int)(clk32() - t) < 0) __nanosleep(40); }
__device__ __forceinline__ void mbar_init_fence() { asm volatile("fence.mbarrier_init.release.cluster;" ::: "memory"); }
__device__ __forceinline__ void mbar_wait(uint32_t bar, uint32_t parity) {
    asm volatile("{\n.reg .pred P1;\nLAB_WAIT:\nmbarrier.try_wait.parity.shared::cta.b64 P1, [%0], %1;\n@!P1 bra LAB_WAIT;\n}" :: "r"(bar), "r"(parity) : "memory");
}
__device__ __forceinline__ uint64_t policy_evict_first() { uint64_t p; asm("createpolicy.fractional.L2::evict_first.b64 %0, 1.0;" : "=l"(p)); return p; }
#define ELECT "{\n.reg .pred e;\nelect.sync _|e, 0xffffffff;\n@e "
__device__ __forceinline__ void e_arrive(uint32_t bar) { asm volatile(ELECT "mbarrier.arrive.shared::cta.b64 _, [%0];\n}" :: "r"(bar) : "memory"); }
__device__ __forceinline__ void e_arrive_tx(uint32_t bar, uint32_t bytes) { asm volatile(ELECT "mbarrier.arrive.expect_tx.shared::cta.b64 _, [%0], %1;\n}" :: "r"(bar), "r"(bytes) : "memory"); }
__device__ __forceinline__ void e_init(uint32_t bar, uint32_t cnt) { asm volatile(ELECT "mbarrier.init.shared::cta.b64 [%0], %1;\n}" :: "r"(bar), "r"(cnt) : "memory"); }
__device__ __forceinline__ void tma_load_ef(uint32_t dst, const CUtensorMap* tm, int c0, int c1, uint32_t bar) {
    asm volatile(ELECT "cp.async.bulk.tensor.2d.shared::cluster.global.mbarrier::complete_tx::bytes.L2::cache_hint [%0], [%1, {%3, %4}], [%2], %5;\n}"
        :: "r"(dst), "l"(tm), "r"(bar), "r"(c0), "r"(c1), "l"(policy_evict_first()) : "memory");
}
__device__ __forceinline__ void tma_load(uint32_t dst, const CUtensorMap* tm, int c0, int c1, uint32_t bar) {
    asm volatile(ELECT "cp.async.bulk.tensor.2d.shared::cluster.global.mbarrier::complete_tx::bytes [%0], [%1, {%3, %4}], [%2];\n}"
        :: "r"(dst), "l"(tm), "r"(bar), "r"(c0), "r"(c1) : "memory");
}
__device__ __forceinline__ void tma_load4(uint32_t dst, const CUtensorMap* tm, int row, int blk, uint32_t bar) {
    asm volatile(ELECT "cp.async.bulk.tensor.4d.shared::cluster.global.mbarrier::complete_tx::bytes [%0], [%1, {0, %3, %4, 0}], [%2];\n}"
        :: "r"(dst), "l"(tm), "r"(bar), "r"(row), "r"(blk) : "memory");
}
__device__ __forceinline__ void tma_store4(const CUtensorMap* tm, int row, int blk, uint32_t src) {
    asm volatile(ELECT "cp.async.bulk.tensor.4d.global.shared::cta.bulk_group [%0, {0, %2, %3, 0}], [%1];\n}" :: "l"(tm), "r"(src), "r"(row), "r"(blk) : "memory");
}
__device__ __forceinline__ void bulk_load(uint32_t dst, const void* src, uint32_t bytes, uint32_t bar) {
    asm volatile(ELECT "cp.async.bulk.shared::cluster.global.mbarrier::complete_tx::bytes [%0], [%1], %2, [%3];\n}" :: "r"(dst), "l"(src), "r"(bytes), "r"(bar) : "memory");
}
__device__ __forceinline__ void bulk_store(void* dst, uint32_t src, uint32_t bytes) {
    asm volatile(ELECT "cp.async.bulk.global.shared::cta.bulk_group [%0], [%1], %2;\n}" :: "l"(dst), "r"(src), "r"(bytes) : "memory");
}
__device__ __forceinline__ void bulk_reduce(void* dst, uint32_t src, uint32_t bytes) {
    asm volatile(ELECT "cp.reduce.async.bulk.global.shared::cta.bulk_group.add.f32 [%0], [%1], %2;\n}" :: "l"(dst), "r"(src), "r"(bytes) : "memory");
}
__device__ __forceinline__ void tma_prefetch(const CUtensorMap* tm, int c0, int c1) {
    asm volatile(ELECT "cp.async.bulk.prefetch.tensor.2d.L2.global [%0, {%1, %2}];\n}" :: "l"(tm), "r"(c0), "r"(c1) : "memory");
}
__device__ __forceinline__ void l2_prefetch(const void* p, uint32_t bytes) {
    asm volatile(ELECT "cp.async.bulk.prefetch.L2.global [%0], %1;\n}" :: "l"(p), "r"(bytes) : "memory");
}
__device__ __forceinline__ void bulk_wait_read() { asm volatile("cp.async.bulk.commit_group;\ncp.async.bulk.wait_group.read 0;" ::: "memory"); }
__device__ __forceinline__ void bulk_wait() { asm volatile("cp.async.bulk.commit_group;\ncp.async.bulk.wait_group 0;" ::: "memory"); }
__device__ __forceinline__ void tmap_prefetch(const CUtensorMap* tm) { asm volatile("prefetch.tensormap [%0];" :: "l"(tm) : "memory"); }
__device__ __forceinline__ void wg_fence() { asm volatile("wgmma.fence.sync.aligned;" ::: "memory"); }
__device__ __forceinline__ void wg_commit() { asm volatile("wgmma.commit_group.sync.aligned;" ::: "memory"); }
template<int N> __device__ __forceinline__ void wg_wait() { asm volatile("wgmma.wait_group.sync.aligned %0;" :: "n"(N) : "memory"); }
template<int N> __device__ __forceinline__ void acc_fence(float (&d)[N]) {
    #pragma unroll
    for (int i = 0; i < N; i++) asm volatile("" : "+f"(d[i]) :: "memory");
}
__device__ __forceinline__ uint32_t desc_lo(uint32_t addr, uint32_t lbo) { return (addr >> 4) | ((lbo >> 4) << 16); }
constexpr uint32_t H128 = 0x40000040u;
constexpr uint32_t H64 = 0x80000020u;
__device__ __forceinline__ void fence_async_smem() { asm volatile("fence.proxy.async.shared::cta;" ::: "memory"); }
__device__ __forceinline__ void bar_sync(int id, int n) { asm volatile("bar.sync %0, %1;" :: "r"(id), "r"(n) : "memory"); }
template<int R> __device__ __forceinline__ void reg_inc() { asm volatile("setmaxnreg.inc.sync.aligned.u32 %0;" :: "n"(R)); }
template<int R> __device__ __forceinline__ void reg_dec() { asm volatile("setmaxnreg.dec.sync.aligned.u32 %0;" :: "n"(R)); }

__device__ __forceinline__ void stsm4(uint32_t addr, uint32_t r0, uint32_t r1, uint32_t r2, uint32_t r3) {
    asm volatile("stmatrix.sync.aligned.m8n8.x4.shared.b16 [%0], {%1,%2,%3,%4};" :: "r"(addr), "r"(r0), "r"(r1), "r"(r2), "r"(r3) : "memory");
}
__device__ __forceinline__ void ldsm4(uint32_t* r, uint32_t addr) {
    asm volatile("ldmatrix.sync.aligned.m8n8.x4.shared.b16 {%0,%1,%2,%3}, [%4];" : "=r"(r[0]), "=r"(r[1]), "=r"(r[2]), "=r"(r[3]) : "r"(addr) : "memory");
}
__device__ __forceinline__ void ldsm4t(uint32_t* r, uint32_t addr) {
    asm volatile("ldmatrix.sync.aligned.m8n8.x4.trans.shared.b16 {%0,%1,%2,%3}, [%4];" : "=r"(r[0]), "=r"(r[1]), "=r"(r[2]), "=r"(r[3]) : "r"(addr) : "memory");
}
__device__ __forceinline__ void mma16816(float (&d)[4], uint32_t a0, uint32_t a1, uint32_t a2, uint32_t a3, uint32_t b0, uint32_t b1) {
    asm volatile("mma.sync.aligned.m16n8k16.row.col.f32.bf16.bf16.f32 {%0,%1,%2,%3}, {%4,%5,%6,%7}, {%8,%9}, {%0,%1,%2,%3};"
        : "+f"(d[0]), "+f"(d[1]), "+f"(d[2]), "+f"(d[3]) : "r"(a0), "r"(a1), "r"(a2), "r"(a3), "r"(b0), "r"(b1));
}
__device__ __forceinline__ uint32_t awake_zero() {
    uint32_t r;
    asm volatile("{\n.reg .f32 d<4>;\nmma.sync.aligned.m16n8k8.row.col.f32.bf16.bf16.f32 {d0,d1,d2,d3}, {%1,%1}, {%1}, {%2,%2,%2,%2};\nmov.b32 %0, d0;\n}" : "=r"(r) : "r"(0), "f"(0.f));
    return r;
}
__device__ __forceinline__ void mbar_wait_awake(uint32_t bar, uint32_t parity) {
    #pragma unroll 1
    for (int it = 0; it < POLL_MAX; it++) {
        uint32_t ok;
        asm volatile("{\n.reg .pred p;\nmbarrier.try_wait.parity.shared::cta.b64 p, [%1], %2;\nselp.u32 %0, 0, 1, p;\n}" : "=r"(ok) : "r"(bar), "r"(parity) : "memory");
        if (__all_sync(0xffffffffu, ok == 0)) break;
        it += awake_zero();
    }
}
__device__ __forceinline__ uint4 lds128(uint32_t a) { uint4 v; asm volatile("ld.shared.v4.b32 {%0,%1,%2,%3}, [%4];" : "=r"(v.x), "=r"(v.y), "=r"(v.z), "=r"(v.w) : "r"(a) : "memory"); return v; }
__device__ __forceinline__ uint32_t lds32(uint32_t a) { uint32_t v; asm volatile("ld.shared.b32 %0, [%1];" : "=r"(v) : "r"(a) : "memory"); return v; }
__device__ __forceinline__ uint2 lds64(uint32_t a) { uint2 v; asm volatile("ld.shared.v2.b32 {%0,%1}, [%2];" : "=r"(v.x), "=r"(v.y) : "r"(a) : "memory"); return v; }
__device__ __forceinline__ float ldsf(uint32_t a) { float v; asm volatile("ld.shared.f32 %0, [%1];" : "=f"(v) : "r"(a) : "memory"); return v; }
__device__ __forceinline__ void sts128(uint32_t a, uint4 v) { asm volatile("st.shared.v4.b32 [%0], {%1,%2,%3,%4};" :: "r"(a), "r"(v.x), "r"(v.y), "r"(v.z), "r"(v.w) : "memory"); }
__device__ __forceinline__ void sts64(uint32_t a, uint32_t x, uint32_t y) { asm volatile("st.shared.v2.b32 [%0], {%1,%2};" :: "r"(a), "r"(x), "r"(y) : "memory"); }
__device__ __forceinline__ void sts32(uint32_t a, uint32_t x) { asm volatile("st.shared.b32 [%0], %1;" :: "r"(a), "r"(x) : "memory"); }
__device__ __forceinline__ void stsf(uint32_t a, float x) { asm volatile("st.shared.f32 [%0], %1;" :: "r"(a), "f"(x) : "memory"); }
__device__ __forceinline__ float u2f(uint32_t v) { return __uint_as_float(v); }
__device__ __forceinline__ uint32_t f2u(float v) { return __float_as_uint(v); }

__device__ __forceinline__ uint32_t ldg32(const void* p) { uint32_t v; asm volatile("ld.global.nc.b32 %0, [%1];" : "=r"(v) : "l"(p)); return v; }
__device__ __forceinline__ void stg128(void* p, uint4 v) { asm volatile("st.global.v4.b32 [%0], {%1,%2,%3,%4};" :: "l"(p), "r"(v.x), "r"(v.y), "r"(v.z), "r"(v.w) : "memory"); }
__device__ __forceinline__ void stg_zero(void* p) { stg128(p, make_uint4(0, 0, 0, 0)); }
__device__ __forceinline__ void fence_gpu() { asm volatile("fence.acq_rel.gpu;" ::: "memory"); }
__device__ __forceinline__ void st_ll(uint4* p, uint32_t x, uint32_t y, uint32_t z, uint32_t w) {
    asm volatile("st.relaxed.gpu.global.v4.b32 [%0], {%1,%2,%3,%4};" :: "l"(p), "r"(x), "r"(y), "r"(z), "r"(w) : "memory");
}
__device__ __forceinline__ uint4 ld_ll(const uint4* p) {
    uint4 v;
    asm volatile("ld.relaxed.gpu.global.v4.b32 {%0,%1,%2,%3}, [%4];" : "=r"(v.x), "=r"(v.y), "=r"(v.z), "=r"(v.w) : "l"(p) : "memory");
    return v;
}
template<uint32_t LUT> __device__ __forceinline__ uint32_t lop3(uint32_t a, uint32_t b, uint32_t c) { uint32_t d; asm("lop3.b32 %0, %1, %2, %3, %4;" : "=r"(d) : "r"(a), "r"(b), "r"(c), "n"(LUT)); return d; }
__device__ __forceinline__ uint32_t tag_bad(uint32_t bad, uint32_t w, uint32_t tag) { return lop3<0xF6>(bad, w, tag); }
__device__ __forceinline__ void st_ll4(uint4* p, float a, float b, float c, float d, uint32_t tag) { st_ll(p, f2u(a), f2u(b), f2u(c), lop3<0xD8>(f2u(d), tag, 3u)); }
__device__ __forceinline__ unsigned ld_rlx(const void* p) { unsigned v; asm volatile("ld.relaxed.gpu.global.u32 %0, [%1];" : "=r"(v) : "l"(p) : "memory"); return v; }
__device__ __forceinline__ void st_flag(uint4* p, uint32_t v, int lane) { if (lane < 2) st_ll(p + lane, v, v, v, v); }
__device__ __forceinline__ void poll_flags(const uint4* f, uint32_t tag) {
    unsigned v0 = ld_rlx(f), v1;
    spin_until(clk32() + 140);
    #pragma unroll 1
    for (int it = 0; it < POLL_MAX; it++) {
        v1 = ld_rlx(f);
        if (__all_sync(0xffffffffu, v0 == tag)) break;
        v0 = ld_rlx(f);
        if (__all_sync(0xffffffffu, v1 == tag)) break;
    }
}
template<int Z> __device__ __forceinline__ uint32_t ll_bad(uint32_t bad, const uint4& v, uint32_t tag) {
    bad = tag_bad(bad, v.w, tag);
    return Z && lop3<0x80>(v.x, v.y, v.z) == ~0u ? 1u : bad;
}
template<int N, int Z, uint32_t M = ~0u, int AW = 0> __device__ __forceinline__ void poll_words(uint4 (&v)[N], const uint4* p, int stride, uint32_t tag) {
    #pragma unroll 1
    for (int it = 0; it < POLL_MAX; it++) {
        uint32_t bad = 0;
        #pragma unroll
        for (int i = 0; i < N; i++) v[i] = ld_ll(p + i * stride);
        #pragma unroll
        for (int i = 0; i < N; i++) bad = ll_bad<Z>(bad, v[i], tag);
        if (__all_sync(0xffffffffu, !(bad & M))) break;
        if (AW) it += awake_zero();
    }
}
constexpr uint32_t ONE2 = 0x3F803F80u;
__device__ __forceinline__ uint32_t pack2(float lo, float hi) { uint32_t d; asm("cvt.rn.bf16x2.f32 %0, %1, %2;" : "=r"(d) : "f"(hi), "f"(lo)); return d; }
__device__ __forceinline__ float bf_lo(uint32_t v) { return u2f(v << 16); }
__device__ __forceinline__ float bf_hi(uint32_t v) { return u2f(v & 0xffff0000u); }
__device__ __forceinline__ float rbf(float x) { return bf_lo(pack2(x, 0.f)); }
__device__ __forceinline__ uint32_t hsub2(uint32_t a, uint32_t b) { uint32_t d; asm("sub.rn.bf16x2 %0, %1, %2;" : "=r"(d) : "r"(a), "r"(b)); return d; }
__device__ __forceinline__ uint32_t hadd2(uint32_t a, uint32_t b) { uint32_t d; asm("add.rn.bf16x2 %0, %1, %2;" : "=r"(d) : "r"(a), "r"(b)); return d; }
__device__ __forceinline__ uint32_t hmul2(uint32_t a, uint32_t b) { uint32_t d; asm("mul.rn.bf16x2 %0, %1, %2;" : "=r"(d) : "r"(a), "r"(b)); return d; }
__device__ __forceinline__ uint32_t hfma2(uint32_t a, uint32_t b, uint32_t c) { uint32_t d; asm("fma.rn.bf16x2 %0, %1, %2, %3;" : "=r"(d) : "r"(a), "r"(b), "r"(c)); return d; }
__device__ __forceinline__ uint32_t hmax2(uint32_t a, uint32_t b) { uint32_t d; asm("max.bf16x2 %0, %1, %2;" : "=r"(d) : "r"(a), "r"(b)); return d; }
__device__ __forceinline__ uint32_t hmin2(uint32_t a, uint32_t b) { uint32_t d; asm("min.bf16x2 %0, %1, %2;" : "=r"(d) : "r"(a), "r"(b)); return d; }
__device__ __forceinline__ float ex2(float x) { float y; asm("ex2.approx.ftz.f32 %0, %1;" : "=f"(y) : "f"(x)); return y; }
__device__ __forceinline__ float rcp(float x) { float y; asm("rcp.approx.ftz.f32 %0, %1;" : "=f"(y) : "f"(x)); return y; }
__device__ __forceinline__ float shfl_x(float v, int m) { return __shfl_xor_sync(0xffffffffu, v, m); }
__device__ __forceinline__ uint32_t hdiv2(uint32_t d, uint32_t rh, uint32_t rl) { return hfma2(d, rh, hmul2(d, rl)); }
__device__ __forceinline__ void split_rcp(float r, uint32_t& rh, uint32_t& rl) { rh = pack2(r, r); const float l = r - bf_lo(rh); rl = pack2(l, l); }
__device__ __forceinline__ uint32_t lnmod(uint32_t x, uint32_t m, uint32_t rh, uint32_t rl, uint32_t a, uint32_t s) { return hadd2(hmul2(hdiv2(hsub2(x, m), rh, rl), a), s); }
__device__ __forceinline__ void ln_final(float s1, float s2, uint32_t& m2, float& rinv) {
    const float mean = s1 * (1.0f / 1024.0f), var = fmaf(-mean, mean, s2 * (1.0f / 1024.0f));
    m2 = pack2(mean, mean);
    float sd;
    asm("sqrt.approx.ftz.f32 %0, %1;" : "=f"(sd) : "f"(rbf(rbf(fmaxf(var, 0.f)) + 1e-5f)));
    rinv = rcp(rbf(sd));
}
__device__ __forceinline__ float sigmoid_f(float x) { return rcp(1.0f + ex2(-1.4426950408889634f * x)); }
__device__ __forceinline__ uint32_t silu2(uint32_t v) { return pack2(bf_lo(v) * sigmoid_f(bf_lo(v)), bf_hi(v) * sigmoid_f(bf_hi(v))); }
__device__ __forceinline__ uint32_t f2key(float f) { uint32_t u = f2u(f); return (u & 0x80000000u) ? ~u : (u | 0x80000000u); }
__device__ __forceinline__ float key2f(uint32_t k) { return u2f((k & 0x80000000u) ? k ^ 0x80000000u : ~k); }
template<int N> __device__ __forceinline__ void top2(uint32_t (&k)[N], uint32_t& b0, uint32_t& b1) {
    uint32_t m = k[0];
    #pragma unroll
    for (int i = 1; i < N; i++) m = max(m, k[i]);
    b0 = __reduce_max_sync(0xffffffffu, m);
    m = 0;
    #pragma unroll
    for (int i = 0; i < N; i++) m = max(m, k[i] == b0 ? 0u : k[i]);
    b1 = __reduce_max_sync(0xffffffffu, m);
}
template<class T> __device__ __forceinline__ T sel4(int c, T a0, T a1, T a2, T a3) { return (c & 2) ? ((c & 1) ? a3 : a2) : ((c & 1) ? a1 : a0); }

__device__ __forceinline__ void fm_max(const float (&a)[16], uint32_t* p, uint32_t* mm) {
    #pragma unroll
    for (int i = 0; i < 8; i++) p[i] = pack2(a[2 * i], a[2 * i + 1]);
    #pragma unroll
    for (int h = 0; h < 2; h++) {
        const uint32_t mx = hmax2(hmax2(p[h], p[2 + h]), hmax2(p[4 + h], p[6 + h]));
        const uint32_t mn = hmin2(hmin2(p[h], p[2 + h]), hmin2(p[4 + h], p[6 + h])) ^ 0x80008000u;
        mm[h] = hmax2(__byte_perm(mx, mn, 0x5410), __byte_perm(mx, mn, 0x7632));
    }
    #pragma unroll
    for (int d = 1; d <= 2; d++) { mm[0] = hmax2(mm[0], __shfl_xor_sync(0xffffffffu, mm[0], d)); mm[1] = hmax2(mm[1], __shfl_xor_sync(0xffffffffu, mm[1], d)); }
}
__device__ __forceinline__ void fm_args(const uint32_t* p, const uint32_t* mm, float (&e)[32]) {
    const float L = 1.4426950408889634f;
    #pragma unroll
    for (int h = 0; h < 2; h++) {
        const float cp = -bf_lo(mm[h]) * L, cn = -bf_hi(mm[h]) * L;
        #pragma unroll
        for (int j = 0; j < 4; j++) {
            const float f0 = bf_lo(p[2 * j + h]), f1 = bf_hi(p[2 * j + h]);
            e[8 * h + 2 * j] = fmaf(f0, L, cp); e[8 * h + 2 * j + 1] = fmaf(f1, L, cp);
            e[16 + 8 * h + 2 * j] = fmaf(f0, -L, cn); e[16 + 8 * h + 2 * j + 1] = fmaf(f1, -L, cn);
        }
    }
}
template<int LO, int HI> __device__ __forceinline__ void fm_exp(float (&e)[32]) {
    #pragma unroll
    for (int i = LO; i < HI; i++) e[i] = ex2(e[i]);
}
__device__ __forceinline__ void fm_norm(const float (&e)[32], uint32_t* ph) {
    float s[4];
    #pragma unroll
    for (int k = 0; k < 4; k++) s[k] = ((e[8 * k] + e[8 * k + 1]) + (e[8 * k + 2] + e[8 * k + 3])) + ((e[8 * k + 4] + e[8 * k + 5]) + (e[8 * k + 6] + e[8 * k + 7]));
    #pragma unroll
    for (int k = 0; k < 4; k++) s[k] += shfl_x(s[k], 1);
    #pragma unroll
    for (int k = 0; k < 4; k++) s[k] = rcp(s[k] + shfl_x(s[k], 2));
    #pragma unroll
    for (int k = 0; k < 4; k++)
        #pragma unroll
        for (int j = 0; j < 4; j++) ph[8 * (k >> 1) + 2 * j + (k & 1)] = pack2(e[8 * k + 2 * j] * s[k], e[8 * k + 2 * j + 1] * s[k]);
}
template<class T> __device__ __forceinline__ T* pin_ptr(T* p) { asm volatile("" : "+l"(p) :: "memory"); return p; }
template<int N> __device__ __forceinline__ void pin(uint32_t* d) {
    #pragma unroll
    for (int i = 0; i < N; i++) asm volatile("" : "+r"(d[i]) :: "memory");
}

template<uint32_t BO, uint32_t BH> __device__ __forceinline__ void mma192_rs(float (&d)[96], const uint32_t* a, uint32_t blo) {
  asm volatile("{\n.reg .pred p;\n.reg .b32 ta, tb;\n.reg .b64 da, db;\nadd.u32 tb, %100, %101;\nmov.b64 db, {tb, %102};\nsetp.ne.b32 p, 1, 0;\n"
    "wgmma.mma_async.sync.aligned.m64n192k16.f32.bf16.bf16 {%0, %1, %2, %3, %4, %5, %6, %7, %8, %9, %10, %11, %12, %13, %14, %15, %16, %17, %18, %19, %20, %21, %22, %23, %24, %25, %26, %27, %28, %29, %30, %31, %32, %33, %34, %35, %36, %37, %38, %39, %40, %41, %42, %43, %44, %45, %46, %47, %48, %49, %50, %51, %52, %53, %54, %55, %56, %57, %58, %59, %60, %61, %62, %63, %64, %65, %66, %67, %68, %69, %70, %71, %72, %73, %74, %75, %76, %77, %78, %79, %80, %81, %82, %83, %84, %85, %86, %87, %88, %89, %90, %91, %92, %93, %94, %95}, {%96,%97,%98,%99}, db, p, 1, 1, 1;\n}\n"
    : "+f"(d[0]), "+f"(d[1]), "+f"(d[2]), "+f"(d[3]), "+f"(d[4]), "+f"(d[5]), "+f"(d[6]), "+f"(d[7]), "+f"(d[8]), "+f"(d[9]), "+f"(d[10]), "+f"(d[11]), "+f"(d[12]), "+f"(d[13]), "+f"(d[14]), "+f"(d[15]), "+f"(d[16]), "+f"(d[17]), "+f"(d[18]), "+f"(d[19]), "+f"(d[20]), "+f"(d[21]), "+f"(d[22]), "+f"(d[23]), "+f"(d[24]), "+f"(d[25]), "+f"(d[26]), "+f"(d[27]), "+f"(d[28]), "+f"(d[29]), "+f"(d[30]), "+f"(d[31]), "+f"(d[32]), "+f"(d[33]), "+f"(d[34]), "+f"(d[35]), "+f"(d[36]), "+f"(d[37]), "+f"(d[38]), "+f"(d[39]), "+f"(d[40]), "+f"(d[41]), "+f"(d[42]), "+f"(d[43]), "+f"(d[44]), "+f"(d[45]), "+f"(d[46]), "+f"(d[47]), "+f"(d[48]), "+f"(d[49]), "+f"(d[50]), "+f"(d[51]), "+f"(d[52]), "+f"(d[53]), "+f"(d[54]), "+f"(d[55]), "+f"(d[56]), "+f"(d[57]), "+f"(d[58]), "+f"(d[59]), "+f"(d[60]), "+f"(d[61]), "+f"(d[62]), "+f"(d[63]), "+f"(d[64]), "+f"(d[65]), "+f"(d[66]), "+f"(d[67]), "+f"(d[68]), "+f"(d[69]), "+f"(d[70]), "+f"(d[71]), "+f"(d[72]), "+f"(d[73]), "+f"(d[74]), "+f"(d[75]), "+f"(d[76]), "+f"(d[77]), "+f"(d[78]), "+f"(d[79]), "+f"(d[80]), "+f"(d[81]), "+f"(d[82]), "+f"(d[83]), "+f"(d[84]), "+f"(d[85]), "+f"(d[86]), "+f"(d[87]), "+f"(d[88]), "+f"(d[89]), "+f"(d[90]), "+f"(d[91]), "+f"(d[92]), "+f"(d[93]), "+f"(d[94]), "+f"(d[95])
    : "r"(a[0]), "r"(a[1]), "r"(a[2]), "r"(a[3]), "r"(blo), "n"(BO), "n"(BH));
}
template<uint32_t BO, uint32_t BH> __device__ __forceinline__ void mma192_rsp(float (&d)[96], const uint32_t* a, uint32_t blo, int sc) {
  asm volatile("{\n.reg .pred p;\n.reg .b32 ta, tb;\n.reg .b64 da, db;\nadd.u32 tb, %100, %101;\nmov.b64 db, {tb, %102};\nsetp.ne.b32 p, %103, 0;\n"
    "wgmma.mma_async.sync.aligned.m64n192k16.f32.bf16.bf16 {%0, %1, %2, %3, %4, %5, %6, %7, %8, %9, %10, %11, %12, %13, %14, %15, %16, %17, %18, %19, %20, %21, %22, %23, %24, %25, %26, %27, %28, %29, %30, %31, %32, %33, %34, %35, %36, %37, %38, %39, %40, %41, %42, %43, %44, %45, %46, %47, %48, %49, %50, %51, %52, %53, %54, %55, %56, %57, %58, %59, %60, %61, %62, %63, %64, %65, %66, %67, %68, %69, %70, %71, %72, %73, %74, %75, %76, %77, %78, %79, %80, %81, %82, %83, %84, %85, %86, %87, %88, %89, %90, %91, %92, %93, %94, %95}, {%96,%97,%98,%99}, db, p, 1, 1, 1;\n}\n"
    : "+f"(d[0]), "+f"(d[1]), "+f"(d[2]), "+f"(d[3]), "+f"(d[4]), "+f"(d[5]), "+f"(d[6]), "+f"(d[7]), "+f"(d[8]), "+f"(d[9]), "+f"(d[10]), "+f"(d[11]), "+f"(d[12]), "+f"(d[13]), "+f"(d[14]), "+f"(d[15]), "+f"(d[16]), "+f"(d[17]), "+f"(d[18]), "+f"(d[19]), "+f"(d[20]), "+f"(d[21]), "+f"(d[22]), "+f"(d[23]), "+f"(d[24]), "+f"(d[25]), "+f"(d[26]), "+f"(d[27]), "+f"(d[28]), "+f"(d[29]), "+f"(d[30]), "+f"(d[31]), "+f"(d[32]), "+f"(d[33]), "+f"(d[34]), "+f"(d[35]), "+f"(d[36]), "+f"(d[37]), "+f"(d[38]), "+f"(d[39]), "+f"(d[40]), "+f"(d[41]), "+f"(d[42]), "+f"(d[43]), "+f"(d[44]), "+f"(d[45]), "+f"(d[46]), "+f"(d[47]), "+f"(d[48]), "+f"(d[49]), "+f"(d[50]), "+f"(d[51]), "+f"(d[52]), "+f"(d[53]), "+f"(d[54]), "+f"(d[55]), "+f"(d[56]), "+f"(d[57]), "+f"(d[58]), "+f"(d[59]), "+f"(d[60]), "+f"(d[61]), "+f"(d[62]), "+f"(d[63]), "+f"(d[64]), "+f"(d[65]), "+f"(d[66]), "+f"(d[67]), "+f"(d[68]), "+f"(d[69]), "+f"(d[70]), "+f"(d[71]), "+f"(d[72]), "+f"(d[73]), "+f"(d[74]), "+f"(d[75]), "+f"(d[76]), "+f"(d[77]), "+f"(d[78]), "+f"(d[79]), "+f"(d[80]), "+f"(d[81]), "+f"(d[82]), "+f"(d[83]), "+f"(d[84]), "+f"(d[85]), "+f"(d[86]), "+f"(d[87]), "+f"(d[88]), "+f"(d[89]), "+f"(d[90]), "+f"(d[91]), "+f"(d[92]), "+f"(d[93]), "+f"(d[94]), "+f"(d[95])
    : "r"(a[0]), "r"(a[1]), "r"(a[2]), "r"(a[3]), "r"(blo), "n"(BO), "n"(BH), "r"(sc));
}
template<uint32_t BO, uint32_t BH> __device__ __forceinline__ void mma32_rs(float (&d)[16], const uint32_t* a, uint32_t blo) {
  asm volatile("{\n.reg .pred p;\n.reg .b32 ta, tb;\n.reg .b64 da, db;\nadd.u32 tb, %20, %21;\nmov.b64 db, {tb, %22};\nsetp.ne.b32 p, 1, 0;\n"
    "wgmma.mma_async.sync.aligned.m64n32k16.f32.bf16.bf16 {%0, %1, %2, %3, %4, %5, %6, %7, %8, %9, %10, %11, %12, %13, %14, %15}, {%16,%17,%18,%19}, db, p, 1, 1, 1;\n}\n"
    : "+f"(d[0]), "+f"(d[1]), "+f"(d[2]), "+f"(d[3]), "+f"(d[4]), "+f"(d[5]), "+f"(d[6]), "+f"(d[7]), "+f"(d[8]), "+f"(d[9]), "+f"(d[10]), "+f"(d[11]), "+f"(d[12]), "+f"(d[13]), "+f"(d[14]), "+f"(d[15])
    : "r"(a[0]), "r"(a[1]), "r"(a[2]), "r"(a[3]), "r"(blo), "n"(BO), "n"(BH));
}
template<uint32_t BO, uint32_t BH> __device__ __forceinline__ void mma32_rs0(float (&d)[16], const uint32_t* a, uint32_t blo) {
  asm volatile("{\n.reg .pred p;\n.reg .b32 ta, tb;\n.reg .b64 da, db;\nadd.u32 tb, %20, %21;\nmov.b64 db, {tb, %22};\nsetp.ne.b32 p, 0, 0;\n"
    "wgmma.mma_async.sync.aligned.m64n32k16.f32.bf16.bf16 {%0, %1, %2, %3, %4, %5, %6, %7, %8, %9, %10, %11, %12, %13, %14, %15}, {%16,%17,%18,%19}, db, p, 1, 1, 1;\n}\n"
    : "=f"(d[0]), "=f"(d[1]), "=f"(d[2]), "=f"(d[3]), "=f"(d[4]), "=f"(d[5]), "=f"(d[6]), "=f"(d[7]), "=f"(d[8]), "=f"(d[9]), "=f"(d[10]), "=f"(d[11]), "=f"(d[12]), "=f"(d[13]), "=f"(d[14]), "=f"(d[15])
    : "r"(a[0]), "r"(a[1]), "r"(a[2]), "r"(a[3]), "r"(blo), "n"(BO), "n"(BH));
}
template<uint32_t BO, uint32_t BH> __device__ __forceinline__ void mma40_rs(float (&d)[20], const uint32_t* a, uint32_t blo) {
  asm volatile("{\n.reg .pred p;\n.reg .b32 ta, tb;\n.reg .b64 da, db;\nadd.u32 tb, %24, %25;\nmov.b64 db, {tb, %26};\nsetp.ne.b32 p, 1, 0;\n"
    "wgmma.mma_async.sync.aligned.m64n40k16.f32.bf16.bf16 {%0, %1, %2, %3, %4, %5, %6, %7, %8, %9, %10, %11, %12, %13, %14, %15, %16, %17, %18, %19}, {%20,%21,%22,%23}, db, p, 1, 1, 1;\n}\n"
    : "+f"(d[0]), "+f"(d[1]), "+f"(d[2]), "+f"(d[3]), "+f"(d[4]), "+f"(d[5]), "+f"(d[6]), "+f"(d[7]), "+f"(d[8]), "+f"(d[9]), "+f"(d[10]), "+f"(d[11]), "+f"(d[12]), "+f"(d[13]), "+f"(d[14]), "+f"(d[15]), "+f"(d[16]), "+f"(d[17]), "+f"(d[18]), "+f"(d[19])
    : "r"(a[0]), "r"(a[1]), "r"(a[2]), "r"(a[3]), "r"(blo), "n"(BO), "n"(BH));
}
template<uint32_t BO, uint32_t BH> __device__ __forceinline__ void mma40_rs0(float (&d)[20], const uint32_t* a, uint32_t blo) {
  asm volatile("{\n.reg .pred p;\n.reg .b32 ta, tb;\n.reg .b64 da, db;\nadd.u32 tb, %24, %25;\nmov.b64 db, {tb, %26};\nsetp.ne.b32 p, 0, 0;\n"
    "wgmma.mma_async.sync.aligned.m64n40k16.f32.bf16.bf16 {%0, %1, %2, %3, %4, %5, %6, %7, %8, %9, %10, %11, %12, %13, %14, %15, %16, %17, %18, %19}, {%20,%21,%22,%23}, db, p, 1, 1, 1;\n}\n"
    : "=f"(d[0]), "=f"(d[1]), "=f"(d[2]), "=f"(d[3]), "=f"(d[4]), "=f"(d[5]), "=f"(d[6]), "=f"(d[7]), "=f"(d[8]), "=f"(d[9]), "=f"(d[10]), "=f"(d[11]), "=f"(d[12]), "=f"(d[13]), "=f"(d[14]), "=f"(d[15]), "=f"(d[16]), "=f"(d[17]), "=f"(d[18]), "=f"(d[19])
    : "r"(a[0]), "r"(a[1]), "r"(a[2]), "r"(a[3]), "r"(blo), "n"(BO), "n"(BH));
}
template<uint32_t AO, uint32_t AH, uint32_t BO, uint32_t BH> __device__ __forceinline__ void mma40_tt(float (&d)[20], uint32_t alo, uint32_t blo) {
  asm volatile("{\n.reg .pred p;\n.reg .b32 ta, tb;\n.reg .b64 da, db;\nadd.u32 ta, %20, %21;\nmov.b64 da, {ta, %22};\nadd.u32 tb, %23, %24;\nmov.b64 db, {tb, %25};\nsetp.ne.b32 p, 1, 0;\n"
    "wgmma.mma_async.sync.aligned.m64n40k16.f32.bf16.bf16 {%0, %1, %2, %3, %4, %5, %6, %7, %8, %9, %10, %11, %12, %13, %14, %15, %16, %17, %18, %19}, da, db, p, 1, 1, 1, 1;\n}\n"
    : "+f"(d[0]), "+f"(d[1]), "+f"(d[2]), "+f"(d[3]), "+f"(d[4]), "+f"(d[5]), "+f"(d[6]), "+f"(d[7]), "+f"(d[8]), "+f"(d[9]), "+f"(d[10]), "+f"(d[11]), "+f"(d[12]), "+f"(d[13]), "+f"(d[14]), "+f"(d[15]), "+f"(d[16]), "+f"(d[17]), "+f"(d[18]), "+f"(d[19])
    : "r"(alo), "n"(AO), "n"(AH), "r"(blo), "n"(BO), "n"(BH));
}
template<uint32_t AO, uint32_t AH, uint32_t BO, uint32_t BH> __device__ __forceinline__ void mma40_tt0(float (&d)[20], uint32_t alo, uint32_t blo) {
  asm volatile("{\n.reg .pred p;\n.reg .b32 ta, tb;\n.reg .b64 da, db;\nadd.u32 ta, %20, %21;\nmov.b64 da, {ta, %22};\nadd.u32 tb, %23, %24;\nmov.b64 db, {tb, %25};\nsetp.ne.b32 p, 0, 0;\n"
    "wgmma.mma_async.sync.aligned.m64n40k16.f32.bf16.bf16 {%0, %1, %2, %3, %4, %5, %6, %7, %8, %9, %10, %11, %12, %13, %14, %15, %16, %17, %18, %19}, da, db, p, 1, 1, 1, 1;\n}\n"
    : "=f"(d[0]), "=f"(d[1]), "=f"(d[2]), "=f"(d[3]), "=f"(d[4]), "=f"(d[5]), "=f"(d[6]), "=f"(d[7]), "=f"(d[8]), "=f"(d[9]), "=f"(d[10]), "=f"(d[11]), "=f"(d[12]), "=f"(d[13]), "=f"(d[14]), "=f"(d[15]), "=f"(d[16]), "=f"(d[17]), "=f"(d[18]), "=f"(d[19])
    : "r"(alo), "n"(AO), "n"(AH), "r"(blo), "n"(BO), "n"(BH));
}
template<uint32_t AO, uint32_t AH, uint32_t BO, uint32_t BH> __device__ __forceinline__ void mma8_tn(float (&d)[4], uint32_t alo, uint32_t blo) {
  asm volatile("{\n.reg .pred p;\n.reg .b32 ta, tb;\n.reg .b64 da, db;\nadd.u32 ta, %4, %5;\nmov.b64 da, {ta, %6};\nadd.u32 tb, %7, %8;\nmov.b64 db, {tb, %9};\nsetp.ne.b32 p, 1, 0;\n"
    "wgmma.mma_async.sync.aligned.m64n8k16.f32.bf16.bf16 {%0, %1, %2, %3}, da, db, p, 1, 1, 1, 0;\n}\n"
    : "+f"(d[0]), "+f"(d[1]), "+f"(d[2]), "+f"(d[3])
    : "r"(alo), "n"(AO), "n"(AH), "r"(blo), "n"(BO), "n"(BH));
}
template<uint32_t AO, uint32_t AH, uint32_t BO, uint32_t BH> __device__ __forceinline__ void mma8_tn0(float (&d)[4], uint32_t alo, uint32_t blo) {
  asm volatile("{\n.reg .pred p;\n.reg .b32 ta, tb;\n.reg .b64 da, db;\nadd.u32 ta, %4, %5;\nmov.b64 da, {ta, %6};\nadd.u32 tb, %7, %8;\nmov.b64 db, {tb, %9};\nsetp.ne.b32 p, 0, 0;\n"
    "wgmma.mma_async.sync.aligned.m64n8k16.f32.bf16.bf16 {%0, %1, %2, %3}, da, db, p, 1, 1, 1, 0;\n}\n"
    : "=f"(d[0]), "=f"(d[1]), "=f"(d[2]), "=f"(d[3])
    : "r"(alo), "n"(AO), "n"(AH), "r"(blo), "n"(BO), "n"(BH));
}
template<uint32_t AO, uint32_t AH, uint32_t BO, uint32_t BH> __device__ __forceinline__ void mma128_ss(float (&d)[64], uint32_t alo, uint32_t blo) {
  asm volatile("{\n.reg .pred p;\n.reg .b32 ta, tb;\n.reg .b64 da, db;\nadd.u32 ta, %64, %65;\nmov.b64 da, {ta, %66};\nadd.u32 tb, %67, %68;\nmov.b64 db, {tb, %69};\nsetp.ne.b32 p, 1, 0;\n"
    "wgmma.mma_async.sync.aligned.m64n128k16.f32.bf16.bf16 {%0, %1, %2, %3, %4, %5, %6, %7, %8, %9, %10, %11, %12, %13, %14, %15, %16, %17, %18, %19, %20, %21, %22, %23, %24, %25, %26, %27, %28, %29, %30, %31, %32, %33, %34, %35, %36, %37, %38, %39, %40, %41, %42, %43, %44, %45, %46, %47, %48, %49, %50, %51, %52, %53, %54, %55, %56, %57, %58, %59, %60, %61, %62, %63}, da, db, p, 1, 1, 0, 1;\n}\n"
    : "+f"(d[0]), "+f"(d[1]), "+f"(d[2]), "+f"(d[3]), "+f"(d[4]), "+f"(d[5]), "+f"(d[6]), "+f"(d[7]), "+f"(d[8]), "+f"(d[9]), "+f"(d[10]), "+f"(d[11]), "+f"(d[12]), "+f"(d[13]), "+f"(d[14]), "+f"(d[15]), "+f"(d[16]), "+f"(d[17]), "+f"(d[18]), "+f"(d[19]), "+f"(d[20]), "+f"(d[21]), "+f"(d[22]), "+f"(d[23]), "+f"(d[24]), "+f"(d[25]), "+f"(d[26]), "+f"(d[27]), "+f"(d[28]), "+f"(d[29]), "+f"(d[30]), "+f"(d[31]), "+f"(d[32]), "+f"(d[33]), "+f"(d[34]), "+f"(d[35]), "+f"(d[36]), "+f"(d[37]), "+f"(d[38]), "+f"(d[39]), "+f"(d[40]), "+f"(d[41]), "+f"(d[42]), "+f"(d[43]), "+f"(d[44]), "+f"(d[45]), "+f"(d[46]), "+f"(d[47]), "+f"(d[48]), "+f"(d[49]), "+f"(d[50]), "+f"(d[51]), "+f"(d[52]), "+f"(d[53]), "+f"(d[54]), "+f"(d[55]), "+f"(d[56]), "+f"(d[57]), "+f"(d[58]), "+f"(d[59]), "+f"(d[60]), "+f"(d[61]), "+f"(d[62]), "+f"(d[63])
    : "r"(alo), "n"(AO), "n"(AH), "r"(blo), "n"(BO), "n"(BH));
}
template<uint32_t AO, uint32_t AH, uint32_t BO, uint32_t BH> __device__ __forceinline__ void mma128_ss0(float (&d)[64], uint32_t alo, uint32_t blo) {
  asm volatile("{\n.reg .pred p;\n.reg .b32 ta, tb;\n.reg .b64 da, db;\nadd.u32 ta, %64, %65;\nmov.b64 da, {ta, %66};\nadd.u32 tb, %67, %68;\nmov.b64 db, {tb, %69};\nsetp.ne.b32 p, 0, 0;\n"
    "wgmma.mma_async.sync.aligned.m64n128k16.f32.bf16.bf16 {%0, %1, %2, %3, %4, %5, %6, %7, %8, %9, %10, %11, %12, %13, %14, %15, %16, %17, %18, %19, %20, %21, %22, %23, %24, %25, %26, %27, %28, %29, %30, %31, %32, %33, %34, %35, %36, %37, %38, %39, %40, %41, %42, %43, %44, %45, %46, %47, %48, %49, %50, %51, %52, %53, %54, %55, %56, %57, %58, %59, %60, %61, %62, %63}, da, db, p, 1, 1, 0, 1;\n}\n"
    : "=f"(d[0]), "=f"(d[1]), "=f"(d[2]), "=f"(d[3]), "=f"(d[4]), "=f"(d[5]), "=f"(d[6]), "=f"(d[7]), "=f"(d[8]), "=f"(d[9]), "=f"(d[10]), "=f"(d[11]), "=f"(d[12]), "=f"(d[13]), "=f"(d[14]), "=f"(d[15]), "=f"(d[16]), "=f"(d[17]), "=f"(d[18]), "=f"(d[19]), "=f"(d[20]), "=f"(d[21]), "=f"(d[22]), "=f"(d[23]), "=f"(d[24]), "=f"(d[25]), "=f"(d[26]), "=f"(d[27]), "=f"(d[28]), "=f"(d[29]), "=f"(d[30]), "=f"(d[31]), "=f"(d[32]), "=f"(d[33]), "=f"(d[34]), "=f"(d[35]), "=f"(d[36]), "=f"(d[37]), "=f"(d[38]), "=f"(d[39]), "=f"(d[40]), "=f"(d[41]), "=f"(d[42]), "=f"(d[43]), "=f"(d[44]), "=f"(d[45]), "=f"(d[46]), "=f"(d[47]), "=f"(d[48]), "=f"(d[49]), "=f"(d[50]), "=f"(d[51]), "=f"(d[52]), "=f"(d[53]), "=f"(d[54]), "=f"(d[55]), "=f"(d[56]), "=f"(d[57]), "=f"(d[58]), "=f"(d[59]), "=f"(d[60]), "=f"(d[61]), "=f"(d[62]), "=f"(d[63])
    : "r"(alo), "n"(AO), "n"(AH), "r"(blo), "n"(BO), "n"(BH));
}

#define XD 600
#define XSTEP 300
#define XPD 450
#define XPB 8192
#define SPG 5600
#define WL0 1800
#define WLS 350
#define NB0 2
#define WP1 2000
#define PF_START 5600
#define PFP 126
#define GPERM 0x76543210u
#define FMODE 1
#define NM0 3
#define PWAIT 600
#define AWAKE 3
#define O1H 1
#define X1N 16
#define WDW 2
#define WDGAP 50
#define YWAIT 500
#define OUTW 0
#define CWAIT 500
#define O1ALL 0
#define RDV 1
#define MSTEP 1200
#define MSLP 1000
#define MPOLL 3200
#define LMP 8
#define WOGAP 200
#define CLR0 22000
#define UPGAP 300
#define OUTGAP 150
#define MPROMO P128
#define MLOAD tma_load_ef
struct Ptrs { const bf16 *x, *wmod, *c, *wr, *wqkv; int by_sm; Scratch* s; const bf16 *wg, *wu, *wd, *wo; bf16* out; uint16_t role[132]; };

#define BAR(i) (sb + OFF_BAR + 8u * (i))

__device__ __forceinline__ uint32_t get_tag(uint32_t sb) { mbar_wait(BAR(B_TAG), 0); const uint32_t d = __shfl_sync(0xffffffffu, lds32(sb + OFF_CST + 32), 0); return d + 1 + (d & 2); }
__device__ __forceinline__ int d_kb(int n, int hg) {
    if (n < 2) return 2 * hg + n;
    const int h = n >= 9, q = n - 2 - 7 * h;
    return 2 * (q + (q >= hg)) + h;
}

__global__ void __launch_bounds__(NTHREADS, 1)
fused_kernel(const Ptrs p, const __grid_constant__ CUtensorMap tmM, const __grid_constant__ CUtensorMap tmX, const __grid_constant__ CUtensorMap tmW,
             const __grid_constant__ CUtensorMap tmWo, const __grid_constant__ CUtensorMap tmPhi, const __grid_constant__ CUtensorMap tmG,
             const __grid_constant__ CUtensorMap tmU, const __grid_constant__ CUtensorMap tmD, const __grid_constant__ CUtensorMap tmO)
{
    extern __shared__ __align__(1024) uint8_t smem_raw[];
    const uint32_t sb = smem_u32(smem_raw);
    const uint32_t cstart = __shfl_sync(0xffffffffu, clk32(), 0);
    const int tid = threadIdx.x, lane = tid & 31, warp = __shfl_sync(0xffffffffu, tid >> 5, 0);
    if (blockIdx.x < 128) {
        if (warp == 8) asm volatile("prefetch.global.L2 [%0];" :: "l"(p.wmod + (size_t)(blockIdx.x * 8 + (lane >> 2)) * 6144 + (lane & 1) * 64 + (lane & 2) * 512));
        if (warp == 13 && (lane & 1) < NM0 - 2) asm volatile("prefetch.global.L2 [%0];" :: "l"(p.wmod + (size_t)(blockIdx.x * 8 + (lane >> 2)) * 6144 + 128 + (lane & 1) * 64 + (lane & 2) * 512));
        if (warp == 12) l2_prefetch(p.wqkv + (size_t)blockIdx.x * 1536, 3072);
        if (warp == 9) { spin_until(cstart + XPD); l2_prefetch(p.x + (size_t)blockIdx.x * 16384, XPB); }
    }
    if (warp == 10) { tmap_prefetch(&tmM); tmap_prefetch(&tmX); tmap_prefetch(&tmW); }
    if (warp == 11) asm volatile("prefetch.global.L2 [%0];" :: "l"((lane < 16 ? p.c : p.wr) + (lane & 15) * 64));
    #pragma unroll
    for (int i = 0; i < 5; i++) e_init(BAR(5 * warp + i), warp < 5 ? 1 : warp < 7 ? 2 : warp < 9 ? 4 : 8);
    mbar_init_fence();
    if (warp == B_TAG / 5) { e_arrive_tx(BAR(B_TAG), 16); bulk_load(sb + OFF_CST + 32, p.s->done, 16, BAR(B_TAG)); }
    uint32_t role;
    asm("mov.u32 %0, %%smid;" : "=r"(role));
    role = p.role[p.by_sm ? role : blockIdx.x];
    const int b = role & 255;
    if (b >= 128 && warp == 0) {
        #pragma unroll
        for (int i = 0; i < 2; i++) { e_arrive_tx(BAR(i), 32768); MLOAD(sb + i * 32768u, &tmM, (b & 1) * 1024, (b & 2) * 256 + i * 256, BAR(i)); }
    }
    __syncthreads();

    if (b >= 128) {
        const int sp = b & 3;
        if (warp == 8) {
            #pragma unroll 1
            for (int j = 2, st = 2, ph = 1; j < 64; j++) {
                if (j == 2 * NM0) spin_until(cstart + SPG);
                mbar_wait(BAR(B_EA + st), ph);
                e_arrive_tx(BAR(st), 32768);
                MLOAD(sb + st * 32768u, &tmM, j < 32 ? (sp & 1) * 1024 + (j >> 1) * 64 : 2560 + sp * 512 + (j >> 2) * 64, (j < 32 ? (sp & 2) + (j & 1) : j & 3) * 256, BAR(st));
                if (++st == 6) { st = 0; ph ^= 1; }
            }
        } else if (warp < 8) {
            const int g = lane >> 2, c = lane & 3;
            {
                const bf16* cp = p.c + (tid >> 3) * 32 + (tid & 1) * 16 + (tid & 6);
                const uint32_t c0 = ldg32(cp), c1 = ldg32(cp + 8);
                stg_zero(p.s->llm1 + (tid >> 4) * 64 + sp * 16 + (tid & 15));
                if (tid < 128) stg_zero(p.s->llmod2 + sp * 128 + tid);
                sts64(sb + 200704u + tid * 8, silu2(c0), silu2(c1));
                bar_sync(1, 256);
                TR(57);
            }
            const uint32_t tag = get_tag(sb);
            const uint32_t wa = sb + (warp * 32 + (lane & 7) + (lane >> 4) * 8) * 128u + ((((lane >> 3) & 1) ^ (lane & 7)) << 4);
            float m[4][4];
            #pragma unroll
            for (int i = 0; i < 4; i++) m[i][0] = m[i][1] = m[i][2] = m[i][3] = 0.f;
            #pragma unroll 1
            for (int r = 0, st = 0, ph = 0; r < 32; r++) {
                const int n = r < 16 ? r : (r >> 1) + 8;
                const bf16* wr = p.wr + (sp & 1) * 512 + (n & 7) * 64 + (g & 3) * 16 + 2 * c;
                const uint32_t wr0 = ldg32(wr), wr1 = ldg32(wr + 8);
                const uint32_t sa = sb + 200704u + ((r < 16 ? sp >> 1 : r & 1) * 16 + warp) * 64 + c * 16;
                const uint4 sv0 = lds128(sa), sv1 = lds128(sa + 512);
                uint32_t f[16][4];
                #pragma unroll
                for (int q = 0; q < 2; q++) {
                    mbar_wait(BAR(st + q), ph);
                    if (r == 0 && warp == 0) TR(60 + q);
                    #pragma unroll
                    for (int i = 0; i < 8; i++) ldsm4t(f[8 * q + i], (wa + (st + q) * 32768u + (i >> 2) * 2048u) ^ ((i & 3) << 5));
                }
                #pragma unroll
                for (int i = 0; i < 16; i++) {
                    const uint4& sv = i < 8 ? sv0 : sv1;
                    mma16816(m[i & 3], f[i][0], f[i][1], f[i][2], f[i][3], (i & 4) ? sv.z : sv.x, (i & 4) ? sv.w : sv.y);
                    if ((i & 7) == 7) e_arrive(BAR(B_EA + st + (i >> 3)));
                }
                st += 2; if (st == 6) { st = 0; ph ^= 1; }
                if (r >= 16 && !(r & 1)) continue;
                const uint32_t red = sb + 196608u + (n & 1) * 2048u;
                const uint32_t a = red + warp * 256u + (c * 16 + (g >> 1) * 4 + (g & 1)) * 4u;
                stsf(a, sel4(c, m[0][0], m[1][0], m[2][0], m[3][0])); stsf(a + 8, sel4(c, m[0][2], m[1][2], m[2][2], m[3][2]));
                #pragma unroll
                for (int i = 0; i < 4; i++) m[i][0] = m[i][1] = m[i][2] = m[i][3] = 0.f;
                bar_sync(1, 256);
                if (warp == (n & 7)) {
                    const uint32_t ra = red + (lane >> 4) * 1024u + (lane & 15) * 16u;
                    const uint4 r0 = lds128(ra), r1 = lds128(ra + 256), r2 = lds128(ra + 512), r3 = lds128(ra + 768);
                    #define F4(f) ((u2f(r0.f) + u2f(r1.f)) + (u2f(r2.f) + u2f(r3.f)))
                    float x = F4(x), y = F4(y), z = F4(z), w = F4(w);
                    #undef F4
                    x += shfl_x(x, 16); y += shfl_x(y, 16); z += shfl_x(z, 16); w += shfl_x(w, 16);
                    if (n < 16) {
                        if (lane < 16) st_ll4(p.s->llm1 + n * 64 + sp * 16 + lane, x, y, z, w, tag);
                    } else {
                        uint32_t lo = pack2(x, y), hi2 = pack2(z, w);
                        float d = fmaf(bf_lo(lo), bf_lo(wr0), bf_hi(lo) * bf_hi(wr0)) + fmaf(bf_lo(hi2), bf_lo(wr1), bf_hi(hi2) * bf_hi(wr1));
                        if (sp >= 2) {
                            lo = hadd2(lo, ONE2); hi2 = hadd2(hi2, ONE2);
                            const uint32_t r0 = hmul2(lo, wr0), r1 = hmul2(hi2, wr1);
                            d = (bf_lo(r0) + bf_hi(r0)) + (bf_lo(r1) + bf_hi(r1));
                        }
                        #pragma unroll 1
                        for (int k = 1; k < 16; k <<= 1) d += shfl_x(d, k);
                        if (lane < 16) st_ll(p.s->llmod2 + sp * 128 + (n & 7) * 16 + lane, lo, hi2, f2u(d), tag);
                    }
                    TR(n);
                }
            }
        }
    } else if (warp >= 12) {
        reg_dec<24>();
        const int rb = b >> 3, hg = b & 7, fs = role >> 8;
        const bool ffn = fs < 112;
        if (warp == 12) {
            #pragma unroll 1
            for (int j = 0, s = 0, ph = 1; j < 16; j++) {
                if (j < 2) mbar_wait(j ? BAR(B_STS) : BAR(B_STP), 0);
                mbar_wait(BAR(B_EA + s), ph);
                e_arrive_tx(BAR(B_FA + s), 16384); tma_load(sb + OFF_A + s * 16384u, &tmX, j * 64, rb * 128, BAR(B_FA + s));
                if (j == 0) TS(2);
                if (j == 1) GT(0);
                if (j == 6) GT(1);
                if (j == 11) GT(2);
                if (++s == 3) { s = 0; ph ^= 1; }
            }
            tmap_prefetch(&tmO);
            const uint32_t tag = get_tag(sb);
            e_arrive(BAR(B_FD)); e_arrive(BAR(B_FD + 1));
            #pragma unroll 1
            for (int q = 0; q < 3; q++) {
                mbar_wait(q < 2 ? BAR(B_KST + 1 + 2 * q) : BAR(B_OWN), 0);
                poll_flags(q < 2 ? p.s->flk + (q + 1) * 256 + (hg * 16 + (lane & 15)) * 2 : p.s->flo + ((rb & 12) * 16 + lane * 2) * 2, tag);
                if (q == 2) break;
                e_arrive_tx(BAR(B_KVL + q), 16896); bulk_load(sb + (q ? OFF_PHI : OFF_KL), p.s->kvacc + hg * 2112 + q * 1056, 16896, BAR(B_KVL + q));
                TS(12 + q);
                if (!q) GT(4);
            }
            if (O1H == 2) e_arrive(BAR(B_UD));
            TS(3); GT(5);
            const uint4* osrc = p.s->os + (size_t)rb * 16 * 1024;
            #pragma unroll 1
            for (int n = 2; n < 17; n++) {
                const uint32_t s = n & 3, fb = BAR(B_FD + s), dst = sb + OFF_R0 + s * 16384u;
                mbar_wait(BAR(B_ED + s), ((n >> 2) - 1) & 1);
                if (n == 5 || n == 9) mbar_wait(n == 5 ? BAR(B_OST) : BAR(B_O1), 0);
                e_arrive_tx(fb, 16384);
                if (n < 16) bulk_load(dst, osrc + d_kb(n, hg) * 1024, 16384, fb);
                else { e_arrive(fb); tma_load(dst, &tmX, hg * 128, rb * 128, fb); }
                if (n == X1N) { e_arrive_tx(BAR(B_WPHI), 16384); tma_load(sb + OFF_X1, &tmX, hg * 128 + 64, rb * 128, BAR(B_WPHI)); }
                TR(32 + n);
            }
            GT(6);
            mbar_wait(BAR(B_CAND), 0);
            GT(7);
            const uint2 lc = lds64(sb + OFF_CST + 16);
            const uint32_t w0 = __shfl_sync(0xffffffffu, lc.x >> 4, 0), w1 = __shfl_sync(0xffffffffu, lc.y >> 4, 0);
            mbar_wait(BAR(B_SWP), 0);
            fence_async_smem();
            if (OUTW) mbar_wait(BAR(B_SEL), 0);
            #pragma unroll 1
            for (uint32_t w = 0; w < 8; w++)
                if (w != w0 && w != w1) { tma_store4(&tmO, rb * 128 + w * 16, hg * 2, sb + OFF_OUT + w * 4096u); spin_until(clk32() + OUTGAP); }
            mbar_wait(BAR(B_SEL), 0);
            const uint2 sel = lds64(sb + OFF_CST + 24);
            #pragma unroll 1
            for (uint32_t i = 0; i < (w0 == w1 ? 8u : 16u); i++) {
                const uint32_t w = i < 8 ? w0 : w1, r = (i & 7) * 2 + (lane >> 4), row = rb * 128 + w * 16 + r;
                const uint4 o = lds128(sb + OFF_OUT + w * 4096u + ((lane >> 3) & 1) * 2048u + r * 128u + (((lane ^ r) & 7) << 4));
                if (row != (~sel.x & 2047u) && row != (~sel.y & 2047u)) stg128(p.out + (size_t)row * 1024 + hg * 128 + (lane & 15) * 8, o);
            }
            bulk_wait_read();
        } else if (warp == 14) {
            const uint32_t fb = ffn ? 65536 : 0;
            e_arrive_tx(BAR(B_GF), fb); e_arrive_tx(BAR(B_UD), fb); e_arrive_tx(BAR(B_UF), fb); e_arrive_tx(BAR(B_WD), fb);
            uint32_t due = cstart + WP1;
            #pragma unroll 1
            for (int i = -2; i < 26; i++) {
                if (i >= 0) {
                    const bf16* a = i < 8 ? p.wg + (size_t)(i * 128 + b) * 3584 : i < 16 ? p.wu + (size_t)((i - 8) * 128 + b) * 3584
                                  : i < 18 ? p.wo + (size_t)(b * 2 + i - 16) * 4096 : p.wd + (size_t)(b * 8 + i - 18) * 3584;
                    sleep_until(due);
                    l2_prefetch(a, (i >> 1) == 8 ? 8192 : 7168);
                    due += 7 * PFP;
                }
                if (i == 1) { tmap_prefetch(&tmPhi); tmap_prefetch(&tmG); tmap_prefetch(&tmWo); tmap_prefetch(&tmU); tmap_prefetch(&tmD); mbar_wait(BAR(B_STS), 0); }
                if (ffn && (uint32_t)(i - 3) < 8u) tma_load_ef(sb + OFF_R0 + (i - 3) * 8192u, &tmG, fs * 32, (i - 3) * 128, BAR(B_GF));
                if (ffn && (uint32_t)(i - 11) < 8u) tma_load(sb + OFF_WPHI, &tmU, fs * 32, (i - 11) * 128, BAR(B_UD));
                if (i == 19) { mbar_wait(BAR(B_UD), 0); e_arrive_tx(BAR(B_WPHI), 8192); tma_load(sb + OFF_WPHI, &tmPhi, 0, hg * 128, BAR(B_WPHI)); }
                if (i == LMP + 2 * (b & 3) + (b >> 6)) tma_prefetch(&tmM, 2048 + (b >> 6) * 2048 + (b >> 2) * 64, (b & 3) * 256);
                if (i < 13) {
                    sleep_until(due);
                    l2_prefetch(p.wqkv + (size_t)((i + 3) * 128 + b) * 1536, 3072);
                    due += i == -2 ? PF_START - WP1 : 3 * PFP;
                }
            }
            if (lane < 4) stg_zero(p.s->flo + b * 4 + lane);
            const uint32_t tag = get_tag(sb);
            #pragma unroll 1
            for (int q = 0; q < 2; q++) {
                mbar_wait(BAR(B_OWN + q), 0);
                if (q && O1H) mbar_wait(O1H == 1 ? BAR(B_FD + 2) : BAR(B_UD), O1H - 1);
                bulk_store(p.s->os + ((size_t)b * 2 + q) * 1024, sb + OFF_R0 + q * 16384u, 16384);
                if (q) { bulk_wait_read(); e_arrive(BAR(B_OST)); }
                bulk_wait();
                __syncwarp();
                st_flag(p.s->flo + (b * 2 + q) * 2, tag, lane);
                TS(7 + q);
            }
        } else {
            uint4* fk = p.s->flk + (hg * 16 + rb) * 2;
            if (warp == 13) {
                #pragma unroll 1
                for (int i = 0; i < 32; i++) {
                    const uint32_t s = i & 3;
                    if (i < NB0) spin_until(cstart + WL0 + WLS * i); else if (i == NB0) mbar_wait(BAR(B_STS), 0);
                    mbar_wait(BAR(B_EB + s), ((i >> 2) - 1) & 1);
                    e_arrive_tx(BAR(B_FB + s), 24576); tma_load4(sb + OFF_B + s * 24576u, &tmW, i * 32, hg * 2, BAR(B_FB + s));
                    TR(64 + i);
                }
                mbar_wait(BAR(B_EB), 1); mbar_wait(BAR(B_EB + 1), 1);
                e_arrive_tx(BAR(B_LMF), 32768); tma_load_ef(sb + OFF_B, &tmM, 2048 + (b >> 6) * 2048 + (b >> 2) * 64, (b & 3) * 256, BAR(B_LMF));
                mbar_wait(BAR(B_LMD), 0);
                #pragma unroll 1
                for (int n = 0; n < 4; n++) {
                    e_arrive_tx(BAR(B_FD + n), 16384); tma_load4(sb + OFF_DB + n * 16384u, &tmWo, d_kb(n, hg) * 64, hg * 2, BAR(B_FD + n));
                    spin_until(clk32() + WOGAP);
                }
            } else {
                sleep_until(cstart + CLR0);
                const uint32_t tag = get_tag(sb);
                #pragma unroll 1
                for (int i = lane; i < 132; i += 32) stg_zero(p.s->kvacc + hg * 2112 + rb * 132 + i);
                if (lane < 4) stg_zero(fk + 256 + (lane >> 1) * 256 + (lane & 1));
                fence_gpu();
                __syncwarp();
                st_flag(fk, tag, lane);
                sleep_until(clk32() + 2000);
                poll_flags(p.s->flk + (hg * 16 + (lane & 15)) * 2, tag);
                mbar_wait(BAR(B_QE), 0);
                #pragma unroll 1
                for (int i = 0; i < 4; i++) {
                    stg_zero(p.s->llln2 + b * 128 + i * 32 + lane);
                    stg_zero(p.s->llrowh + (i >> 1) * 8192 + (rb * 2 + (i & 1)) * 256 + hg * 32 + lane);
                    #pragma unroll
                    for (int k = 0; k < 4; k++) stg_zero(p.s->lly + (fs & 127) * 512 + i * 128 + k * 32 + lane);
                }
                if (lane < 2 && hg == (rb & 7)) stg_zero(p.s->llcand + rb * 2 + lane);
                __syncwarp();
                e_arrive(BAR(B_KZ));
            }
            const int q = warp == 13;
            const uint32_t tag = get_tag(sb);
            mbar_wait(BAR(B_KZ), 0);
            #pragma unroll 1
            for (int h = 2 * q; h < 2 * q + 2; h++) {
                mbar_wait(BAR(B_KST + h), 0);
                uint4* acc = p.s->kvacc + (hg * 4 + h) * 528;
                bulk_reduce(acc, sb + OFF_V + h * 8192u, 8192); bulk_reduce(acc + 512, sb + OFF_ZS + h * 256u, 256);
            }
            bulk_wait();
            if (q) e_arrive(BAR(B_KZ));
            TR(158 + q);
            fence_gpu();
            __syncwarp();
            st_flag(fk + 256 + q * 256, tag, lane);
            TS(10 + q);
            if (q) {
                #pragma unroll 1
                for (int n = 4; n < 16; n++) {
                    const uint32_t s = n & 3;
                    mbar_wait(BAR(B_ED + s), ((n >> 2) - 1) & 1);
                    e_arrive_tx(BAR(B_FD + s), 16384);
                    tma_load4(sb + OFF_DB + s * 16384u, &tmWo, d_kb(n, hg) * 64, hg * 2, BAR(B_FD + s));
                    TR(96 + n);
                    if (ffn && (n >> 2) == 2) {
                        const int z = 8 * (n & 1) + (n & 2);
                        #pragma unroll
                        for (int k = 0; k < 2; k++) tma_load_ef(sb + OFF_F2 + (n & 1) * 32768u + k * 16384u + (n & 2) * 2048u, &tmD, z * 64 + k * 256, fs * 32, BAR(B_WD));
                    }
                }
                if (ffn) {
                    mbar_wait(BAR(B_ED + WDW), 1);
                    #pragma unroll 1
                    for (int z = 0; z < 8; z++) { tma_load_ef(sb + OFF_DB + z * 4096u, &tmD, z * 128 + 64, fs * 32, BAR(B_WD)); sleep_until(clk32() + WDGAP); }
                }
            } else {
                if (ffn) {
                    mbar_wait(BAR(B_KZ), 1);
                    #pragma unroll 1
                    for (int i = 7; i < 15; i++) {
                        if (i == 12) mbar_wait(BAR(B_KVT + 1), 0);
                        tma_load_ef(sb + OFF_F2 + (i & 7) * 8192u, &tmU, fs * 32, (i & 7) * 128, BAR(B_UF));
                        sleep_until(clk32() + UPGAP);
                    }
                }
                mbar_wait(BAR(B_OST), 0);
                poll_flags(p.s->flo + (O1ALL ? (rb & 12) * 16 + lane * 2 + 1 : rb * 16 + (lane & 7) * 2 + 1) * 2, tag);
                e_arrive(BAR(B_O1));
                TS(4);
            }
        }
    } else if (warp >= 8) {
        reg_dec<24>();
        const int rb = b >> 3, hg = b & 7, w4 = warp & 3, g = lane >> 2, c = lane & 3, t = tid & 127;
        const uint32_t sv = silu2(ldg32(p.c + (b & 3) * 256 + 2 * t)), tag = get_tag(sb);
        if (w4 < 3) {
            spin_until(cstart + MPOLL + MSTEP * w4);
            #pragma unroll 1
            for (int j = w4, ph = 1; j < 16; j += 3, ph ^= 1) {
                uint4 w[2];
                poll_words<2, 0, 3>(w, p.s->llm1 + j * 64 + lane, 32, tag);
                uint32_t lo = pack2(u2f(w[0].x) + u2f(w[1].x), u2f(w[0].y) + u2f(w[1].y)), hi = pack2(u2f(w[0].z) + u2f(w[1].z), u2f(w[0].w) + u2f(w[1].w));
                if (lane >= 16) { lo = hadd2(lo, ONE2); hi = hadd2(hi, ONE2); }
                sts64(sb + OFF_TAB + j * 256 + (lane & 15) * 16 + (lane < 16 ? 8 : 0), lo, hi);
                __syncwarp();
                if (j == 0) TS(5);
                TR(16 + j);
                mbar_wait(BAR(B_EA + w4), ph);
                e_arrive(BAR(B_FA + w4));
                __nanosleep(MSLP);
            }
        }
        mbar_wait(BAR(B_QE), 0);
        if (warp == 8) GT(3);
        sts32(sb + OFF_KL + w4 * 1024u + lane * 4, sv);
        fence_async_smem();
        bar_sync(2, 128);
        reg_inc<56>();
        {
            float m0[4], m1[4];
            const uint32_t da = desc_lo(sb + OFF_B, 16), db = desc_lo(sb + OFF_KL, 16);
            mbar_wait(BAR(B_LMF), 0);
            wg_fence();
            #define LMS(f, i) f<(i) * 256, H128, ((i) >> 1) * 64 + ((i) & 1) * 4, H128>(m0, da, db); f<(i) * 256 + 128, H128, ((i) >> 1) * 64 + ((i) & 1) * 4 + 2, H128>(m1, da, db)
            LMS(mma8_tn0, 0); LMS(mma8_tn, 1); LMS(mma8_tn, 2); LMS(mma8_tn, 3); LMS(mma8_tn, 4); LMS(mma8_tn, 5); LMS(mma8_tn, 6); LMS(mma8_tn, 7);
            #undef LMS
            wg_commit();
            wg_wait<0>();
            acc_fence(m0); acc_fence(m1);
            e_arrive(BAR(B_LMD));
            const float v0 = m0[0] + m1[0], v1 = m0[2] + m1[2], u0 = shfl_x(v0, 4), u1 = shfl_x(v1, 4);
            if (!(lane & 7)) st_ll4(p.s->llg + (b >> 6) * 1024 + (b & 3) * 256 + ((b >> 2) & 15) * 16 + w4 * 4 + (lane >> 3), v0, u0, v1, u1, tag);
            if (warp == 8) TR(150);
        }
        #pragma unroll 1
        for (int h = 0; h < 4; h++) {
            float okv[20];
            const uint32_t vb = OFF_V + h * 8192u, dp = desc_lo(sb + OFF_PHI + (h & 1) * 16384u, 16), dv = desc_lo(sb + vb, OFF_ONES - vb);
            mbar_wait(BAR(B_PF + h), 0);
            fence_async_smem();
            wg_fence();
            #define KVS(i) mma40_tt<(i) * 128, H128, (i) * (64u - (64u << 16)), H64>(okv, dp, dv)
            mma40_tt0<0, H128, 0, H64>(okv, dp, dv); KVS(1); KVS(2); KVS(3); KVS(4); KVS(5); KVS(6); KVS(7);
            #undef KVS
            wg_commit();
            wg_wait<0>();
            acc_fence(okv);
            if (h < 2) e_arrive(BAR(B_PE + h));
            bar_sync(2, 128);
            #pragma unroll
            for (int k = 0; k < 4; k++) sts128(sb + vb + (k * 128 + t) * 16u, make_uint4(f2u(okv[4 * k]), f2u(okv[4 * k + 1]), f2u(okv[4 * k + 2]), f2u(okv[4 * k + 3])));
            if (c == 0) sts64(sb + OFF_ZS + h * 256u + (w4 * 8 + g) * 8u, f2u(okv[16]), f2u(okv[18]));
            fence_async_smem();
            __syncwarp();
            e_arrive(BAR(B_KST + h));
            if (warp == 8) TR(151 + h);
        }
        #pragma unroll 1
        for (int q = 0; q < 2; q++) {
            const uint32_t f = w4 * 16 + g, kl = sb + (q ? OFF_PHI : OFF_KL), ta = sb + (q ? OFF_KL : OFF_KVT) + f * 64u + ((g >> 1) << 4) + 4 * c;
            const uint32_t za = sb + OFF_Z + (f + 8 * (c & 1)) * 64u + (((2 * q) ^ (g >> 1)) << 4) + (c >> 1) * 8;
            mbar_wait(q ? BAR(B_KVT) : BAR(B_STP), q ^ 1);
            mbar_wait(BAR(B_KVL + q), 0);
            uint4 v[8]; float z[2];
            #pragma unroll
            for (int k = 0; k < 8; k++) v[k] = lds128(kl + (k >> 2) * 8448u + (k & 3) * 2048u + t * 16u);
            #pragma unroll
            for (int hh = 0; hh < 2; hh++) z[hh] = ldsf(kl + hh * 8448u + 8192u + (w4 * 8 + g) * 8u + (c & 1) * 4);
            #pragma unroll
            for (int k = 0; k < 8; k++) {
                sts32((ta ^ ((k & 3) << 4)) + (k >> 2) * 4096u, pack2(u2f(v[k].x), u2f(v[k].y))); sts32((ta ^ ((k & 3) << 4)) + (k >> 2) * 4096u + 512, pack2(u2f(v[k].z), u2f(v[k].w)));
            }
            #pragma unroll
            for (int hh = 0; hh < 2; hh++) { const uint32_t zz = pack2(z[hh], z[hh]); sts64(za ^ (hh << 4), zz, zz); }
            fence_async_smem();
            __syncwarp();
            e_arrive(BAR(B_KVT + q));
            if (warp == 8) TR(155 + q);
        }
        reg_dec<24>();
        mbar_wait(BAR(B_O1), 0);
        if (w4 == 0 || w4 == 3) {
            float s[4] = {0.f, 0.f, 0.f, 0.f};
            #pragma unroll 1
            for (int k = 0; k < 2; k++) {
                uint4 w[2];
                poll_words<2, 0, 3>(w, p.s->llg + (w4 & 1) * 1024 + k * 512 + hg * 32 + lane, 256, tag);
                s[0] += u2f(w[0].x) + u2f(w[1].x); s[1] += u2f(w[0].y) + u2f(w[1].y); s[2] += u2f(w[0].z) + u2f(w[1].z); s[3] += u2f(w[0].w) + u2f(w[1].w);
            }
            const uint32_t lo = pack2(s[0], s[1]), hi = pack2(s[2], s[3]);
            sts64(w4 ? sb + OFF_T3 + lane * 8 : sb + OFF_T1 + lane * 16, lo, hi);
            if (!w4) sts64(sb + OFF_T1 + 512 + lane * 16, lo, hi);
        } else {
            const bf16* wr = p.wr + hg * 128 + g * 16 + 2 * c;
            const uint32_t wr0 = ldg32(wr), wr1 = ldg32(wr + 8);
            uint4 w[2];
            poll_words<2, 1>(w, p.s->llmod2 + (w4 - 1) * 256 + hg * 32 + lane, (lane & 15) * 16 - hg * 32 - lane, tag);
            sts64(sb + OFF_T2 + lane * 16 + (w4 & 1) * 8, w[0].x, w[0].y);
            if (w4 == 2) sts64(sb + OFF_T1 + 512 + lane * 16 + 8, hmul2(w[0].x, wr0), hmul2(w[0].y, wr1));
            float d = u2f(w[1].z);
            #pragma unroll 1
            for (int k = 1; k < 16; k <<= 1) d += shfl_x(d, k);
            stsf(sb + OFF_CST + 8 + (w4 & 1) * 4, d);
        }
        __syncwarp();
        e_arrive(BAR(B_PAR));
        if (warp == 9) TS(6);
        if (w4 < 2) {
            mbar_wait(BAR(B_PAR), 0);
            const uint4 ta = lds128(sb + OFF_T2 + lane * 16);
            const uint2 gb = lds64(sb + OFF_T3 + lane * 8);
            uint4* d = pin_ptr(p.s->llrowh + (rb * 2 + w4) * 256 + hg * 32 + lane);
            mbar_wait(BAR(B_KEYS), 0);
            const uint4 kk = lds128(sb + OFF_KEY + lane * 16);
            uint32_t k[4] = {kk.x, kk.y, kk.z, kk.w}, b0, b1;
            top2<4>(k, b0, b1);
            const uint32_t cd = ~(w4 ? b1 : b0) & 127u;
            const uint32_t xa = sb + OFF_R0 + (g >> 2) * (OFF_X1 - OFF_R0) + cd * 128u + ((((g & 3) * 2) ^ (cd & 7)) << 4) + c * 4;
            const uint32_t x0 = lds32(xa), x1 = lds32(xa ^ 16);
            const uint4 st = lds128(sb + OFF_ST2 + cd * 16);
            st_ll(d, lnmod(x0, st.x, st.y, st.z, ta.x, ta.z), lnmod(x1, st.x, st.y, st.z, ta.y, ta.w), gb.x, tag);
            st_ll(d + 8192, x0, x1, gb.y, tag);
            sts32(sb + OFF_CST + 16 + w4 * 4, cd);
            __syncwarp();
            e_arrive(BAR(B_CAND));
            if (warp == 8) TS(9);
        } else if (w4 == 2) {
            uint4* cp = pin_ptr(p.s->llcand + lane);
            mbar_wait(BAR(B_KEYS), 0);
            if (hg == (rb & 7)) {
                const uint4 kk = lds128(sb + OFF_KEY + lane * 16);
                uint32_t k[4] = {kk.x, kk.y, kk.z, kk.w}, b0, b1;
                top2<4>(k, b0, b1);
                if ((lane >> 1) == rb) st_ll(cp, (lane & 1) ? b1 : b0, tag, tag, tag);
            } else spin_until(clk32() + CWAIT);
            uint2 v = make_uint2(0, 0);
            #pragma unroll 1
            for (int it = 0; it < POLL_MAX; it++) {
                if (v.y != tag) asm volatile("ld.relaxed.gpu.global.v2.b32 {%0,%1}, [%2];" : "=r"(v.x), "=r"(v.y) : "l"(cp) : "memory");
                if (__all_sync(0xffffffffu, v.y == tag)) break;
            }
            uint32_t k[1] = {v.x}, b0, b1;
            top2<1>(k, b0, b1);
            sts64(sb + OFF_CST + 24, b0, b1);
            __syncwarp();
            e_arrive(BAR(B_SEL));
        }
    } else {
        reg_inc<232>();
        float a0[96], a1[96];
        {
            const int g = lane >> 2, c = lane & 3;
            uint4* stp = p.s->llstat + b * 16 + warp * 2 + (lane >> 4);
            if ((lane & 15) == 0) stg_zero(stp);
            spin_until(cstart + XD + XSTEP * warp);
            e_arrive_tx(BAR(B_XP + warp), 4096);
            bulk_load(sb + OFF_R0 + warp * 4096u, p.x + (size_t)(b * 16 + 2 * warp) * 1024, 4096, BAR(B_XP + warp));
            const uint32_t tag = get_tag(sb);
            if (tid < 64) sts128(sb + OFF_ONES + tid * 16, make_uint4(ONE2, ONE2, ONE2, ONE2));
            if (tid == 64) sts64(sb + OFF_CST, role, tag);
            if (AWAKE & 1) mbar_wait_awake(BAR(B_XP + warp), 0); else mbar_wait(BAR(B_XP + warp), 0);
            e_arrive(BAR(B_STP));
            if (warp == 7) TS(14);
            float s[2][4], q0[2][4], q1[2][4];
            #pragma unroll
            for (int i = 0; i < 4; i++) s[0][i] = s[1][i] = q0[0][i] = q0[1][i] = q1[0][i] = q1[1][i] = 0.f;
            #pragma unroll
            for (int i = 0; i < 4; i++) {
                const uint4 x0 = lds128(sb + OFF_R0 + warp * 4096u + (lane + 32 * i) * 16u), x1 = lds128(sb + OFF_R0 + warp * 4096u + 2048u + (lane + 32 * i) * 16u);
                mma16816(s[0], x0.x, x1.x, x0.y, x1.y, ONE2, ONE2); mma16816(s[1], x0.z, x1.z, x0.w, x1.w, ONE2, ONE2);
                mma16816(q0[0], x0.x, x1.x, x0.y, x1.y, x0.x, x0.y); mma16816(q0[1], x0.z, x1.z, x0.w, x1.w, x0.z, x0.w);
                mma16816(q1[0], x0.x, x1.x, x0.y, x1.y, x1.x, x1.y); mma16816(q1[1], x0.z, x1.z, x0.w, x1.w, x1.z, x1.w);
            }
            const bool dg = c == (g >> 1);
            const float s0 = dg ? s[0][0] + s[1][0] : 0.f, s1 = dg ? s[0][2] + s[1][2] : 0.f;
            const float sq0 = dg ? ((g & 1) ? q0[0][1] + q0[1][1] : q0[0][0] + q0[1][0]) : 0.f, sq1 = dg ? ((g & 1) ? q1[0][3] + q1[1][3] : q1[0][2] + q1[1][2]) : 0.f;
            const bool up = lane >= 16;
            float sm = (up ? s1 : s0) + shfl_x(up ? s0 : s1, 16), sq = (up ? sq1 : sq0) + shfl_x(up ? sq0 : sq1, 16);
            #pragma unroll
            for (int m = 8; m >= 1; m >>= 1) { sm += shfl_x(sm, m); sq += shfl_x(sq, m); }
            uint32_t m2, rh, rl; float rinv;
            ln_final(sm, sq, m2, rinv);
            split_rcp(rinv, rh, rl);
            if ((lane & 15) == 0) st_ll(stp, m2, rh, rl, tag);
            if (warp == 7) TS(15);
            uint4 st[2];
            if (PWAIT) { mbar_wait(BAR(B_STP), 0); if (warp < 7) spin_until(clk32() + PWAIT); }
            #pragma unroll 1
            for (int it = 0; it < POLL_MAX; it++) {
                st[0] = ld_ll(p.s->llstat + (b >> 3) * 128 + warp * 16 + g); st[1] = ld_ll(p.s->llstat + (b >> 3) * 128 + warp * 16 + g + 8);
                const uint32_t o = RDV ? ld_rlx(&p.s->llstat[((b >> 5) * 4 + c) * 128 + warp * 16 + 15].w) : tag;
                if (__all_sync(0xffffffffu, !tag_bad(tag_bad(o ^ tag, st[0].w, tag), st[1].w, tag))) break;
                if (AWAKE & 1) it += awake_zero();
            }
            e_arrive(BAR(B_STS));
            if (warp == 0) TS(16);
            const uint32_t lrow = warp * 16 + (lane & 15);
            uint32_t aad = sb + OFF_A + lrow * 128u + (((lane >> 4) ^ (lrow & 7)) << 4);
            uint32_t tad = sb + OFF_TAB + c * 16, ab = BAR(B_FA), pa = 0;
            uint32_t f0[4], f1[4];
            #define PREP(f, q) do { \
                const uint4 t = lds128(tad + (q) * 64); \
                ldsm4(f, aad ^ ((q) << 5)); \
                f[0] = lnmod(f[0], st[0].x, st[0].y, st[0].z, t.x, t.z); f[1] = lnmod(f[1], st[1].x, st[1].y, st[1].z, t.x, t.z); \
                f[2] = lnmod(f[2], st[0].x, st[0].y, st[0].z, t.y, t.w); f[3] = lnmod(f[3], st[1].x, st[1].y, st[1].z, t.y, t.w); } while (0)
            #define MMA(f, off) do { wg_fence(); mma192_rs<(off), H128>(a0, f, blo); mma192_rs<(off) + 768, H128>(a1, f, blo); wg_commit(); wg_wait<1>(); } while (0)
            mbar_wait(ab, 0);
            PREP(f0, 0);
            if (RDV) mbar_wait(BAR(B_STS), 0);
            #pragma unroll 1
            for (int j = 0; j < 16; j++) {
                const uint32_t bb = BAR(B_FB) + (j & 1) * 16, blo = desc_lo(sb + OFF_B, 4096) + (j & 1) * 3072, pb = (j >> 1) & 1;
                mbar_wait(bb, pb);
                wg_fence(); mma192_rsp<0, H128>(a0, f0, blo, j); mma192_rsp<768, H128>(a1, f0, blo, j); wg_commit(); wg_wait<1>();
                if (j) e_arrive((bb ^ 16) + 8 * (B_EB - B_FB) + 8);
                PREP(f1, 1);
                MMA(f1, 128);
                PREP(f0, 2);
                mbar_wait(bb + 8, pb);
                MMA(f0, 1536);
                e_arrive(bb + 8 * (B_EB - B_FB));
                PREP(f1, 3);
                MMA(f1, 1536 + 128);
                e_arrive(ab + 8 * (B_EA - B_FA));
                ab += 8; aad += 16384; tad += 256;
                if (ab == BAR(B_FA + 3)) { ab -= 24; aad -= 49152; pa ^= 1; }
                if (j < 15) mbar_wait(ab, pa);
                PREP(f0, 0);
            }
            #undef PREP
            #undef MMA
        }
        int tid_o; asm volatile("mov.u32 %0, %%tid.x;" : "=r"(tid_o) :: "memory");
        const int tid = tid_o, lane = tid & 31, warp = __shfl_sync(0xffffffffu, tid >> 5, 0), wgi = warp >> 2, g = lane >> 2, c = lane & 3;
        const uint32_t srow = warp * 16 + (lane & 15);
        const uint32_t t128 = srow * 128u + (((lane >> 4) ^ (srow & 7)) << 4);
        mbar_wait(BAR(B_WPHI), 0);
        mbar_wait(BAR(B_EA), 1);
        wg_wait<0>();
        acc_fence(a0); acc_fence(a1);
        e_arrive(BAR(B_QE));
        if (warp == 0) TS(18);
        uint32_t ph0[16], ph1[16], kq[32];
        {
        uint32_t pk[16], mm[4];
        float ea[32], eb[32];
        #define PIN() do { acc_fence(ea); acc_fence(eb); pin<16>(pk); pin<4>(mm); } while (0)
        {
            float p0[16], p1[16];
            const uint32_t dw = desc_lo(sb + OFF_WPHI, 16);
            #define PMMA(f, o) do { wg_fence(); mma32_rs0<(o), H64>(p0, f, dw); mma32_rs0<(o) + 128, H64>(p1, f + 8, dw); \
                mma32_rs<(o) + 64, H64>(p0, f + 4, dw); mma32_rs<(o) + 192, H64>(p1, f + 12, dw); wg_commit(); } while (0)
            #define V_OUT(lo) _Pragma("unroll") for (int i = lo; i < lo + 4; i++) { const int o = 32 + 8 * i; \
                stsm4(sb + OFF_V + (i >> 1) * 8192u + srow * 64u + (((2 * (i & 1) + (lane >> 4)) ^ ((srow >> 1) & 3)) << 4), \
                      pack2(a1[o], a1[o + 1]), pack2(a1[o + 2], a1[o + 3]), pack2(a1[o + 4], a1[o + 5]), pack2(a1[o + 6], a1[o + 7])); }
            V_OUT(0);
            #pragma unroll
            for (int i = 0; i < 16; i++) ph0[i] = pack2(a0[64 + 2 * i], a0[65 + 2 * i]);
            PMMA(ph0, 0);
            V_OUT(4);
            #undef V_OUT
            wg_wait<0>();
            acc_fence(p0); acc_fence(p1);
            fm_max(p0, pk, mm); fm_max(p1, pk + 8, mm + 2);
            #pragma unroll
            for (int i = 0; i < 16; i++) ph1[i] = pack2(a1[2 * i], a1[2 * i + 1]);
            PMMA(ph1, 256);
            fm_args(pk, mm, ea);
            if (warp == 0) TS(19);
            fm_exp<0, 16>(ea);
            #pragma unroll
            for (int i = 0; i < 32; i++) kq[i] = pack2(a0[2 * i], a0[2 * i + 1]);
            acc_fence(ea); pin<32>(kq);
            wg_wait<0>();
            acc_fence(p0); acc_fence(p1);
            #define PHI_OUT(ph, i) do { if (u < 2) { \
                    mbar_wait(u ? BAR(B_PE + (i)) : (i) ? BAR(B_LMD) : BAR(B_QE), 0);          \
                    _Pragma("unroll") for (int q = 0; q < 4; q++) stsm4((sb + OFF_PHI + (i) * 16384u + t128) ^ (q << 5), ph[4 * q], ph[4 * q + 1], ph[4 * q + 2], ph[4 * q + 3]); \
                    __syncwarp(); \
                    e_arrive(BAR(B_PF + (i)) + u * 16); } } while (0)
            reg_dec<216>();
            #pragma unroll 1
            for (int u = 0; u < 4; u++) {
                fm_exp<16, 32>(ea); fm_args(pk + 8, mm + 2, eb);
                PIN();
                if (warp == 0) TR(129 + (u & 1) * 6);
                fm_exp<0, 16>(eb); fm_norm(ea, ph0); fm_max(p0, pk, mm);
                acc_fence(eb); pin<8>(pk); pin<2>(mm);
                PHI_OUT(ph0, 0);
                if (warp == 0) TR(130 + (u & 1) * 6);
                fm_exp<16, 32>(eb); fm_args(pk, mm, ea); fm_max(p1, pk + 8, mm + 2);
                PIN();
                if (warp == 0) TR(131 + (u & 1) * 6);
                if (u == 0) PMMA(kq, 0); else PMMA(kq + 16, 256);
                fm_exp<0, 16>(ea); fm_norm(eb, ph1);
                acc_fence(ea);
                if (warp == 0) TR(132 + (u & 1) * 6);
                PHI_OUT(ph1, 1);
                wg_wait<0>();
                acc_fence(p0); acc_fence(p1);
                if (u == 1) e_arrive(BAR(B_STP));
                if (u == 2) {
                    #pragma unroll
                    for (int i = 0; i < 16; i++) { kq[i] = ph0[i]; kq[16 + i] = ph1[i]; }
                }
                if (warp == 0) TR(133 + (u & 1) * 6);
                if (warp == 0) TS(21 + u);
            }
            #undef PHI_OUT
            #undef PMMA
        }
        }
        uint32_t gf[16][4], uf[16][4];
        const uint32_t fo = (warp >> 1) * 16384u + ((lane & 7) + (lane >> 4) * 8) * 64u + (((2 * (warp & 1) + ((lane >> 3) & 1)) ^ ((lane >> 1) & 3)) << 4);
        mbar_wait(BAR(B_GF), 0);
        #pragma unroll
        for (int i = 0; i < 16; i++) ldsm4t(gf[i], sb + OFF_R0 + fo + i * 1024u);
        e_arrive(BAR(B_STS));
        #define O_BLOCK(pp, ph0, ph1) do { \
            if ((AWAKE & 2) && !(pp)) mbar_wait_awake(BAR(B_KVT + (pp)), 0); else mbar_wait(BAR(B_KVT + (pp)), 0); \
            if (warp == 0) TS(25 + 3 * (pp)); \
            float o0[20], o1[20]; \
            const uint32_t dk = (pp) ? desc_lo(sb + OFF_KL, OFF_Z + 32 - OFF_KL) : desc_lo(sb + OFF_KVT, OFF_Z - OFF_KVT); \
            constexpr uint32_t K1 = 256u - (255u << 16);          \
            wg_fence(); \
            mma40_rs0<0, H64>(o0, ph0, dk); mma40_rs0<K1, H64>(o1, ph1, dk); \
            mma40_rs<64, H64>(o0, ph0 + 4, dk); mma40_rs<K1 + 64, H64>(o1, ph1 + 4, dk); \
            mma40_rs<128, H64>(o0, ph0 + 8, dk); mma40_rs<K1 + 128, H64>(o1, ph1 + 8, dk); \
            mma40_rs<192, H64>(o0, ph0 + 12, dk); mma40_rs<K1 + 192, H64>(o1, ph1 + 12, dk); \
            wg_commit(); \
            wg_wait<0>(); \
            acc_fence(o0); acc_fence(o1); \
            if (warp == 0) TS(26 + 3 * (pp)); \
            if (!(pp)) mbar_wait(BAR(B_STS), 1);          \
            _Pragma("unroll") for (int hh = 0; hh < 2; hh++) { \
                const float (&o)[20] = hh ? o1 : o0; \
                uint32_t h0, l0, h1, l1; \
                split_rcp(rcp(rbf(rbf(o[16]) + 1e-6f)), h0, l0); split_rcp(rcp(rbf(rbf(o[18]) + 1e-6f)), h1, l1); \
                _Pragma("unroll") for (int q = 0; q < 2; q++) \
                    stsm4((sb + OFF_R0 + (pp) * 16384u + t128) ^ ((2 * hh + q) << 5), hdiv2(pack2(o[8 * q], o[8 * q + 1]), h0, l0), hdiv2(pack2(o[8 * q + 2], o[8 * q + 3]), h1, l1), \
                          hdiv2(pack2(o[8 * q + 4], o[8 * q + 5]), h0, l0), hdiv2(pack2(o[8 * q + 6], o[8 * q + 7]), h1, l1)); \
            } \
            fence_async_smem(); \
            __syncwarp(); \
            e_arrive(BAR(B_OWN + (pp))); \
            if (warp == 0) TS(27 + 3 * (pp)); \
        } while (0)
        float acc[64];
        const uint32_t da = desc_lo(sb + OFF_R0 + wgi * 8192u, 16), db = desc_lo(sb + OFF_DB, 8192);
        #define D_MMA(first, s) do { \
            wg_fence(); \
            first<(s) * 1024, H128, (s) * 1024, H128>(acc, da, db); mma128_ss<(s) * 1024 + 2, H128, (s) * 1024 + 128, H128>(acc, da, db); \
            mma128_ss<(s) * 1024 + 4, H128, (s) * 1024 + 256, H128>(acc, da, db); mma128_ss<(s) * 1024 + 6, H128, (s) * 1024 + 384, H128>(acc, da, db); \
            wg_commit(); } while (0)
        O_BLOCK(0, kq, (kq + 16));
        O_BLOCK(1, ph0, ph1);
        reg_inc<232>();
        mbar_wait(BAR(B_OWN), 0);
        mbar_wait(BAR(B_FD), 0);
        D_MMA(mma128_ss0, 0);
        mbar_wait(BAR(B_OWN + 1), 0);
        #undef PIN
        #undef O_BLOCK
        #define D_STEP(n) do { \
            mbar_wait(BAR(B_FD + ((n) & 3)), ((n) >> 2) & 1); \
            if (warp == 0) TR(112 + (n)); \
            D_MMA(mma128_ss, (n) & 3); \
            if ((n) == 3) mbar_wait(BAR(B_UF), 0); \
            if ((n) >= 3 && (n) < 7) { ldsm4t(uf[2 * (((n) + 5) & 7)], sb + OFF_F2 + fo + (((n) + 5) & 7) * 2048u); ldsm4t(uf[2 * (((n) + 5) & 7) + 1], sb + OFF_F2 + fo + (((n) + 5) & 7) * 2048u + 1024u); } \
            wg_wait<1>(); \
            if ((n) != 2) e_arrive(BAR(B_ED + (((n) + 3) & 3))); } while (0)
        D_STEP(1);
        wg_wait<0>();
        e_arrive(BAR(B_ED + 1));
        D_STEP(2);
        if (warp == 0) TS(31);
        D_STEP(3); D_STEP(4); D_STEP(5); D_STEP(6); D_STEP(7); D_STEP(8); D_STEP(9); D_STEP(10); D_STEP(11); D_STEP(12); D_STEP(13); D_STEP(14); D_STEP(15);
        #undef D_STEP
        #undef D_MMA
        #define XADDR(i) ((sb + ((i) < 4 ? OFF_R0 : OFF_X1) + t128) ^ (((i) & 3) << 5))
        mbar_wait(BAR(B_PAR), 0);
        const uint4 cst = lds128(sb + OFF_CST);
        const int b = cst.x & 255;
        const uint32_t tag = cst.y;
        {
            uint32_t x2[8][4];
            mbar_wait(BAR(B_WPHI), 1); mbar_wait(BAR(B_FD), 0);
            #pragma unroll
            for (int i = 0; i < 8; i++) ldsm4(x2[i], XADDR(i));
            uint4* d = pin_ptr(p.s->llln2 + b * 128 + warp * 16 + g);
            const uint32_t ta = sb + OFF_T1 + (g & 1) * 512 + c * 16;
            uint4 t = lds128(ta), tn = lds128(ta + 64);
            wg_wait<0>();
            acc_fence(acc);
            e_arrive(BAR(B_ED + 3));
            if (warp == 0) TS(32);
            float sd[4] = {0.f, 0.f, 0.f, 0.f}, qa[4] = {0.f, 0.f, 0.f, 0.f}, qb[4] = {0.f, 0.f, 0.f, 0.f};
            #pragma unroll
            for (int i = 0; i < 8; i++) {
                x2[i][0] = hadd2(x2[i][0], hmul2(t.x, pack2(acc[8 * i], acc[8 * i + 1]))); x2[i][1] = hadd2(x2[i][1], hmul2(t.x, pack2(acc[8 * i + 2], acc[8 * i + 3])));
                x2[i][2] = hadd2(x2[i][2], hmul2(t.y, pack2(acc[8 * i + 4], acc[8 * i + 5]))); x2[i][3] = hadd2(x2[i][3], hmul2(t.y, pack2(acc[8 * i + 6], acc[8 * i + 7])));
                mma16816(sd, x2[i][0], x2[i][1], x2[i][2], x2[i][3], t.z, t.w);
                t = tn;
                if (i < 6) tn = lds128(ta + (i + 2) * 64);
                mma16816(qa, x2[i][0], x2[i][1], x2[i][2], x2[i][3], x2[i][0], x2[i][2]);
                mma16816(qb, x2[i][0], x2[i][1], x2[i][2], x2[i][3], x2[i][1], x2[i][3]);
            }
            if (c == (g >> 1)) {
                st_ll(d, f2u(sd[0]), f2u((g & 1) ? qa[1] : qa[0]), f2u(sd[1]), tag);
                st_ll(d + 8, f2u(sd[2]), f2u((g & 1) ? qb[3] : qb[2]), f2u(sd[3]), tag);
            }
            if (warp == 0) TS(33);
            #pragma unroll
            for (int i = 0; i < 8; i++) stsm4(XADDR(i), x2[i][0], x2[i][1], x2[i][2], x2[i][3]);
        }
        {
        uint32_t x2[8][4]; uint4 t2[8]; uint2 t3[8];
        __syncwarp();
        #pragma unroll
        for (int i = 0; i < 8; i++) { ldsm4(x2[i], XADDR(i)); t2[i] = lds128(sb + OFF_T2 + i * 64 + c * 16); t3[i] = lds64(sb + OFF_T3 + i * 32 + c * 8); }
        mbar_wait(BAR(B_ED + 3), 1);
        {
            uint4 w[4];
            const uint32_t rl = warp * 16 + g + 8 * (c & 1);
            poll_words<4, 0, ~0u, AWAKE & 4>(w, p.s->llln2 + ((b & ~7) + (c >> 1) * 4) * 128 + rl, 128, tag);
            float s1 = (u2f(w[0].x) + u2f(w[1].x)) + (u2f(w[2].x) + u2f(w[3].x));
            float s2 = (u2f(w[0].y) + u2f(w[1].y)) + (u2f(w[2].y) + u2f(w[3].y));
            float dt = (u2f(w[0].z) + u2f(w[1].z)) + (u2f(w[2].z) + u2f(w[3].z));
            s1 += shfl_x(s1, 2); s2 += shfl_x(s2, 2); dt += shfl_x(dt, 2);
            uint32_t m2, rh, rl2; float rinv;
            ln_final(s1, s2, m2, rinv);
            const uint32_t key = (f2key(fmaf(fmaf(-bf_lo(m2), u2f(cst.z), dt), rinv, u2f(cst.w))) | 2047u) ^ ((b >> 3) * 128 + rl);
            split_rcp(rinv, rh, rl2);
            if (c < 2) { sts32(sb + OFF_KEY + rl * 4, key); sts128(sb + OFF_ST2 + rl * 16, make_uint4(m2, rh, rl2, 0)); }
            __syncwarp();
            e_arrive(BAR(B_KEYS));
        }
        if (warp == 0) TS(34);
        {
            const uint4 s0 = lds128(sb + OFF_ST2 + (warp * 16 + g) * 16), s1 = lds128(sb + OFF_ST2 + (warp * 16 + g + 8) * 16);
            const uint32_t oa = sb + OFF_OUT + warp * 2048u + t128;
            #pragma unroll
            for (int i = 0; i < 8; i++) {
                const uint4 t = t2[i]; const uint2 gb = t3[i];
                stsm4((oa + (i >> 2) * 2048u) ^ ((i & 3) << 5),
                      hadd2(x2[i][0], hmul2(gb.x, lnmod(x2[i][0], s0.x, s0.y, s0.z, t.x, t.z))), hadd2(x2[i][1], hmul2(gb.x, lnmod(x2[i][1], s1.x, s1.y, s1.z, t.x, t.z))),
                      hadd2(x2[i][2], hmul2(gb.y, lnmod(x2[i][2], s0.x, s0.y, s0.z, t.y, t.w))), hadd2(x2[i][3], hmul2(gb.y, lnmod(x2[i][3], s1.x, s1.y, s1.z, t.y, t.w))));
            }
            __syncwarp();
            e_arrive(BAR(B_SWP));
        }
        }
        #undef XADDR
        if (warp == 0) TS(35);
        uint32_t fx = 0, fh = 0, fg = 0, fs2, frow;
        uint32_t df[16][4];
        {
            const uint4* rh = pin_ptr(p.s->llrowh + tid);
            #pragma unroll
            for (int i = 8; i < 16; i++) ldsm4t(uf[i], sb + OFF_F2 + fo + i * 1024u);
            mbar_wait(BAR(B_WD), 0);
            const uint32_t da = ((lane & 7) + (lane >> 4) * 8) * 128u + ((((lane >> 3) & 1) ^ (lane & 7)) << 4);
            const uint32_t d0 = sb + OFF_F2 + (warp >> 1) * 16384u + (warp & 1) * 4096u + da, d1 = sb + OFF_DB + warp * 4096u + da;
            #pragma unroll
            for (int i = 0; i < 16; i++) ldsm4t(df[i], ((i < 8 ? d0 : d1) + (i & 1) * 2048u) ^ (((i >> 1) & 3) << 5));
            mbar_wait(BAR(B_SEL) + ((AWAKE & 4) ? awake_zero() : 0), 0);
            const uint2 bb = lds64(sb + OFF_CST + 24);
            const uint32_t b0 = bb.x, b1 = bb.y;
            if (warp == 0) TS(36);
            const uint32_t o0 = (~b0 & 0x780u) * 4, o1 = (~b1 & 0x780u) * 4, slot0 = o0, slot1 = o1 + (o0 == o1 ? 256 : 0);
            const int wd = ((g & 1) ? slot1 : slot0) + b * 2 + (c >> 1) - tid;
            uint4 hv[2], fv[2];
            #pragma unroll 1
            for (int it = 0; it < POLL_MAX; it++) {
                hv[0] = ld_ll(rh + slot0); hv[1] = ld_ll(rh + slot1);
                uint32_t bad = 0;
                if (warp == 0) {
                    fv[0] = ld_ll(rh + wd + 8192); fv[1] = ld_ll(rh + wd);
                    bad = tag_bad(fv[0].w ^ tag, fv[1].w, tag);
                    fx = (g & 2) ? fv[0].y : fv[0].x; fh = (g & 2) ? fv[1].y : fv[1].x; fg = (g & 2) ? fv[0].z : fv[1].z;
                }
                if (__all_sync(0xffffffffu, !ll_bad<1>(ll_bad<1>(bad, hv[0], tag), hv[1], tag))) break;
            }
            const uint32_t ha = sb + OFF_HSEL + (tid >> 3) * 128u + c * 16u + (g & 1) * 8u;
            sts64(ha, hv[0].x, hv[0].y); sts64(ha + 64, hv[1].x, hv[1].y);
            bar_sync(2 + (warp >> 1), 64);
            const uint32_t bk = (g & 1) ? b1 : b0;
            frow = ~bk & 2047u;
            const float sg = sigmoid_f(rbf(key2f((bk & ~2047u) | 1024u)));
            fs2 = pack2(sg, sg);
        }
        if (warp == 0) TS(37);
        uint4* yd = p.s->lly + (cst.x >> 8) * 512 + (warp * 8 + c) * 8 + g;
        const uint4* ys = p.s->lly + (tid >> 2) * 512 + b * 4 + c;
        uint16_t* od = (uint16_t*)p.out + (size_t)frow * 1024 + (b >> 1) * 16 + (b & 1) * 4 + c + 8 * (g >> 1);
        {
            float ag[2][4], au[2][4];
            #pragma unroll
            for (int i = 0; i < 4; i++) ag[0][i] = ag[1][i] = au[0][i] = au[1][i] = 0.f;
            #pragma unroll
            for (int i = 0; i < 8; i++) {
                const uint4 h = lds128(sb + OFF_HSEL + (warp >> 1) * 1024u + i * 128u + (lane & 7) * 16u);
                mma16816(ag[0], gf[2 * i][0], gf[2 * i][1], gf[2 * i][2], gf[2 * i][3], h.x, h.y);
                mma16816(au[0], uf[2 * i][0], uf[2 * i][1], uf[2 * i][2], uf[2 * i][3], h.x, h.y);
                mma16816(ag[1], gf[2 * i + 1][0], gf[2 * i + 1][1], gf[2 * i + 1][2], gf[2 * i + 1][3], h.z, h.w);
                mma16816(au[1], uf[2 * i + 1][0], uf[2 * i + 1][1], uf[2 * i + 1][2], uf[2 * i + 1][3], h.z, h.w);
            }
            sts64(sb + OFF_RED + (warp >> 1) * 512u + (c & 1) * 256u + ((warp & 1) * 16 + (c >> 1) * 8 + g) * 8u,
                  f2u(sel4(c, ag[0][0], ag[0][1], ag[0][2], ag[0][3]) + sel4(c, ag[1][0], ag[1][1], ag[1][2], ag[1][3])),
                  f2u(sel4(c, au[0][0], au[0][1], au[0][2], au[0][3]) + sel4(c, au[1][0], au[1][1], au[1][2], au[1][3])));
        }
        yd = pin_ptr(yd); ys = pin_ptr(ys); od = pin_ptr(od); pin<1>(&fs2);
        bar_sync(1, 256);
        {
            const uint32_t ra = sb + OFF_RED + lane * 16u;
            const uint4 r0 = lds128(ra), r1 = lds128(ra + 512), r2 = lds128(ra + 1024), r3 = lds128(ra + 1536);
            #define F4(f) ((u2f(r0.f) + u2f(r1.f)) + (u2f(r2.f) + u2f(r3.f)))
            const uint32_t hid = hmul2(silu2(pack2(F4(x), F4(z))), pack2(F4(y), F4(w)));
            #undef F4
            if (warp == 0) TS(38);
            const int src = (g & 1) * 16 + c;
            const uint32_t b0 = __shfl_sync(0xffffffffu, hid, src), b1 = __shfl_sync(0xffffffffu, hid, src + 4), b2 = __shfl_sync(0xffffffffu, hid, src + 8), b3 = __shfl_sync(0xffffffffu, hid, src + 12);
            float y[8][4];
            #pragma unroll
            for (int i = 0; i < 8; i++) {
                y[i][0] = y[i][1] = y[i][2] = y[i][3] = 0.f;
                mma16816(y[i], df[2 * i][0], df[2 * i][1], df[2 * i][2], df[2 * i][3], b0, b1);
            }
            #pragma unroll
            for (int i = 0; i < 8; i++) mma16816(y[i], df[2 * i + 1][0], df[2 * i + 1][1], df[2 * i + 1][2], df[2 * i + 1][3], b2, b3);
            if (cst.x < 112 * 256) {
                #pragma unroll
                for (int h = 0; h < 2; h++) {
                    #define YS(e) sel4(c, y[4 * h][e], y[4 * h + 1][e], y[4 * h + 2][e], y[4 * h + 3][e])
                    st_ll4(yd + 32 * h, YS(0), YS(1), YS(2), YS(3), tag);
                    #undef YS
                }
            }
        }
        if (warp == 0) TS(39);
        if (warp < 7) {
            uint4 v[2];
            v[0].w = v[1].w = 0;
            spin_until(clk32() + YWAIT);
            #pragma unroll 1
            for (int it = 0; it < POLL_MAX; it++) {
                if ((v[0].w ^ tag) & 3) v[0] = ld_ll(ys);
                if ((v[1].w ^ tag) & 3) v[1] = ld_ll(ys + 56 * 512);
                if (__all_sync(0xffffffffu, !(tag_bad(v[0].w ^ tag, v[1].w, tag) & 3))) break;
            }
            float y0 = u2f(v[0].x) + u2f(v[1].x), y1 = u2f(v[0].y) + u2f(v[1].y), y2 = u2f(v[0].z) + u2f(v[1].z), y3 = u2f(v[0].w) + u2f(v[1].w);
            const bool g0 = g & 1, g1 = g & 2;
            const float k0 = (g0 ? y1 : y0) + shfl_x(g0 ? y0 : y1, 4), k1 = (g0 ? y3 : y2) + shfl_x(g0 ? y2 : y3, 4);
            const float y = (g1 ? k1 : k0) + shfl_x(g1 ? k0 : k1, 8);
            stsf(sb + OFF_RED2 + (lane & 15) * 64u + (lane >> 4) * 32u + warp * 4u, y);
            bar_sync(6, 224);
            if (tid < 16) {
                const uint32_t a = sb + OFF_RED2 + lane * 64u;
                const uint4 ya = lds128(a), yb = lds128(a + 16), yc = lds128(a + 32), ye = lds128(a + 48);
                const float s = (((u2f(ya.x) + u2f(ya.y)) + (u2f(ya.z) + u2f(ya.w))) + ((u2f(yb.x) + u2f(yb.y)) + u2f(yb.z)))
                              + (((u2f(yc.x) + u2f(yc.y)) + (u2f(yc.z) + u2f(yc.w))) + ((u2f(ye.x) + u2f(ye.y)) + u2f(ye.z)));
                const uint32_t o = hadd2(fx, hmul2(fg, hadd2(fh, hmul2(pack2(s, s), fs2))));
                *od = (c & 1) ? o >> 16 : o;
                if (b == 0 && tid == 0) p.s->done[0] = tag;
                TS(40);
            }
        }
    }
}

typedef CUresult (*EncodeFn)(CUtensorMap*, CUtensorMapDataType, cuuint32_t, void*, const cuuint64_t*, const cuuint64_t*, const cuuint32_t*,
                             const cuuint32_t*, CUtensorMapInterleave, CUtensorMapSwizzle, CUtensorMapL2promotion, CUtensorMapFloatOOBfill);

CUtensorMap make_map(EncodeFn enc, const void* ptr, uint64_t cols, uint64_t rows, uint32_t bc, uint32_t br, CUtensorMapSwizzle swz, CUtensorMapL2promotion promo) {
    CUtensorMap m;
    cuuint64_t dims[2] = {cols, rows}, strides[1] = {cols * 2};
    cuuint32_t box[2] = {bc, br}, es[2] = {1, 1};
    enc(&m, CU_TENSOR_MAP_DATA_TYPE_BFLOAT16, 2, const_cast<void*>(ptr), dims, strides, box, es, CU_TENSOR_MAP_INTERLEAVE_NONE, swz, promo,
        CU_TENSOR_MAP_FLOAT_OOB_FILL_NONE);
    return m;
}
CUtensorMap make_map4(EncodeFn enc, const void* ptr, uint32_t groups, uint64_t rows, uint32_t br, CUtensorMapL2promotion promo) {
    CUtensorMap m;
    cuuint64_t dims[4] = {64, rows, 16, groups}, strides[3] = {groups * 2048ull, 128, 2048};
    cuuint32_t box[4] = {64, br, 2, groups}, es[4] = {1, 1, 1, 1};
    enc(&m, CU_TENSOR_MAP_DATA_TYPE_BFLOAT16, 4, const_cast<void*>(ptr), dims, strides, box, es, CU_TENSOR_MAP_INTERLEAVE_NONE, CU_TENSOR_MAP_SWIZZLE_128B, promo,
        CU_TENSOR_MAP_FLOAT_OOB_FILL_NONE);
    return m;
}

}

extern "C" void kernel_launch(void* const* d_in, const int* in_sizes, int n_in, void* d_out, int out_size) {
    (void)in_sizes; (void)n_in; (void)out_size;
    void* fn = nullptr; cudaDriverEntryPointQueryResult qr;
    cudaGetDriverEntryPoint("cuTensorMapEncodeTiled", &fn, cudaEnableDefault, &qr);
    EncodeFn enc = (EncodeFn)fn;
    void* hs = nullptr;
    cudaGetSymbolAddress(&hs, g_scratch);
    int dev = 0, sms = 0;
    cudaGetDevice(&dev);
    cudaDeviceGetAttribute(&sms, cudaDevAttrMultiProcessorCount, dev);
    const CUtensorMapL2promotion P256 = CU_TENSOR_MAP_L2_PROMOTION_L2_256B, P128 = CU_TENSOR_MAP_L2_PROMOTION_L2_128B, P0 = CU_TENSOR_MAP_L2_PROMOTION_NONE;
    CUtensorMap tmW = make_map4(enc, d_in[1], 3, 1024, 32, P256);
    CUtensorMap tmWo = make_map4(enc, d_in[3], 1, 1024, 64, P256);
    CUtensorMap tmO = make_map4(enc, d_out, 1, 2048, 16, P0);
    CUtensorMap tmPhi = make_map(enc, d_in[2], 32, 1024, 32, 128, CU_TENSOR_MAP_SWIZZLE_64B, P128);
    CUtensorMap tmG = make_map(enc, d_in[6], 3584, 1024, 32, 128, CU_TENSOR_MAP_SWIZZLE_64B, P0);
    CUtensorMap tmU = make_map(enc, d_in[7], 3584, 1024, 32, 128, CU_TENSOR_MAP_SWIZZLE_64B, P0);
    CUtensorMap tmD = make_map(enc, d_in[8], 1024, 3584, 64, 32, CU_TENSOR_MAP_SWIZZLE_128B, P128);
    CUtensorMap tmX = make_map(enc, d_in[0], 1024, 2048, 64, 128, CU_TENSOR_MAP_SWIZZLE_128B, P128);
    CUtensorMap tmM = make_map(enc, d_in[10], 6144, 1024, 64, 256, CU_TENSOR_MAP_SWIZZLE_128B, MPROMO);
    Ptrs p;
    p.x = (const bf16*)d_in[0]; p.c = (const bf16*)d_in[9]; p.wmod = (const bf16*)d_in[10]; p.wr = (const bf16*)d_in[5];
    p.wg = (const bf16*)d_in[6]; p.wu = (const bf16*)d_in[7]; p.wd = (const bf16*)d_in[8]; p.out = (bf16*)d_out; p.s = (Scratch*)hs;
    p.wqkv = (const bf16*)d_in[1]; p.wo = (const bf16*)d_in[3];
    p.by_sm = sms == 132;
    for (int sm = 0; sm < 132; sm++) {
        const int tp = sm >> 1, u = tp - 32;
        const int gp = (GPERM >> (4 * (tp < 32 ? tp & 7 : tp < 60 ? 1 + u % 7 : 0))) & 7, sl = 2 * (tp < 32 ? tp >> 3 : tp < 60 ? 4 + u / 7 : tp - 58) + (sm & 1);
        const int b = (tp >> 1) == 30 ? sm + 8 : ((gp >> 1) * 4 + (sl & 3)) * 8 + (gp & 1) * 4 + (sl >> 2);
        const int f = FMODE == 0 ? (b < 112 ? b : 255) : FMODE == 1 ? (sl < 14 && b < 128 ? gp * 14 + sl : 255) : (sm < 112 ? sm : 255);
        p.role[sm] = (uint16_t)(b | f << 8);
    }
    cudaFuncSetAttribute(fused_kernel, cudaFuncAttributeMaxDynamicSharedMemorySize, SMEM_BYTES);
    fused_kernel<<<132, NTHREADS, SMEM_BYTES, cudaStreamPerThread>>>(p, tmM, tmX, tmW, tmWo, tmPhi, tmG, tmU, tmD, tmO);
}
```

```cpp
#include <cuda_runtime.h>
#include <cuda.h>
#include <cuda_bf16.h>
#include <stdint.h>

namespace {

typedef __nv_bfloat16 bf16;

constexpr int NTHREADS = 512;
constexpr int POLL_MAX = 400000;

constexpr uint32_t OFF_R0   = 0;
constexpr uint32_t OFF_A    = 65536;
constexpr uint32_t OFF_B    = 114688;
constexpr uint32_t OFF_V    = 65536;
constexpr uint32_t OFF_PHI  = 98304;
constexpr uint32_t OFF_F2   = 65536;
constexpr uint32_t OFF_DB   = 131072;
constexpr uint32_t OFF_KL   = 196608;
constexpr uint32_t OFF_WPHI = 214016;
constexpr uint32_t OFF_KVT  = OFF_WPHI;
constexpr uint32_t OFF_Z    = 222208;
constexpr uint32_t OFF_TAB  = OFF_Z;
constexpr uint32_t OFF_ONES = 226304;
constexpr uint32_t OFF_BAR  = 227328;
constexpr uint32_t OFF_CST  = OFF_BAR + 640;
constexpr uint32_t OFF_T1   = OFF_ONES;
constexpr uint32_t OFF_T2   = OFF_CST + 64;
constexpr uint32_t OFF_T3   = OFF_T2 + 512;
constexpr uint32_t OFF_KEY  = OFF_T3 + 256;
constexpr uint32_t OFF_ST2  = OFF_KEY + 512;
constexpr uint32_t OFF_ZS   = OFF_ST2;
constexpr uint32_t SMEM_BYTES = 232448;
constexpr uint32_t OFF_X1   = OFF_KL;
constexpr uint32_t OFF_OUT  = OFF_R0 + 32768;
constexpr uint32_t OFF_HSEL = OFF_WPHI;
constexpr uint32_t OFF_RED  = OFF_WPHI + 4096;
constexpr uint32_t OFF_RED2 = OFF_RED + 2048;
static_assert(OFF_ST2 + 2048 <= SMEM_BYTES, "layout");

enum {
    B_O1 = 0, B_UF = 1, B_UD = 2, B_WPHI = 3, B_FB = 4  , B_OST = 8, B_GF = 9, B_WD = 10, B_KVL = 11  , B_KZ = 13, B_LMF = 14, B_SEL = 15, B_XP = 16  , B_TAG = 24,
    B_FA = 25  , B_FD = 30  , B_CAND = 34,
    B_PE = 35  , B_KST = 37  , B_KVT = 41  , B_LMD = 43, B_PAR = 44,
    B_EA = 45  , B_EB = 48  , B_ED = 52  , B_PF = 56  , B_OWN = 60  , B_QE = 62, B_STP = 63, B_KEYS = 64, B_SWP = 65, B_STS = 66
};

struct Scratch {
    uint4 os[16 * 16 * 1024];
    uint4 kvacc[8 * 4 * 528];
    uint4 flk[3 * 128 * 2];
    uint4 llstat[2048];
    uint4 llm1[16 * 64];
    uint4 flo[16 * 16 * 2];
    uint4 llmod2[2 * 256];
    uint4 llg[2 * 4 * 256];
    uint4 llln2[16 * 8 * 128];
    uint4 llcand[16 * 2];
    uint4 llrowh[32 * 256];
    uint4 llrowx[32 * 256];
    uint4 lly[128 * 512];
    unsigned done[4];
};
__device__ __align__(1024) Scratch g_scratch;
#define GT(i) do {} while (0)
#define TS(i) do {} while (0)
#define TR(i) do {} while (0)

__device__ __forceinline__ uint32_t smem_u32(const void* p) { return (uint32_t)__cvta_generic_to_shared(p); }
__device__ __forceinline__ uint32_t clk32() { uint32_t c; asm volatile("mov.u32 %0, %%clock;" : "=r"(c) :: "memory"); return c; }
__device__ __forceinline__ void spin_until(uint32_t t) { while ((int)(clk32() - t) < 0) {} }
__device__ __forceinline__ void sleep_until(uint32_t t) { while ((int)(clk32() - t) < 0) __nanosleep(40); }
__device__ __forceinline__ void mbar_init_fence() { asm volatile("fence.mbarrier_init.release.cluster;" ::: "memory"); }
__device__ __forceinline__ void mbar_wait(uint32_t bar, uint32_t parity) {
    asm volatile("{\n.reg .pred P1;\nLAB_WAIT:\nmbarrier.try_wait.parity.shared::cta.b64 P1, [%0], %1;\n@!P1 bra LAB_WAIT;\n}" :: "r"(bar), "r"(parity) : "memory");
}
__device__ __forceinline__ uint64_t policy_evict_first() { uint64_t p; asm("createpolicy.fractional.L2::evict_first.b64 %0, 1.0;" : "=l"(p)); return p; }
#define ELECT "{\n.reg .pred e;\nelect.sync _|e, 0xffffffff;\n@e "
__device__ __forceinline__ void e_arrive(uint32_t bar) { asm volatile(ELECT "mbarrier.arrive.shared::cta.b64 _, [%0];\n}" :: "r"(bar) : "memory"); }
__device__ __forceinline__ void e_arrive_tx(uint32_t bar, uint32_t bytes) { asm volatile(ELECT "mbarrier.arrive.expect_tx.shared::cta.b64 _, [%0], %1;\n}" :: "r"(bar), "r"(bytes) : "memory"); }
__device__ __forceinline__ void e_init(uint32_t bar, uint32_t cnt) { asm volatile(ELECT "mbarrier.init.shared::cta.b64 [%0], %1;\n}" :: "r"(bar), "r"(cnt) : "memory"); }
__device__ __forceinline__ void tma_load_ef(uint32_t dst, const CUtensorMap* tm, int c0, int c1, uint32_t bar) {
    asm volatile(ELECT "cp.async.bulk.tensor.2d.shared::cluster.global.mbarrier::complete_tx::bytes.L2::cache_hint [%0], [%1, {%3, %4}], [%2], %5;\n}"
        :: "r"(dst), "l"(tm), "r"(bar), "r"(c0), "r"(c1), "l"(policy_evict_first()) : "memory");
}
__device__ __forceinline__ void tma_load(uint32_t dst, const CUtensorMap* tm, int c0, int c1, uint32_t bar) {
    asm volatile(ELECT "cp.async.bulk.tensor.2d.shared::cluster.global.mbarrier::complete_tx::bytes [%0], [%1, {%3, %4}], [%2];\n}"
        :: "r"(dst), "l"(tm), "r"(bar), "r"(c0), "r"(c1) : "memory");
}
__device__ __forceinline__ void tma_load4(uint32_t dst, const CUtensorMap* tm, int row, int blk, uint32_t bar) {
    asm volatile(ELECT "cp.async.bulk.tensor.4d.shared::cluster.global.mbarrier::complete_tx::bytes [%0], [%1, {0, %3, %4, 0}], [%2];\n}"
        :: "r"(dst), "l"(tm), "r"(bar), "r"(row), "r"(blk) : "memory");
}
__device__ __forceinline__ void tma_store4(const CUtensorMap* tm, int row, int blk, uint32_t src) {
    asm volatile(ELECT "cp.async.bulk.tensor.4d.global.shared::cta.bulk_group [%0, {0, %2, %3, 0}], [%1];\n}" :: "l"(tm), "r"(src), "r"(row), "r"(blk) : "memory");
}
__device__ __forceinline__ void bulk_load(uint32_t dst, const void* src, uint32_t bytes, uint32_t bar) {
    asm volatile(ELECT "cp.async.bulk.shared::cluster.global.mbarrier::complete_tx::bytes [%0], [%1], %2, [%3];\n}" :: "r"(dst), "l"(src), "r"(bytes), "r"(bar) : "memory");
}
__device__ __forceinline__ void bulk_store(void* dst, uint32_t src, uint32_t bytes) {
    asm volatile(ELECT "cp.async.bulk.global.shared::cta.bulk_group [%0], [%1], %2;\n}" :: "l"(dst), "r"(src), "r"(bytes) : "memory");
}
__device__ __forceinline__ void bulk_reduce(void* dst, uint32_t src, uint32_t bytes) {
    asm volatile(ELECT "cp.reduce.async.bulk.global.shared::cta.bulk_group.add.f32 [%0], [%1], %2;\n}" :: "l"(dst), "r"(src), "r"(bytes) : "memory");
}
__device__ __forceinline__ void tma_prefetch(const CUtensorMap* tm, int c0, int c1) {
    asm volatile(ELECT "cp.async.bulk.prefetch.tensor.2d.L2.global [%0, {%1, %2}];\n}" :: "l"(tm), "r"(c0), "r"(c1) : "memory");
}
__device__ __forceinline__ void l2_prefetch(const void* p, uint32_t bytes) {
    asm volatile(ELECT "cp.async.bulk.prefetch.L2.global [%0], %1;\n}" :: "l"(p), "r"(bytes) : "memory");
}
__device__ __forceinline__ void bulk_wait_read() { asm volatile("cp.async.bulk.commit_group;\ncp.async.bulk.wait_group.read 0;" ::: "memory"); }
__device__ __forceinline__ void bulk_wait() { asm volatile("cp.async.bulk.commit_group;\ncp.async.bulk.wait_group 0;" ::: "memory"); }
__device__ __forceinline__ void tmap_prefetch(const CUtensorMap* tm) { asm volatile("prefetch.tensormap [%0];" :: "l"(tm) : "memory"); }
__device__ __forceinline__ void wg_fence() { asm volatile("wgmma.fence.sync.aligned;" ::: "memory"); }
__device__ __forceinline__ void wg_commit() { asm volatile("wgmma.commit_group.sync.aligned;" ::: "memory"); }
template<int N> __device__ __forceinline__ void wg_wait() { asm volatile("wgmma.wait_group.sync.aligned %0;" :: "n"(N) : "memory"); }
template<int N> __device__ __forceinline__ void acc_fence(float (&d)[N]) {
    #pragma unroll
    for (int i = 0; i < N; i++) asm volatile("" : "+f"(d[i]) :: "memory");
}
__device__ __forceinline__ uint32_t desc_lo(uint32_t addr, uint32_t lbo) { return (addr >> 4) | ((lbo >> 4) << 16); }
constexpr uint32_t H128 = 0x40000040u;
constexpr uint32_t H64 = 0x80000020u;
__device__ __forceinline__ void fence_async_smem() { asm volatile("fence.proxy.async.shared::cta;" ::: "memory"); }
__device__ __forceinline__ void bar_sync(int id, int n) { asm volatile("bar.sync %0, %1;" :: "r"(id), "r"(n) : "memory"); }
template<int R> __device__ __forceinline__ void reg_inc() { asm volatile("setmaxnreg.inc.sync.aligned.u32 %0;" :: "n"(R)); }
template<int R> __device__ __forceinline__ void reg_dec() { asm volatile("setmaxnreg.dec.sync.aligned.u32 %0;" :: "n"(R)); }

__device__ __forceinline__ void stsm4(uint32_t addr, uint32_t r0, uint32_t r1, uint32_t r2, uint32_t r3) {
    asm volatile("stmatrix.sync.aligned.m8n8.x4.shared.b16 [%0], {%1,%2,%3,%4};" :: "r"(addr), "r"(r0), "r"(r1), "r"(r2), "r"(r3) : "memory");
}
__device__ __forceinline__ void ldsm4(uint32_t* r, uint32_t addr) {
    asm volatile("ldmatrix.sync.aligned.m8n8.x4.shared.b16 {%0,%1,%2,%3}, [%4];" : "=r"(r[0]), "=r"(r[1]), "=r"(r[2]), "=r"(r[3]) : "r"(addr) : "memory");
}
__device__ __forceinline__ void ldsm4t(uint32_t* r, uint32_t addr) {
    asm volatile("ldmatrix.sync.aligned.m8n8.x4.trans.shared.b16 {%0,%1,%2,%3}, [%4];" : "=r"(r[0]), "=r"(r[1]), "=r"(r[2]), "=r"(r[3]) : "r"(addr) : "memory");
}
__device__ __forceinline__ void mma16816(float (&d)[4], uint32_t a0, uint32_t a1, uint32_t a2, uint32_t a3, uint32_t b0, uint32_t b1) {
    asm volatile("mma.sync.aligned.m16n8k16.row.col.f32.bf16.bf16.f32 {%0,%1,%2,%3}, {%4,%5,%6,%7}, {%8,%9}, {%0,%1,%2,%3};"
        : "+f"(d[0]), "+f"(d[1]), "+f"(d[2]), "+f"(d[3]) : "r"(a0), "r"(a1), "r"(a2), "r"(a3), "r"(b0), "r"(b1));
}
__device__ __forceinline__ uint32_t awake_zero() {
    uint32_t r;
    asm volatile("{\n.reg .f32 d<4>;\nmma.sync.aligned.m16n8k8.row.col.f32.bf16.bf16.f32 {d0,d1,d2,d3}, {%1,%1}, {%1}, {%2,%2,%2,%2};\nmov.b32 %0, d0;\n}" : "=r"(r) : "r"(0), "f"(0.f));
    return r;
}
__device__ __forceinline__ void mbar_wait_awake(uint32_t bar, uint32_t parity) {
    #pragma unroll 1
    for (int it = 0; it < POLL_MAX; it++) {
        uint32_t ok;
        asm volatile("{\n.reg .pred p;\nmbarrier.try_wait.parity.shared::cta.b64 p, [%1], %2;\nselp.u32 %0, 0, 1, p;\n}" : "=r"(ok) : "r"(bar), "r"(parity) : "memory");
        if (__all_sync(0xffffffffu, ok == 0)) break;
        it += awake_zero();
    }
}
__device__ __forceinline__ uint4 lds128(uint32_t a) { uint4 v; asm volatile("ld.shared.v4.b32 {%0,%1,%2,%3}, [%4];" : "=r"(v.x), "=r"(v.y), "=r"(v.z), "=r"(v.w) : "r"(a) : "memory"); return v; }
__device__ __forceinline__ uint32_t lds32(uint32_t a) { uint32_t v; asm volatile("ld.shared.b32 %0, [%1];" : "=r"(v) : "r"(a) : "memory"); return v; }
__device__ __forceinline__ uint2 lds64(uint32_t a) { uint2 v; asm volatile("ld.shared.v2.b32 {%0,%1}, [%2];" : "=r"(v.x), "=r"(v.y) : "r"(a) : "memory"); return v; }
__device__ __forceinline__ float ldsf(uint32_t a) { float v; asm volatile("ld.shared.f32 %0, [%1];" : "=f"(v) : "r"(a) : "memory"); return v; }
__device__ __forceinline__ void sts128(uint32_t a, uint4 v) { asm volatile("st.shared.v4.b32 [%0], {%1,%2,%3,%4};" :: "r"(a), "r"(v.x), "r"(v.y), "r"(v.z), "r"(v.w) : "memory"); }
__device__ __forceinline__ void sts64(uint32_t a, uint32_t x, uint32_t y) { asm volatile("st.shared.v2.b32 [%0], {%1,%2};" :: "r"(a), "r"(x), "r"(y) : "memory"); }
__device__ __forceinline__ void sts32(uint32_t a, uint32_t x) { asm volatile("st.shared.b32 [%0], %1;" :: "r"(a), "r"(x) : "memory"); }
__device__ __forceinline__ void stsf(uint32_t a, float x) { asm volatile("st.shared.f32 [%0], %1;" :: "r"(a), "f"(x) : "memory"); }
__device__ __forceinline__ float u2f(uint32_t v) { return __uint_as_float(v); }
__device__ __forceinline__ uint32_t f2u(float v) { return __float_as_uint(v); }

__device__ __forceinline__ uint32_t ldg32(const void* p) { uint32_t v; asm volatile("ld.global.nc.b32 %0, [%1];" : "=r"(v) : "l"(p)); return v; }
__device__ __forceinline__ void stg128(void* p, uint4 v) { asm volatile("st.global.v4.b32 [%0], {%1,%2,%3,%4};" :: "l"(p), "r"(v.x), "r"(v.y), "r"(v.z), "r"(v.w) : "memory"); }
__device__ __forceinline__ void stg_zero(void* p) { stg128(p, make_uint4(0, 0, 0, 0)); }
__device__ __forceinline__ void fence_gpu() { asm volatile("fence.acq_rel.gpu;" ::: "memory"); }
__device__ __forceinline__ void st_ll(uint4* p, uint32_t x, uint32_t y, uint32_t z, uint32_t w) {
    asm volatile("st.relaxed.gpu.global.v4.b32 [%0], {%1,%2,%3,%4};" :: "l"(p), "r"(x), "r"(y), "r"(z), "r"(w) : "memory");
}
__device__ __forceinline__ uint4 ld_ll(const uint4* p) {
    uint4 v;
    asm volatile("ld.relaxed.gpu.global.v4.b32 {%0,%1,%2,%3}, [%4];" : "=r"(v.x), "=r"(v.y), "=r"(v.z), "=r"(v.w) : "l"(p) : "memory");
    return v;
}
template<uint32_t LUT> __device__ __forceinline__ uint32_t lop3(uint32_t a, uint32_t b, uint32_t c) { uint32_t d; asm("lop3.b32 %0, %1, %2, %3, %4;" : "=r"(d) : "r"(a), "r"(b), "r"(c), "n"(LUT)); return d; }
__device__ __forceinline__ uint32_t tag_bad(uint32_t bad, uint32_t w, uint32_t tag) { return lop3<0xF6>(bad, w, tag); }
__device__ __forceinline__ void st_ll4(uint4* p, float a, float b, float c, float d, uint32_t tag) { st_ll(p, f2u(a), f2u(b), f2u(c), lop3<0xD8>(f2u(d), tag, 3u)); }
__device__ __forceinline__ unsigned ld_rlx(const void* p) { unsigned v; asm volatile("ld.relaxed.gpu.global.u32 %0, [%1];" : "=r"(v) : "l"(p) : "memory"); return v; }
__device__ __forceinline__ void st_flag(uint4* p, uint32_t v, int lane) { if (lane < 2) st_ll(p + lane, v, v, v, v); }
__device__ __forceinline__ void poll_flags(const uint4* f, uint32_t tag) {
    unsigned v0 = ld_rlx(f), v1;
    spin_until(clk32() + 140);
    #pragma unroll 1
    for (int it = 0; it < POLL_MAX; it++) {
        v1 = ld_rlx(f);
        if (__all_sync(0xffffffffu, v0 == tag)) break;
        v0 = ld_rlx(f);
        if (__all_sync(0xffffffffu, v1 == tag)) break;
    }
}
template<int Z> __device__ __forceinline__ uint32_t ll_bad(uint32_t bad, const uint4& v, uint32_t tag) {
    bad = tag_bad(bad, v.w, tag);
    return Z && lop3<0x80>(v.x, v.y, v.z) == ~0u ? 1u : bad;
}
template<int N, int Z, uint32_t M = ~0u, int AW = 0> __device__ __forceinline__ void poll_words(uint4 (&v)[N], const uint4* p, int stride, uint32_t tag) {
    #pragma unroll 1
    for (int it = 0; it < POLL_MAX; it++) {
        uint32_t bad = 0;
        #pragma unroll
        for (int i = 0; i < N; i++) v[i] = ld_ll(p + i * stride);
        #pragma unroll
        for (int i = 0; i < N; i++) bad = ll_bad<Z>(bad, v[i], tag);
        if (__all_sync(0xffffffffu, !(bad & M))) break;
        if (AW) it += awake_zero();
    }
}
constexpr uint32_t ONE2 = 0x3F803F80u;
__device__ __forceinline__ uint32_t pack2(float lo, float hi) { uint32_t d; asm("cvt.rn.bf16x2.f32 %0, %1, %2;" : "=r"(d) : "f"(hi), "f"(lo)); return d; }
__device__ __forceinline__ float bf_lo(uint32_t v) { return u2f(v << 16); }
__device__ __forceinline__ float bf_hi(uint32_t v) { return u2f(v & 0xffff0000u); }
__device__ __forceinline__ float rbf(float x) { return bf_lo(pack2(x, 0.f)); }
__device__ __forceinline__ uint32_t hsub2(uint32_t a, uint32_t b) { uint32_t d; asm("sub.rn.bf16x2 %0, %1, %2;" : "=r"(d) : "r"(a), "r"(b)); return d; }
__device__ __forceinline__ uint32_t hadd2(uint32_t a, uint32_t b) { uint32_t d; asm("add.rn.bf16x2 %0, %1, %2;" : "=r"(d) : "r"(a), "r"(b)); return d; }
__device__ __forceinline__ uint32_t hmul2(uint32_t a, uint32_t b) { uint32_t d; asm("mul.rn.bf16x2 %0, %1, %2;" : "=r"(d) : "r"(a), "r"(b)); return d; }
__device__ __forceinline__ uint32_t hfma2(uint32_t a, uint32_t b, uint32_t c) { uint32_t d; asm("fma.rn.bf16x2 %0, %1, %2, %3;" : "=r"(d) : "r"(a), "r"(b), "r"(c)); return d; }
__device__ __forceinline__ uint32_t hmax2(uint32_t a, uint32_t b) { uint32_t d; asm("max.bf16x2 %0, %1, %2;" : "=r"(d) : "r"(a), "r"(b)); return d; }
__device__ __forceinline__ uint32_t hmin2(uint32_t a, uint32_t b) { uint32_t d; asm("min.bf16x2 %0, %1, %2;" : "=r"(d) : "r"(a), "r"(b)); return d; }
__device__ __forceinline__ float ex2(float x) { float y; asm("ex2.approx.ftz.f32 %0, %1;" : "=f"(y) : "f"(x)); return y; }
__device__ __forceinline__ float rcp(float x) { float y; asm("rcp.approx.ftz.f32 %0, %1;" : "=f"(y) : "f"(x)); return y; }
__device__ __forceinline__ float shfl_x(float v, int m) { return __shfl_xor_sync(0xffffffffu, v, m); }
__device__ __forceinline__ uint32_t hdiv2(uint32_t d, uint32_t rh, uint32_t rl) { return hfma2(d, rh, hmul2(d, rl)); }
__device__ __forceinline__ void split_rcp(float r, uint32_t& rh, uint32_t& rl) { rh = pack2(r, r); const float l = r - bf_lo(rh); rl = pack2(l, l); }
__device__ __forceinline__ uint32_t lnmod(uint32_t x, uint32_t m, uint32_t rh, uint32_t rl, uint32_t a, uint32_t s) { return hadd2(hmul2(hdiv2(hsub2(x, m), rh, rl), a), s); }
__device__ __forceinline__ void ln_final(float s1, float s2, uint32_t& m2, float& rinv) {
    const float mean = s1 * (1.0f / 1024.0f), var = fmaf(-mean, mean, s2 * (1.0f / 1024.0f));
    m2 = pack2(mean, mean);
    float sd;
    asm("sqrt.approx.ftz.f32 %0, %1;" : "=f"(sd) : "f"(rbf(rbf(fmaxf(var, 0.f)) + 1e-5f)));
    rinv = rcp(rbf(sd));
}
__device__ __forceinline__ float sigmoid_f(float x) { return rcp(1.0f + ex2(-1.4426950408889634f * x)); }
__device__ __forceinline__ uint32_t silu2(uint32_t v) { return pack2(bf_lo(v) * sigmoid_f(bf_lo(v)), bf_hi(v) * sigmoid_f(bf_hi(v))); }
__device__ __forceinline__ uint32_t f2key(float f) { uint32_t u = f2u(f); return (u & 0x80000000u) ? ~u : (u | 0x80000000u); }
__device__ __forceinline__ float key2f(uint32_t k) { return u2f((k & 0x80000000u) ? k ^ 0x80000000u : ~k); }
template<int N> __device__ __forceinline__ void top2(uint32_t (&k)[N], uint32_t& b0, uint32_t& b1) {
    uint32_t m = k[0];
    #pragma unroll
    for (int i = 1; i < N; i++) m = max(m, k[i]);
    b0 = __reduce_max_sync(0xffffffffu, m);
    m = 0;
    #pragma unroll
    for (int i = 0; i < N; i++) m = max(m, k[i] == b0 ? 0u : k[i]);
    b1 = __reduce_max_sync(0xffffffffu, m);
}
template<class T> __device__ __forceinline__ T sel4(int c, T a0, T a1, T a2, T a3) { return (c & 2) ? ((c & 1) ? a3 : a2) : ((c & 1) ? a1 : a0); }

__device__ __forceinline__ void fm_max(const float (&a)[16], uint32_t* p, uint32_t* mm) {
    #pragma unroll
    for (int i = 0; i < 8; i++) p[i] = pack2(a[2 * i], a[2 * i + 1]);
    #pragma unroll
    for (int h = 0; h < 2; h++) {
        const uint32_t mx = hmax2(hmax2(p[h], p[2 + h]), hmax2(p[4 + h], p[6 + h]));
        const uint32_t mn = hmin2(hmin2(p[h], p[2 + h]), hmin2(p[4 + h], p[6 + h])) ^ 0x80008000u;
        mm[h] = hmax2(__byte_perm(mx, mn, 0x5410), __byte_perm(mx, mn, 0x7632));
    }
    #pragma unroll
    for (int d = 1; d <= 2; d++) { mm[0] = hmax2(mm[0], __shfl_xor_sync(0xffffffffu, mm[0], d)); mm[1] = hmax2(mm[1], __shfl_xor_sync(0xffffffffu, mm[1], d)); }
}
__device__ __forceinline__ void fm_args(const uint32_t* p, const uint32_t* mm, float (&e)[32]) {
    const float L = 1.4426950408889634f;
    #pragma unroll
    for (int h = 0; h < 2; h++) {
        const float cp = -bf_lo(mm[h]) * L, cn = -bf_hi(mm[h]) * L;
        #pragma unroll
        for (int j = 0; j < 4; j++) {
            const float f0 = bf_lo(p[2 * j + h]), f1 = bf_hi(p[2 * j + h]);
            e[8 * h + 2 * j] = fmaf(f0, L, cp); e[8 * h + 2 * j + 1] = fmaf(f1, L, cp);
            e[16 + 8 * h + 2 * j] = fmaf(f0, -L, cn); e[16 + 8 * h + 2 * j + 1] = fmaf(f1, -L, cn);
        }
    }
}
template<int LO, int HI> __device__ __forceinline__ void fm_exp(float (&e)[32]) {
    #pragma unroll
    for (int i = LO; i < HI; i++) e[i] = ex2(e[i]);
}
__device__ __forceinline__ void fm_norm(const float (&e)[32], uint32_t* ph) {
    float s[4];
    #pragma unroll
    for (int k = 0; k < 4; k++) s[k] = ((e[8 * k] + e[8 * k + 1]) + (e[8 * k + 2] + e[8 * k + 3])) + ((e[8 * k + 4] + e[8 * k + 5]) + (e[8 * k + 6] + e[8 * k + 7]));
    #pragma unroll
    for (int k = 0; k < 4; k++) s[k] += shfl_x(s[k], 1);
    #pragma unroll
    for (int k = 0; k < 4; k++) s[k] = rcp(s[k] + shfl_x(s[k], 2));
    #pragma unroll
    for (int k = 0; k < 4; k++)
        #pragma unroll
        for (int j = 0; j < 4; j++) ph[8 * (k >> 1) + 2 * j + (k & 1)] = pack2(e[8 * k + 2 * j] * s[k], e[8 * k + 2 * j + 1] * s[k]);
}
template<class T> __device__ __forceinline__ T* pin_ptr(T* p) { asm volatile("" : "+l"(p) :: "memory"); return p; }
template<int N> __device__ __forceinline__ void pin(uint32_t* d) {
    #pragma unroll
    for (int i = 0; i < N; i++) asm volatile("" : "+r"(d[i]) :: "memory");
}

template<uint32_t BO, uint32_t BH> __device__ __forceinline__ void mma192_rs(float (&d)[96], const uint32_t* a, uint32_t blo) {
  asm volatile("{\n.reg .pred p;\n.reg .b32 ta, tb;\n.reg .b64 da, db;\nadd.u32 tb, %100, %101;\nmov.b64 db, {tb, %102};\nsetp.ne.b32 p, 1, 0;\n"
    "wgmma.mma_async.sync.aligned.m64n192k16.f32.bf16.bf16 {%0, %1, %2, %3, %4, %5, %6, %7, %8, %9, %10, %11, %12, %13, %14, %15, %16, %17, %18, %19, %20, %21, %22, %23, %24, %25, %26, %27, %28, %29, %30, %31, %32, %33, %34, %35, %36, %37, %38, %39, %40, %41, %42, %43, %44, %45, %46, %47, %48, %49, %50, %51, %52, %53, %54, %55, %56, %57, %58, %59, %60, %61, %62, %63, %64, %65, %66, %67, %68, %69, %70, %71, %72, %73, %74, %75, %76, %77, %78, %79, %80, %81, %82, %83, %84, %85, %86, %87, %88, %89, %90, %91, %92, %93, %94, %95}, {%96,%97,%98,%99}, db, p, 1, 1, 1;\n}\n"
    : "+f"(d[0]), "+f"(d[1]), "+f"(d[2]), "+f"(d[3]), "+f"(d[4]), "+f"(d[5]), "+f"(d[6]), "+f"(d[7]), "+f"(d[8]), "+f"(d[9]), "+f"(d[10]), "+f"(d[11]), "+f"(d[12]), "+f"(d[13]), "+f"(d[14]), "+f"(d[15]), "+f"(d[16]), "+f"(d[17]), "+f"(d[18]), "+f"(d[19]), "+f"(d[20]), "+f"(d[21]), "+f"(d[22]), "+f"(d[23]), "+f"(d[24]), "+f"(d[25]), "+f"(d[26]), "+f"(d[27]), "+f"(d[28]), "+f"(d[29]), "+f"(d[30]), "+f"(d[31]), "+f"(d[32]), "+f"(d[33]), "+f"(d[34]), "+f"(d[35]), "+f"(d[36]), "+f"(d[37]), "+f"(d[38]), "+f"(d[39]), "+f"(d[40]), "+f"(d[41]), "+f"(d[42]), "+f"(d[43]), "+f"(d[44]), "+f"(d[45]), "+f"(d[46]), "+f"(d[47]), "+f"(d[48]), "+f"(d[49]), "+f"(d[50]), "+f"(d[51]), "+f"(d[52]), "+f"(d[53]), "+f"(d[54]), "+f"(d[55]), "+f"(d[56]), "+f"(d[57]), "+f"(d[58]), "+f"(d[59]), "+f"(d[60]), "+f"(d[61]), "+f"(d[62]), "+f"(d[63]), "+f"(d[64]), "+f"(d[65]), "+f"(d[66]), "+f"(d[67]), "+f"(d[68]), "+f"(d[69]), "+f"(d[70]), "+f"(d[71]), "+f"(d[72]), "+f"(d[73]), "+f"(d[74]), "+f"(d[75]), "+f"(d[76]), "+f"(d[77]), "+f"(d[78]), "+f"(d[79]), "+f"(d[80]), "+f"(d[81]), "+f"(d[82]), "+f"(d[83]), "+f"(d[84]), "+f"(d[85]), "+f"(d[86]), "+f"(d[87]), "+f"(d[88]), "+f"(d[89]), "+f"(d[90]), "+f"(d[91]), "+f"(d[92]), "+f"(d[93]), "+f"(d[94]), "+f"(d[95])
    : "r"(a[0]), "r"(a[1]), "r"(a[2]), "r"(a[3]), "r"(blo), "n"(BO), "n"(BH));
}
template<uint32_t BO, uint32_t BH> __device__ __forceinline__ void mma192_rsp(float (&d)[96], const uint32_t* a, uint32_t blo, int sc) {
  asm volatile("{\n.reg .pred p;\n.reg .b32 ta, tb;\n.reg .b64 da, db;\nadd.u32 tb, %100, %101;\nmov.b64 db, {tb, %102};\nsetp.ne.b32 p, %103, 0;\n"
    "wgmma.mma_async.sync.aligned.m64n192k16.f32.bf16.bf16 {%0, %1, %2, %3, %4, %5, %6, %7, %8, %9, %10, %11, %12, %13, %14, %15, %16, %17, %18, %19, %20, %21, %22, %23, %24, %25, %26, %27, %28, %29, %30, %31, %32, %33, %34, %35, %36, %37, %38, %39, %40, %41, %42, %43, %44, %45, %46, %47, %48, %49, %50, %51, %52, %53, %54, %55, %56, %57, %58, %59, %60, %61, %62, %63, %64, %65, %66, %67, %68, %69, %70, %71, %72, %73, %74, %75, %76, %77, %78, %79, %80, %81, %82, %83, %84, %85, %86, %87, %88, %89, %90, %91, %92, %93, %94, %95}, {%96,%97,%98,%99}, db, p, 1, 1, 1;\n}\n"
    : "+f"(d[0]), "+f"(d[1]), "+f"(d[2]), "+f"(d[3]), "+f"(d[4]), "+f"(d[5]), "+f"(d[6]), "+f"(d[7]), "+f"(d[8]), "+f"(d[9]), "+f"(d[10]), "+f"(d[11]), "+f"(d[12]), "+f"(d[13]), "+f"(d[14]), "+f"(d[15]), "+f"(d[16]), "+f"(d[17]), "+f"(d[18]), "+f"(d[19]), "+f"(d[20]), "+f"(d[21]), "+f"(d[22]), "+f"(d[23]), "+f"(d[24]), "+f"(d[25]), "+f"(d[26]), "+f"(d[27]), "+f"(d[28]), "+f"(d[29]), "+f"(d[30]), "+f"(d[31]), "+f"(d[32]), "+f"(d[33]), "+f"(d[34]), "+f"(d[35]), "+f"(d[36]), "+f"(d[37]), "+f"(d[38]), "+f"(d[39]), "+f"(d[40]), "+f"(d[41]), "+f"(d[42]), "+f"(d[43]), "+f"(d[44]), "+f"(d[45]), "+f"(d[46]), "+f"(d[47]), "+f"(d[48]), "+f"(d[49]), "+f"(d[50]), "+f"(d[51]), "+f"(d[52]), "+f"(d[53]), "+f"(d[54]), "+f"(d[55]), "+f"(d[56]), "+f"(d[57]), "+f"(d[58]), "+f"(d[59]), "+f"(d[60]), "+f"(d[61]), "+f"(d[62]), "+f"(d[63]), "+f"(d[64]), "+f"(d[65]), "+f"(d[66]), "+f"(d[67]), "+f"(d[68]), "+f"(d[69]), "+f"(d[70]), "+f"(d[71]), "+f"(d[72]), "+f"(d[73]), "+f"(d[74]), "+f"(d[75]), "+f"(d[76]), "+f"(d[77]), "+f"(d[78]), "+f"(d[79]), "+f"(d[80]), "+f"(d[81]), "+f"(d[82]), "+f"(d[83]), "+f"(d[84]), "+f"(d[85]), "+f"(d[86]), "+f"(d[87]), "+f"(d[88]), "+f"(d[89]), "+f"(d[90]), "+f"(d[91]), "+f"(d[92]), "+f"(d[93]), "+f"(d[94]), "+f"(d[95])
    : "r"(a[0]), "r"(a[1]), "r"(a[2]), "r"(a[3]), "r"(blo), "n"(BO), "n"(BH), "r"(sc));
}
template<uint32_t BO, uint32_t BH> __device__ __forceinline__ void mma32_rs(float (&d)[16], const uint32_t* a, uint32_t blo) {
  asm volatile("{\n.reg .pred p;\n.reg .b32 ta, tb;\n.reg .b64 da, db;\nadd.u32 tb, %20, %21;\nmov.b64 db, {tb, %22};\nsetp.ne.b32 p, 1, 0;\n"
    "wgmma.mma_async.sync.aligned.m64n32k16.f32.bf16.bf16 {%0, %1, %2, %3, %4, %5, %6, %7, %8, %9, %10, %11, %12, %13, %14, %15}, {%16,%17,%18,%19}, db, p, 1, 1, 1;\n}\n"
    : "+f"(d[0]), "+f"(d[1]), "+f"(d[2]), "+f"(d[3]), "+f"(d[4]), "+f"(d[5]), "+f"(d[6]), "+f"(d[7]), "+f"(d[8]), "+f"(d[9]), "+f"(d[10]), "+f"(d[11]), "+f"(d[12]), "+f"(d[13]), "+f"(d[14]), "+f"(d[15])
    : "r"(a[0]), "r"(a[1]), "r"(a[2]), "r"(a[3]), "r"(blo), "n"(BO), "n"(BH));
}
template<uint32_t BO, uint32_t BH> __device__ __forceinline__ void mma32_rs0(float (&d)[16], const uint32_t* a, uint32_t blo) {
  asm volatile("{\n.reg .pred p;\n.reg .b32 ta, tb;\n.reg .b64 da, db;\nadd.u32 tb, %20, %21;\nmov.b64 db, {tb, %22};\nsetp.ne.b32 p, 0, 0;\n"
    "wgmma.mma_async.sync.aligned.m64n32k16.f32.bf16.bf16 {%0, %1, %2, %3, %4, %5, %6, %7, %8, %9, %10, %11, %12, %13, %14, %15}, {%16,%17,%18,%19}, db, p, 1, 1, 1;\n}\n"
    : "=f"(d[0]), "=f"(d[1]), "=f"(d[2]), "=f"(d[3]), "=f"(d[4]), "=f"(d[5]), "=f"(d[6]), "=f"(d[7]), "=f"(d[8]), "=f"(d[9]), "=f"(d[10]), "=f"(d[11]), "=f"(d[12]), "=f"(d[13]), "=f"(d[14]), "=f"(d[15])
    : "r"(a[0]), "r"(a[1]), "r"(a[2]), "r"(a[3]), "r"(blo), "n"(BO), "n"(BH));
}
template<uint32_t BO, uint32_t BH> __device__ __forceinline__ void mma40_rs(float (&d)[20], const uint32_t* a, uint32_t blo) {
  asm volatile("{\n.reg .pred p;\n.reg .b32 ta, tb;\n.reg .b64 da, db;\nadd.u32 tb, %24, %25;\nmov.b64 db, {tb, %26};\nsetp.ne.b32 p, 1, 0;\n"
    "wgmma.mma_async.sync.aligned.m64n40k16.f32.bf16.bf16 {%0, %1, %2, %3, %4, %5, %6, %7, %8, %9, %10, %11, %12, %13, %14, %15, %16, %17, %18, %19}, {%20,%21,%22,%23}, db, p, 1, 1, 1;\n}\n"
    : "+f"(d[0]), "+f"(d[1]), "+f"(d[2]), "+f"(d[3]), "+f"(d[4]), "+f"(d[5]), "+f"(d[6]), "+f"(d[7]), "+f"(d[8]), "+f"(d[9]), "+f"(d[10]), "+f"(d[11]), "+f"(d[12]), "+f"(d[13]), "+f"(d[14]), "+f"(d[15]), "+f"(d[16]), "+f"(d[17]), "+f"(d[18]), "+f"(d[19])
    : "r"(a[0]), "r"(a[1]), "r"(a[2]), "r"(a[3]), "r"(blo), "n"(BO), "n"(BH));
}
template<uint32_t BO, uint32_t BH> __device__ __forceinline__ void mma40_rs0(float (&d)[20], const uint32_t* a, uint32_t blo) {
  asm volatile("{\n.reg .pred p;\n.reg .b32 ta, tb;\n.reg .b64 da, db;\nadd.u32 tb, %24, %25;\nmov.b64 db, {tb, %26};\nsetp.ne.b32 p, 0, 0;\n"
    "wgmma.mma_async.sync.aligned.m64n40k16.f32.bf16.bf16 {%0, %1, %2, %3, %4, %5, %6, %7, %8, %9, %10, %11, %12, %13, %14, %15, %16, %17, %18, %19}, {%20,%21,%22,%23}, db, p, 1, 1, 1;\n}\n"
    : "=f"(d[0]), "=f"(d[1]), "=f"(d[2]), "=f"(d[3]), "=f"(d[4]), "=f"(d[5]), "=f"(d[6]), "=f"(d[7]), "=f"(d[8]), "=f"(d[9]), "=f"(d[10]), "=f"(d[11]), "=f"(d[12]), "=f"(d[13]), "=f"(d[14]), "=f"(d[15]), "=f"(d[16]), "=f"(d[17]), "=f"(d[18]), "=f"(d[19])
    : "r"(a[0]), "r"(a[1]), "r"(a[2]), "r"(a[3]), "r"(blo), "n"(BO), "n"(BH));
}
template<uint32_t AO, uint32_t AH, uint32_t BO, uint32_t BH> __device__ __forceinline__ void mma40_tt(float (&d)[20], uint32_t alo, uint32_t blo) {
  asm volatile("{\n.reg .pred p;\n.reg .b32 ta, tb;\n.reg .b64 da, db;\nadd.u32 ta, %20, %21;\nmov.b64 da, {ta, %22};\nadd.u32 tb, %23, %24;\nmov.b64 db, {tb, %25};\nsetp.ne.b32 p, 1, 0;\n"
    "wgmma.mma_async.sync.aligned.m64n40k16.f32.bf16.bf16 {%0, %1, %2, %3, %4, %5, %6, %7, %8, %9, %10, %11, %12, %13, %14, %15, %16, %17, %18, %19}, da, db, p, 1, 1, 1, 1;\n}\n"
    : "+f"(d[0]), "+f"(d[1]), "+f"(d[2]), "+f"(d[3]), "+f"(d[4]), "+f"(d[5]), "+f"(d[6]), "+f"(d[7]), "+f"(d[8]), "+f"(d[9]), "+f"(d[10]), "+f"(d[11]), "+f"(d[12]), "+f"(d[13]), "+f"(d[14]), "+f"(d[15]), "+f"(d[16]), "+f"(d[17]), "+f"(d[18]), "+f"(d[19])
    : "r"(alo), "n"(AO), "n"(AH), "r"(blo), "n"(BO), "n"(BH));
}
template<uint32_t AO, uint32_t AH, uint32_t BO, uint32_t BH> __device__ __forceinline__ void mma40_tt0(float (&d)[20], uint32_t alo, uint32_t blo) {
  asm volatile("{\n.reg .pred p;\n.reg .b32 ta, tb;\n.reg .b64 da, db;\nadd.u32 ta, %20, %21;\nmov.b64 da, {ta, %22};\nadd.u32 tb, %23, %24;\nmov.b64 db, {tb, %25};\nsetp.ne.b32 p, 0, 0;\n"
    "wgmma.mma_async.sync.aligned.m64n40k16.f32.bf16.bf16 {%0, %1, %2, %3, %4, %5, %6, %7, %8, %9, %10, %11, %12, %13, %14, %15, %16, %17, %18, %19}, da, db, p, 1, 1, 1, 1;\n}\n"
    : "=f"(d[0]), "=f"(d[1]), "=f"(d[2]), "=f"(d[3]), "=f"(d[4]), "=f"(d[5]), "=f"(d[6]), "=f"(d[7]), "=f"(d[8]), "=f"(d[9]), "=f"(d[10]), "=f"(d[11]), "=f"(d[12]), "=f"(d[13]), "=f"(d[14]), "=f"(d[15]), "=f"(d[16]), "=f"(d[17]), "=f"(d[18]), "=f"(d[19])
    : "r"(alo), "n"(AO), "n"(AH), "r"(blo), "n"(BO), "n"(BH));
}
template<uint32_t AO, uint32_t AH, uint32_t BO, uint32_t BH> __device__ __forceinline__ void mma8_tn(float (&d)[4], uint32_t alo, uint32_t blo) {
  asm volatile("{\n.reg .pred p;\n.reg .b32 ta, tb;\n.reg .b64 da, db;\nadd.u32 ta, %4, %5;\nmov.b64 da, {ta, %6};\nadd.u32 tb, %7, %8;\nmov.b64 db, {tb, %9};\nsetp.ne.b32 p, 1, 0;\n"
    "wgmma.mma_async.sync.aligned.m64n8k16.f32.bf16.bf16 {%0, %1, %2, %3}, da, db, p, 1, 1, 1, 0;\n}\n"
    : "+f"(d[0]), "+f"(d[1]), "+f"(d[2]), "+f"(d[3])
    : "r"(alo), "n"(AO), "n"(AH), "r"(blo), "n"(BO), "n"(BH));
}
template<uint32_t AO, uint32_t AH, uint32_t BO, uint32_t BH> __device__ __forceinline__ void mma8_tn0(float (&d)[4], uint32_t alo, uint32_t blo) {
  asm volatile("{\n.reg .pred p;\n.reg .b32 ta, tb;\n.reg .b64 da, db;\nadd.u32 ta, %4, %5;\nmov.b64 da, {ta, %6};\nadd.u32 tb, %7, %8;\nmov.b64 db, {tb, %9};\nsetp.ne.b32 p, 0, 0;\n"
    "wgmma.mma_async.sync.aligned.m64n8k16.f32.bf16.bf16 {%0, %1, %2, %3}, da, db, p, 1, 1, 1, 0;\n}\n"
    : "=f"(d[0]), "=f"(d[1]), "=f"(d[2]), "=f"(d[3])
    : "r"(alo), "n"(AO), "n"(AH), "r"(blo), "n"(BO), "n"(BH));
}
template<uint32_t AO, uint32_t AH, uint32_t BO, uint32_t BH> __device__ __forceinline__ void mma128_ss(float (&d)[64], uint32_t alo, uint32_t blo) {
  asm volatile("{\n.reg .pred p;\n.reg .b32 ta, tb;\n.reg .b64 da, db;\nadd.u32 ta, %64, %65;\nmov.b64 da, {ta, %66};\nadd.u32 tb, %67, %68;\nmov.b64 db, {tb, %69};\nsetp.ne.b32 p, 1, 0;\n"
    "wgmma.mma_async.sync.aligned.m64n128k16.f32.bf16.bf16 {%0, %1, %2, %3, %4, %5, %6, %7, %8, %9, %10, %11, %12, %13, %14, %15, %16, %17, %18, %19, %20, %21, %22, %23, %24, %25, %26, %27, %28, %29, %30, %31, %32, %33, %34, %35, %36, %37, %38, %39, %40, %41, %42, %43, %44, %45, %46, %47, %48, %49, %50, %51, %52, %53, %54, %55, %56, %57, %58, %59, %60, %61, %62, %63}, da, db, p, 1, 1, 0, 1;\n}\n"
    : "+f"(d[0]), "+f"(d[1]), "+f"(d[2]), "+f"(d[3]), "+f"(d[4]), "+f"(d[5]), "+f"(d[6]), "+f"(d[7]), "+f"(d[8]), "+f"(d[9]), "+f"(d[10]), "+f"(d[11]), "+f"(d[12]), "+f"(d[13]), "+f"(d[14]), "+f"(d[15]), "+f"(d[16]), "+f"(d[17]), "+f"(d[18]), "+f"(d[19]), "+f"(d[20]), "+f"(d[21]), "+f"(d[22]), "+f"(d[23]), "+f"(d[24]), "+f"(d[25]), "+f"(d[26]), "+f"(d[27]), "+f"(d[28]), "+f"(d[29]), "+f"(d[30]), "+f"(d[31]), "+f"(d[32]), "+f"(d[33]), "+f"(d[34]), "+f"(d[35]), "+f"(d[36]), "+f"(d[37]), "+f"(d[38]), "+f"(d[39]), "+f"(d[40]), "+f"(d[41]), "+f"(d[42]), "+f"(d[43]), "+f"(d[44]), "+f"(d[45]), "+f"(d[46]), "+f"(d[47]), "+f"(d[48]), "+f"(d[49]), "+f"(d[50]), "+f"(d[51]), "+f"(d[52]), "+f"(d[53]), "+f"(d[54]), "+f"(d[55]), "+f"(d[56]), "+f"(d[57]), "+f"(d[58]), "+f"(d[59]), "+f"(d[60]), "+f"(d[61]), "+f"(d[62]), "+f"(d[63])
    : "r"(alo), "n"(AO), "n"(AH), "r"(blo), "n"(BO), "n"(BH));
}
template<uint32_t AO, uint32_t AH, uint32_t BO, uint32_t BH> __device__ __forceinline__ void mma128_ss0(float (&d)[64], uint32_t alo, uint32_t blo) {
  asm volatile("{\n.reg .pred p;\n.reg .b32 ta, tb;\n.reg .b64 da, db;\nadd.u32 ta, %64, %65;\nmov.b64 da, {ta, %66};\nadd.u32 tb, %67, %68;\nmov.b64 db, {tb, %69};\nsetp.ne.b32 p, 0, 0;\n"
    "wgmma.mma_async.sync.aligned.m64n128k16.f32.bf16.bf16 {%0, %1, %2, %3, %4, %5, %6, %7, %8, %9, %10, %11, %12, %13, %14, %15, %16, %17, %18, %19, %20, %21, %22, %23, %24, %25, %26, %27, %28, %29, %30, %31, %32, %33, %34, %35, %36, %37, %38, %39, %40, %41, %42, %43, %44, %45, %46, %47, %48, %49, %50, %51, %52, %53, %54, %55, %56, %57, %58, %59, %60, %61, %62, %63}, da, db, p, 1, 1, 0, 1;\n}\n"
    : "=f"(d[0]), "=f"(d[1]), "=f"(d[2]), "=f"(d[3]), "=f"(d[4]), "=f"(d[5]), "=f"(d[6]), "=f"(d[7]), "=f"(d[8]), "=f"(d[9]), "=f"(d[10]), "=f"(d[11]), "=f"(d[12]), "=f"(d[13]), "=f"(d[14]), "=f"(d[15]), "=f"(d[16]), "=f"(d[17]), "=f"(d[18]), "=f"(d[19]), "=f"(d[20]), "=f"(d[21]), "=f"(d[22]), "=f"(d[23]), "=f"(d[24]), "=f"(d[25]), "=f"(d[26]), "=f"(d[27]), "=f"(d[28]), "=f"(d[29]), "=f"(d[30]), "=f"(d[31]), "=f"(d[32]), "=f"(d[33]), "=f"(d[34]), "=f"(d[35]), "=f"(d[36]), "=f"(d[37]), "=f"(d[38]), "=f"(d[39]), "=f"(d[40]), "=f"(d[41]), "=f"(d[42]), "=f"(d[43]), "=f"(d[44]), "=f"(d[45]), "=f"(d[46]), "=f"(d[47]), "=f"(d[48]), "=f"(d[49]), "=f"(d[50]), "=f"(d[51]), "=f"(d[52]), "=f"(d[53]), "=f"(d[54]), "=f"(d[55]), "=f"(d[56]), "=f"(d[57]), "=f"(d[58]), "=f"(d[59]), "=f"(d[60]), "=f"(d[61]), "=f"(d[62]), "=f"(d[63])
    : "r"(alo), "n"(AO), "n"(AH), "r"(blo), "n"(BO), "n"(BH));
}

#define XD 600
#define XSTEP 300
#define XPD 450
#define XPB 8192
#define SPG 5600
#define WL0 1800
#define WLS 350
#define NB0 2
#define WP1 2000
#define PF_START 5600
#define PFP 126
#define GPERM 0x76543210u
#define FMODE 1
#define NM0 3
#define PWAIT 600
#define AWAKE 3
#define O1H 1
#define X1N 16
#define WDW 3
#define WDGAP 300
#define YWAIT 500
#define OUTW 0
#define CWAIT 500
#define NDF 8
#define O0ALL 0
#define O1ALL 0
#define RDV 1
#define MSTEP 1200
#define MSLP 1000
#define MPOLL 3200
#define LMP 8
#define WOGAP 200
#define CLR0 22000
#define UPGAP 300
#define OUTGAP 150
#define MPROMO P128
#define MLOAD tma_load_ef
struct Ptrs { const bf16 *x, *wmod, *c, *wr, *wqkv; int by_sm; Scratch* s; const bf16 *wg, *wu, *wd, *wo; bf16* out; uint16_t role[132]; };

#define BAR(i) (sb + OFF_BAR + 8u * (i))

__device__ __forceinline__ uint32_t get_tag(uint32_t sb) { mbar_wait(BAR(B_TAG), 0); const uint32_t d = __shfl_sync(0xffffffffu, lds32(sb + OFF_CST + 32), 0); return d + 1 + (d & 2); }
__device__ __forceinline__ int d_kb(int n, int hg) {
    if (n < 2) return 2 * hg + n;
    const int h = n >= 9, q = n - 2 - 7 * h;
    return 2 * (q + (q >= hg)) + h;
}

__global__ void __launch_bounds__(NTHREADS, 1)
fused_kernel(const Ptrs p, const __grid_constant__ CUtensorMap tmM, const __grid_constant__ CUtensorMap tmX, const __grid_constant__ CUtensorMap tmW,
             const __grid_constant__ CUtensorMap tmWo, const __grid_constant__ CUtensorMap tmPhi, const __grid_constant__ CUtensorMap tmG,
             const __grid_constant__ CUtensorMap tmU, const __grid_constant__ CUtensorMap tmD, const __grid_constant__ CUtensorMap tmO)
{
    extern __shared__ __align__(1024) uint8_t smem_raw[];
    const uint32_t sb = smem_u32(smem_raw);
    const uint32_t cstart = __shfl_sync(0xffffffffu, clk32(), 0);
    const int tid = threadIdx.x, lane = tid & 31, warp = __shfl_sync(0xffffffffu, tid >> 5, 0);
    if (blockIdx.x < 128) {
        if (warp == 8) asm volatile("prefetch.global.L2 [%0];" :: "l"(p.wmod + (size_t)(blockIdx.x * 8 + (lane >> 2)) * 6144 + (lane & 1) * 64 + (lane & 2) * 512));
        if (warp == 13 && (lane & 1) < NM0 - 2) asm volatile("prefetch.global.L2 [%0];" :: "l"(p.wmod + (size_t)(blockIdx.x * 8 + (lane >> 2)) * 6144 + 128 + (lane & 1) * 64 + (lane & 2) * 512));
        if (warp == 12) l2_prefetch(p.wqkv + (size_t)blockIdx.x * 1536, 3072);
        if (warp == 9) { spin_until(cstart + XPD); l2_prefetch(p.x + (size_t)blockIdx.x * 16384, XPB); }
    }
    if (warp == 10) { tmap_prefetch(&tmM); tmap_prefetch(&tmX); tmap_prefetch(&tmW); }
    if (warp == 11) asm volatile("prefetch.global.L2 [%0];" :: "l"((lane < 16 ? p.c : p.wr) + (lane & 15) * 64));
    #pragma unroll
    for (int i = 0; i < 5; i++) e_init(BAR(5 * warp + i), warp < 5 ? 1 : warp < 7 ? 2 : warp < 9 ? 4 : 8);
    mbar_init_fence();
    if (warp == B_TAG / 5) { e_arrive_tx(BAR(B_TAG), 16); bulk_load(sb + OFF_CST + 32, p.s->done, 16, BAR(B_TAG)); }
    uint32_t role;
    asm("mov.u32 %0, %%smid;" : "=r"(role));
    role = p.role[p.by_sm ? role : blockIdx.x];
    const int b = role & 255;
    if (b >= 128 && warp == 0) {
        #pragma unroll
        for (int i = 0; i < 2; i++) { e_arrive_tx(BAR(i), 32768); MLOAD(sb + i * 32768u, &tmM, (b & 1) * 1024, (b & 2) * 256 + i * 256, BAR(i)); }
    }
    __syncthreads();

    if (b >= 128) {
        const int sp = b & 3;
        if (warp == 8) {
            #pragma unroll 1
            for (int j = 2, st = 2, ph = 1; j < 64; j++) {
                if (j == 2 * NM0) spin_until(cstart + SPG);
                mbar_wait(BAR(B_EA + st), ph);
                e_arrive_tx(BAR(st), 32768);
                MLOAD(sb + st * 32768u, &tmM, j < 32 ? (sp & 1) * 1024 + (j >> 1) * 64 : 2560 + sp * 512 + (j >> 2) * 64, (j < 32 ? (sp & 2) + (j & 1) : j & 3) * 256, BAR(st));
                if (++st == 6) { st = 0; ph ^= 1; }
            }
        } else if (warp < 8) {
            const int g = lane >> 2, c = lane & 3;
            {
                const bf16* cp = p.c + (tid >> 3) * 32 + (tid & 1) * 16 + (tid & 6);
                const uint32_t c0 = ldg32(cp), c1 = ldg32(cp + 8);
                stg_zero(p.s->llm1 + (tid >> 4) * 64 + sp * 16 + (tid & 15));
                if (tid < 128) stg_zero(p.s->llmod2 + sp * 128 + tid);
                sts64(sb + 200704u + tid * 8, silu2(c0), silu2(c1));
                bar_sync(1, 256);
                TR(57);
            }
            const uint32_t tag = get_tag(sb);
            const uint32_t wa = sb + (warp * 32 + (lane & 7) + (lane >> 4) * 8) * 128u + ((((lane >> 3) & 1) ^ (lane & 7)) << 4);
            float m[4][4];
            #pragma unroll
            for (int i = 0; i < 4; i++) m[i][0] = m[i][1] = m[i][2] = m[i][3] = 0.f;
            #pragma unroll 1
            for (int r = 0, st = 0, ph = 0; r < 32; r++) {
                const int n = r < 16 ? r : (r >> 1) + 8;
                const bf16* wr = p.wr + (sp & 1) * 512 + (n & 7) * 64 + (g & 3) * 16 + 2 * c;
                const uint32_t wr0 = ldg32(wr), wr1 = ldg32(wr + 8);
                const uint32_t sa = sb + 200704u + ((r < 16 ? sp >> 1 : r & 1) * 16 + warp) * 64 + c * 16;
                const uint4 sv0 = lds128(sa), sv1 = lds128(sa + 512);
                uint32_t f[16][4];
                #pragma unroll
                for (int q = 0; q < 2; q++) {
                    mbar_wait(BAR(st + q), ph);
                    if (r == 0 && warp == 0) TR(60 + q);
                    #pragma unroll
                    for (int i = 0; i < 8; i++) ldsm4t(f[8 * q + i], (wa + (st + q) * 32768u + (i >> 2) * 2048u) ^ ((i & 3) << 5));
                }
                #pragma unroll
                for (int i = 0; i < 16; i++) {
                    const uint4& sv = i < 8 ? sv0 : sv1;
                    mma16816(m[i & 3], f[i][0], f[i][1], f[i][2], f[i][3], (i & 4) ? sv.z : sv.x, (i & 4) ? sv.w : sv.y);
                    if ((i & 7) == 7) e_arrive(BAR(B_EA + st + (i >> 3)));
                }
                st += 2; if (st == 6) { st = 0; ph ^= 1; }
                if (r >= 16 && !(r & 1)) continue;
                const uint32_t red = sb + 196608u + (n & 1) * 2048u;
                const uint32_t a = red + warp * 256u + (c * 16 + (g >> 1) * 4 + (g & 1)) * 4u;
                stsf(a, sel4(c, m[0][0], m[1][0], m[2][0], m[3][0])); stsf(a + 8, sel4(c, m[0][2], m[1][2], m[2][2], m[3][2]));
                #pragma unroll
                for (int i = 0; i < 4; i++) m[i][0] = m[i][1] = m[i][2] = m[i][3] = 0.f;
                bar_sync(1, 256);
                if (warp == (n & 7)) {
                    const uint32_t ra = red + (lane >> 4) * 1024u + (lane & 15) * 16u;
                    const uint4 r0 = lds128(ra), r1 = lds128(ra + 256), r2 = lds128(ra + 512), r3 = lds128(ra + 768);
                    #define F4(f) ((u2f(r0.f) + u2f(r1.f)) + (u2f(r2.f) + u2f(r3.f)))
                    float x = F4(x), y = F4(y), z = F4(z), w = F4(w);
                    #undef F4
                    x += shfl_x(x, 16); y += shfl_x(y, 16); z += shfl_x(z, 16); w += shfl_x(w, 16);
                    if (n < 16) {
                        if (lane < 16) st_ll4(p.s->llm1 + n * 64 + sp * 16 + lane, x, y, z, w, tag);
                    } else {
                        uint32_t lo = pack2(x, y), hi2 = pack2(z, w);
                        float d = fmaf(bf_lo(lo), bf_lo(wr0), bf_hi(lo) * bf_hi(wr0)) + fmaf(bf_lo(hi2), bf_lo(wr1), bf_hi(hi2) * bf_hi(wr1));
                        if (sp >= 2) {
                            lo = hadd2(lo, ONE2); hi2 = hadd2(hi2, ONE2);
                            const uint32_t r0 = hmul2(lo, wr0), r1 = hmul2(hi2, wr1);
                            d = (bf_lo(r0) + bf_hi(r0)) + (bf_lo(r1) + bf_hi(r1));
                        }
                        #pragma unroll 1
                        for (int k = 1; k < 16; k <<= 1) d += shfl_x(d, k);
                        if (lane < 16) st_ll(p.s->llmod2 + sp * 128 + (n & 7) * 16 + lane, lo, hi2, f2u(d), tag);
                    }
                    TR(n);
                }
            }
        }
    } else if (warp >= 12) {
        reg_dec<24>();
        const int rb = b >> 3, hg = b & 7, fs = role >> 8;
        const bool ffn = fs < 112;
        if (warp == 12) {
            #pragma unroll 1
            for (int j = 0, s = 0, ph = 1; j < 16; j++) {
                if (j < 2) mbar_wait(j ? BAR(B_STS) : BAR(B_STP), 0);
                mbar_wait(BAR(B_EA + s), ph);
                e_arrive_tx(BAR(B_FA + s), 16384); tma_load(sb + OFF_A + s * 16384u, &tmX, j * 64, rb * 128, BAR(B_FA + s));
                if (j == 0) TS(2);
                if (j == 1) GT(0);
                if (j == 6) GT(1);
                if (j == 11) GT(2);
                if (++s == 3) { s = 0; ph ^= 1; }
            }
            tmap_prefetch(&tmO);
            const uint32_t tag = get_tag(sb);
            e_arrive(BAR(B_FD)); e_arrive(BAR(B_FD + 1));
            #pragma unroll 1
            for (int q = 0; q < 3; q++) {
                mbar_wait(q < 2 ? BAR(B_KST + 1 + 2 * q) : BAR(B_OWN), 0);
                poll_flags(q < 2 ? p.s->flk + (q + 1) * 256 + (hg * 16 + (lane & 15)) * 2 : p.s->flo + (O0ALL ? (rb & 12) * 16 + lane * 2 : rb * 16 + (lane & 7) * 2) * 2, tag);
                if (q == 2) break;
                e_arrive_tx(BAR(B_KVL + q), 16896); bulk_load(sb + (q ? OFF_PHI : OFF_KL), p.s->kvacc + hg * 2112 + q * 1056, 16896, BAR(B_KVL + q));
                TS(12 + q);
                if (!q) GT(4);
            }
            if (O1H == 2) e_arrive(BAR(B_UD));
            TS(3); GT(5);
            const uint4* osrc = p.s->os + (size_t)rb * 16 * 1024;
            #pragma unroll 1
            for (int n = 2; n < 17; n++) {
                const uint32_t s = n & 3, fb = BAR(B_FD + s), dst = sb + OFF_R0 + s * 16384u;
                mbar_wait(BAR(B_ED + s), ((n >> 2) - 1) & 1);
                if (n == 5 || n == 9) mbar_wait(n == 5 ? BAR(B_OST) : BAR(B_O1), 0);
                e_arrive_tx(fb, 16384);
                if (n < 16) bulk_load(dst, osrc + d_kb(n, hg) * 1024, 16384, fb);
                else { e_arrive(fb); tma_load(dst, &tmX, hg * 128, rb * 128, fb); }
                if (n == X1N) { e_arrive_tx(BAR(B_WPHI), 16384); tma_load(sb + OFF_X1, &tmX, hg * 128 + 64, rb * 128, BAR(B_WPHI)); }
                TR(32 + n);
            }
            GT(6);
            mbar_wait(BAR(B_CAND), 0);
            GT(7);
            const uint2 lc = lds64(sb + OFF_CST + 16);
            const uint32_t w0 = __shfl_sync(0xffffffffu, lc.x >> 4, 0), w1 = __shfl_sync(0xffffffffu, lc.y >> 4, 0);
            mbar_wait(BAR(B_SWP), 0);
            fence_async_smem();
            if (OUTW) mbar_wait(BAR(B_SEL), 0);
            #pragma unroll 1
            for (uint32_t w = 0; w < 8; w++)
                if (w != w0 && w != w1) { tma_store4(&tmO, rb * 128 + w * 16, hg * 2, sb + OFF_OUT + w * 4096u); spin_until(clk32() + OUTGAP); }
            mbar_wait(BAR(B_SEL), 0);
            const uint2 sel = lds64(sb + OFF_CST + 24);
            #pragma unroll 1
            for (uint32_t i = 0; i < (w0 == w1 ? 8u : 16u); i++) {
                const uint32_t w = i < 8 ? w0 : w1, r = (i & 7) * 2 + (lane >> 4), row = rb * 128 + w * 16 + r;
                const uint4 o = lds128(sb + OFF_OUT + w * 4096u + ((lane >> 3) & 1) * 2048u + r * 128u + (((lane ^ r) & 7) << 4));
                if (row != (~sel.x & 2047u) && row != (~sel.y & 2047u)) stg128(p.out + (size_t)row * 1024 + hg * 128 + (lane & 15) * 8, o);
            }
            bulk_wait_read();
        } else if (warp == 14) {
            const uint32_t fb = ffn ? 65536 : 0;
            e_arrive_tx(BAR(B_GF), fb); e_arrive_tx(BAR(B_UD), fb); e_arrive_tx(BAR(B_UF), fb); e_arrive_tx(BAR(B_WD), fb);
            uint32_t due = cstart + WP1;
            #pragma unroll 1
            for (int i = -2; i < 26; i++) {
                if (i >= 0) {
                    const bf16* a = i < 8 ? p.wg + (size_t)(i * 128 + b) * 3584 : i < 16 ? p.wu + (size_t)((i - 8) * 128 + b) * 3584
                                  : i < 18 ? p.wo + (size_t)(b * 2 + i - 16) * 4096 : p.wd + (size_t)(b * 8 + i - 18) * 3584;
                    sleep_until(due);
                    l2_prefetch(a, (i >> 1) == 8 ? 8192 : 7168);
                    due += 7 * PFP;
                }
                if (i == 1) { tmap_prefetch(&tmPhi); tmap_prefetch(&tmG); tmap_prefetch(&tmWo); tmap_prefetch(&tmU); tmap_prefetch(&tmD); mbar_wait(BAR(B_STS), 0); }
                if (ffn && (uint32_t)(i - 3) < 8u) tma_load_ef(sb + OFF_R0 + (i - 3) * 8192u, &tmG, fs * 32, (i - 3) * 128, BAR(B_GF));
                if (ffn && (uint32_t)(i - 11) < 8u) tma_load(sb + OFF_WPHI, &tmU, fs * 32, (i - 11) * 128, BAR(B_UD));
                if (i == 19) { mbar_wait(BAR(B_UD), 0); e_arrive_tx(BAR(B_WPHI), 8192); tma_load(sb + OFF_WPHI, &tmPhi, 0, hg * 128, BAR(B_WPHI)); }
                if (i == LMP + 2 * (b & 3) + (b >> 6)) tma_prefetch(&tmM, 2048 + (b >> 6) * 2048 + (b >> 2) * 64, (b & 3) * 256);
                if (i < 13) {
                    sleep_until(due);
                    l2_prefetch(p.wqkv + (size_t)((i + 3) * 128 + b) * 1536, 3072);
                    due += i == -2 ? PF_START - WP1 : 3 * PFP;
                }
            }
            if (lane < 4) stg_zero(p.s->flo + b * 4 + lane);
            const uint32_t tag = get_tag(sb);
            #pragma unroll 1
            for (int q = 0; q < 2; q++) {
                mbar_wait(BAR(B_OWN + q), 0);
                if (q && O1H) mbar_wait(O1H == 1 ? BAR(B_FD + 2) : BAR(B_UD), O1H - 1);
                bulk_store(p.s->os + ((size_t)b * 2 + q) * 1024, sb + OFF_R0 + q * 16384u, 16384);
                if (q) { bulk_wait_read(); e_arrive(BAR(B_OST)); }
                bulk_wait();
                __syncwarp();
                st_flag(p.s->flo + (b * 2 + q) * 2, tag, lane);
                TS(7 + q);
            }
        } else {
            uint4* fk = p.s->flk + (hg * 16 + rb) * 2;
            if (warp == 13) {
                #pragma unroll 1
                for (int i = 0; i < 32; i++) {
                    const uint32_t s = i & 3;
                    if (i < NB0) spin_until(cstart + WL0 + WLS * i); else if (i == NB0) mbar_wait(BAR(B_STS), 0);
                    mbar_wait(BAR(B_EB + s), ((i >> 2) - 1) & 1);
                    e_arrive_tx(BAR(B_FB + s), 24576); tma_load4(sb + OFF_B + s * 24576u, &tmW, i * 32, hg * 2, BAR(B_FB + s));
                    TR(64 + i);
                }
                mbar_wait(BAR(B_EB), 1); mbar_wait(BAR(B_EB + 1), 1);
                e_arrive_tx(BAR(B_LMF), 32768); tma_load_ef(sb + OFF_B, &tmM, 2048 + (b >> 6) * 2048 + (b >> 2) * 64, (b & 3) * 256, BAR(B_LMF));
                mbar_wait(BAR(B_LMD), 0);
                #pragma unroll 1
                for (int n = 0; n < 4; n++) {
                    e_arrive_tx(BAR(B_FD + n), 16384); tma_load4(sb + OFF_DB + n * 16384u, &tmWo, d_kb(n, hg) * 64, hg * 2, BAR(B_FD + n));
                    spin_until(clk32() + WOGAP);
                }
            } else {
                sleep_until(cstart + CLR0);
                const uint32_t tag = get_tag(sb);
                #pragma unroll 1
                for (int i = lane; i < 132; i += 32) stg_zero(p.s->kvacc + hg * 2112 + rb * 132 + i);
                if (lane < 4) stg_zero(fk + 256 + (lane >> 1) * 256 + (lane & 1));
                fence_gpu();
                __syncwarp();
                st_flag(fk, tag, lane);
                sleep_until(clk32() + 2000);
                poll_flags(p.s->flk + (hg * 16 + (lane & 15)) * 2, tag);
                mbar_wait(BAR(B_QE), 0);
                #pragma unroll 1
                for (int i = 0; i < 4; i++) {
                    stg_zero(p.s->llln2 + b * 128 + i * 32 + lane);
                    stg_zero(p.s->llrowh + (i >> 1) * 8192 + (rb * 2 + (i & 1)) * 256 + hg * 32 + lane);
                    #pragma unroll
                    for (int k = 0; k < 4; k++) stg_zero(p.s->lly + (fs & 127) * 512 + i * 128 + k * 32 + lane);
                }
                if (lane < 2 && hg == (rb & 7)) stg_zero(p.s->llcand + rb * 2 + lane);
                __syncwarp();
                e_arrive(BAR(B_KZ));
            }
            const int q = warp == 13;
            const uint32_t tag = get_tag(sb);
            mbar_wait(BAR(B_KZ), 0);
            #pragma unroll 1
            for (int h = 2 * q; h < 2 * q + 2; h++) {
                mbar_wait(BAR(B_KST + h), 0);
                uint4* acc = p.s->kvacc + (hg * 4 + h) * 528;
                bulk_reduce(acc, sb + OFF_V + h * 8192u, 8192); bulk_reduce(acc + 512, sb + OFF_ZS + h * 256u, 256);
            }
            bulk_wait();
            if (q) e_arrive(BAR(B_KZ));
            TR(158 + q);
            fence_gpu();
            __syncwarp();
            st_flag(fk + 256 + q * 256, tag, lane);
            TS(10 + q);
            if (q) {
                #pragma unroll 1
                for (int n = 4; n < 16; n++) {
                    const uint32_t s = n & 3;
                    mbar_wait(BAR(B_ED + s), ((n >> 2) - 1) & 1);
                    e_arrive_tx(BAR(B_FD + s), 16384);
                    tma_load4(sb + OFF_DB + s * 16384u, &tmWo, d_kb(n, hg) * 64, hg * 2, BAR(B_FD + s));
                    TR(96 + n);
                    if (ffn && (n >> 2) == 2) {
                        const int z = 8 * (n & 1) + (n & 2);
                        #pragma unroll
                        for (int k = 0; k < 2; k++) tma_load_ef(sb + OFF_F2 + (n & 1) * 32768u + k * 16384u + (n & 2) * 2048u, &tmD, z * 64 + k * 256, fs * 32, BAR(B_WD));
                    }
                }
                if (ffn) {
                    mbar_wait(BAR(B_ED + WDW), 1);
                    #pragma unroll 1
                    for (int z = 0; z < 8; z++) { tma_load_ef(sb + OFF_DB + z * 4096u, &tmD, z * 128 + 64, fs * 32, BAR(B_WD)); sleep_until(clk32() + WDGAP); }
                }
            } else {
                if (ffn) {
                    mbar_wait(BAR(B_KZ), 1);
                    #pragma unroll 1
                    for (int i = 7; i < 15; i++) {
                        if (i == 12) mbar_wait(BAR(B_KVT + 1), 0);
                        tma_load_ef(sb + OFF_F2 + (i & 7) * 8192u, &tmU, fs * 32, (i & 7) * 128, BAR(B_UF));
                        sleep_until(clk32() + UPGAP);
                    }
                }
                mbar_wait(BAR(B_OST), 0);
                poll_flags(p.s->flo + (O1ALL ? (rb & 12) * 16 + lane * 2 + 1 : rb * 16 + (lane & 7) * 2 + 1) * 2, tag);
                e_arrive(BAR(B_O1));
                TS(4);
            }
        }
    } else if (warp >= 8) {
        reg_dec<24>();
        const int rb = b >> 3, hg = b & 7, w4 = warp & 3, g = lane >> 2, c = lane & 3, t = tid & 127;
        const uint32_t sv = silu2(ldg32(p.c + (b & 3) * 256 + 2 * t)), tag = get_tag(sb);
        if (w4 < 3) {
            spin_until(cstart + MPOLL + MSTEP * w4);
            #pragma unroll 1
            for (int j = w4, ph = 1; j < 16; j += 3, ph ^= 1) {
                uint4 w[2];
                poll_words<2, 0, 3>(w, p.s->llm1 + j * 64 + lane, 32, tag);
                uint32_t lo = pack2(u2f(w[0].x) + u2f(w[1].x), u2f(w[0].y) + u2f(w[1].y)), hi = pack2(u2f(w[0].z) + u2f(w[1].z), u2f(w[0].w) + u2f(w[1].w));
                if (lane >= 16) { lo = hadd2(lo, ONE2); hi = hadd2(hi, ONE2); }
                sts64(sb + OFF_TAB + j * 256 + (lane & 15) * 16 + (lane < 16 ? 8 : 0), lo, hi);
                __syncwarp();
                if (j == 0) TS(5);
                TR(16 + j);
                mbar_wait(BAR(B_EA + w4), ph);
                e_arrive(BAR(B_FA + w4));
                __nanosleep(MSLP);
            }
        }
        mbar_wait(BAR(B_QE), 0);
        if (warp == 8) GT(3);
        sts32(sb + OFF_KL + w4 * 1024u + lane * 4, sv);
        fence_async_smem();
        bar_sync(2, 128);
        reg_inc<56>();
        {
            float m0[4], m1[4];
            const uint32_t da = desc_lo(sb + OFF_B, 16), db = desc_lo(sb + OFF_KL, 16);
            mbar_wait(BAR(B_LMF), 0);
            wg_fence();
            #define LMS(f, i) f<(i) * 256, H128, ((i) >> 1) * 64 + ((i) & 1) * 4, H128>(m0, da, db); f<(i) * 256 + 128, H128, ((i) >> 1) * 64 + ((i) & 1) * 4 + 2, H128>(m1, da, db)
            LMS(mma8_tn0, 0); LMS(mma8_tn, 1); LMS(mma8_tn, 2); LMS(mma8_tn, 3); LMS(mma8_tn, 4); LMS(mma8_tn, 5); LMS(mma8_tn, 6); LMS(mma8_tn, 7);
            #undef LMS
            wg_commit();
            wg_wait<0>();
            acc_fence(m0); acc_fence(m1);
            e_arrive(BAR(B_LMD));
            const float v0 = m0[0] + m1[0], v1 = m0[2] + m1[2], u0 = shfl_x(v0, 4), u1 = shfl_x(v1, 4);
            if (!(lane & 7)) st_ll4(p.s->llg + (b >> 6) * 1024 + (b & 3) * 256 + ((b >> 2) & 15) * 16 + w4 * 4 + (lane >> 3), v0, u0, v1, u1, tag);
            if (warp == 8) TR(150);
        }
        #pragma unroll 1
        for (int h = 0; h < 4; h++) {
            float okv[20];
            const uint32_t vb = OFF_V + h * 8192u, dp = desc_lo(sb + OFF_PHI + (h & 1) * 16384u, 16), dv = desc_lo(sb + vb, OFF_ONES - vb);
            mbar_wait(BAR(B_PF + h), 0);
            fence_async_smem();
            wg_fence();
            #define KVS(i) mma40_tt<(i) * 128, H128, (i) * (64u - (64u << 16)), H64>(okv, dp, dv)
            mma40_tt0<0, H128, 0, H64>(okv, dp, dv); KVS(1); KVS(2); KVS(3); KVS(4); KVS(5); KVS(6); KVS(7);
            #undef KVS
            wg_commit();
            wg_wait<0>();
            acc_fence(okv);
            if (h < 2) e_arrive(BAR(B_PE + h));
            bar_sync(2, 128);
            #pragma unroll
            for (int k = 0; k < 4; k++) sts128(sb + vb + (k * 128 + t) * 16u, make_uint4(f2u(okv[4 * k]), f2u(okv[4 * k + 1]), f2u(okv[4 * k + 2]), f2u(okv[4 * k + 3])));
            if (c == 0) sts64(sb + OFF_ZS + h * 256u + (w4 * 8 + g) * 8u, f2u(okv[16]), f2u(okv[18]));
            fence_async_smem();
            __syncwarp();
            e_arrive(BAR(B_KST + h));
            if (warp == 8) TR(151 + h);
        }
        #pragma unroll 1
        for (int q = 0; q < 2; q++) {
            const uint32_t f = w4 * 16 + g, kl = sb + (q ? OFF_PHI : OFF_KL), ta = sb + (q ? OFF_KL : OFF_KVT) + f * 64u + ((g >> 1) << 4) + 4 * c;
            const uint32_t za = sb + OFF_Z + (f + 8 * (c & 1)) * 64u + (((2 * q) ^ (g >> 1)) << 4) + (c >> 1) * 8;
            mbar_wait(q ? BAR(B_KVT) : BAR(B_STP), q ^ 1);
            mbar_wait(BAR(B_KVL + q), 0);
            uint4 v[8]; float z[2];
            #pragma unroll
            for (int k = 0; k < 8; k++) v[k] = lds128(kl + (k >> 2) * 8448u + (k & 3) * 2048u + t * 16u);
            #pragma unroll
            for (int hh = 0; hh < 2; hh++) z[hh] = ldsf(kl + hh * 8448u + 8192u + (w4 * 8 + g) * 8u + (c & 1) * 4);
            #pragma unroll
            for (int k = 0; k < 8; k++) {
                sts32((ta ^ ((k & 3) << 4)) + (k >> 2) * 4096u, pack2(u2f(v[k].x), u2f(v[k].y))); sts32((ta ^ ((k & 3) << 4)) + (k >> 2) * 4096u + 512, pack2(u2f(v[k].z), u2f(v[k].w)));
            }
            #pragma unroll
            for (int hh = 0; hh < 2; hh++) { const uint32_t zz = pack2(z[hh], z[hh]); sts64(za ^ (hh << 4), zz, zz); }
            fence_async_smem();
            __syncwarp();
            e_arrive(BAR(B_KVT + q));
            if (warp == 8) TR(155 + q);
        }
        reg_dec<24>();
        mbar_wait(BAR(B_O1), 0);
        if (w4 == 0 || w4 == 3) {
            float s[4] = {0.f, 0.f, 0.f, 0.f};
            #pragma unroll 1
            for (int k = 0; k < 2; k++) {
                uint4 w[2];
                poll_words<2, 0, 3>(w, p.s->llg + (w4 & 1) * 1024 + k * 512 + hg * 32 + lane, 256, tag);
                s[0] += u2f(w[0].x) + u2f(w[1].x); s[1] += u2f(w[0].y) + u2f(w[1].y); s[2] += u2f(w[0].z) + u2f(w[1].z); s[3] += u2f(w[0].w) + u2f(w[1].w);
            }
            const uint32_t lo = pack2(s[0], s[1]), hi = pack2(s[2], s[3]);
            sts64(w4 ? sb + OFF_T3 + lane * 8 : sb + OFF_T1 + lane * 16, lo, hi);
            if (!w4) sts64(sb + OFF_T1 + 512 + lane * 16, lo, hi);
        } else {
            const bf16* wr = p.wr + hg * 128 + g * 16 + 2 * c;
            const uint32_t wr0 = ldg32(wr), wr1 = ldg32(wr + 8);
            uint4 w[2];
            poll_words<2, 1>(w, p.s->llmod2 + (w4 - 1) * 256 + hg * 32 + lane, (lane & 15) * 16 - hg * 32 - lane, tag);
            sts64(sb + OFF_T2 + lane * 16 + (w4 & 1) * 8, w[0].x, w[0].y);
            if (w4 == 2) sts64(sb + OFF_T1 + 512 + lane * 16 + 8, hmul2(w[0].x, wr0), hmul2(w[0].y, wr1));
            float d = u2f(w[1].z);
            #pragma unroll 1
            for (int k = 1; k < 16; k <<= 1) d += shfl_x(d, k);
            stsf(sb + OFF_CST + 8 + (w4 & 1) * 4, d);
        }
        __syncwarp();
        e_arrive(BAR(B_PAR));
        if (warp == 9) TS(6);
        if (w4 < 2) {
            mbar_wait(BAR(B_PAR), 0);
            const uint4 ta = lds128(sb + OFF_T2 + lane * 16);
            const uint2 gb = lds64(sb + OFF_T3 + lane * 8);
            uint4* d = pin_ptr(p.s->llrowh + (rb * 2 + w4) * 256 + hg * 32 + lane);
            mbar_wait(BAR(B_KEYS), 0);
            const uint4 kk = lds128(sb + OFF_KEY + lane * 16);
            uint32_t k[4] = {kk.x, kk.y, kk.z, kk.w}, b0, b1;
            top2<4>(k, b0, b1);
            const uint32_t cd = ~(w4 ? b1 : b0) & 127u;
            const uint32_t xa = sb + OFF_R0 + (g >> 2) * (OFF_X1 - OFF_R0) + cd * 128u + ((((g & 3) * 2) ^ (cd & 7)) << 4) + c * 4;
            const uint32_t x0 = lds32(xa), x1 = lds32(xa ^ 16);
            const uint4 st = lds128(sb + OFF_ST2 + cd * 16);
            st_ll(d, lnmod(x0, st.x, st.y, st.z, ta.x, ta.z), lnmod(x1, st.x, st.y, st.z, ta.y, ta.w), gb.x, tag);
            st_ll(d + 8192, x0, x1, gb.y, tag);
            sts32(sb + OFF_CST + 16 + w4 * 4, cd);
            __syncwarp();
            e_arrive(BAR(B_CAND));
            if (warp == 8) TS(9);
        } else if (w4 == 2) {
            uint4* cp = pin_ptr(p.s->llcand + lane);
            mbar_wait(BAR(B_KEYS), 0);
            if (hg == (rb & 7)) {
                const uint4 kk = lds128(sb + OFF_KEY + lane * 16);
                uint32_t k[4] = {kk.x, kk.y, kk.z, kk.w}, b0, b1;
                top2<4>(k, b0, b1);
                if ((lane >> 1) == rb) st_ll(cp, (lane & 1) ? b1 : b0, tag, tag, tag);
            } else spin_until(clk32() + CWAIT);
            uint2 v = make_uint2(0, 0);
            #pragma unroll 1
            for (int it = 0; it < POLL_MAX; it++) {
                if (v.y != tag) asm volatile("ld.relaxed.gpu.global.v2.b32 {%0,%1}, [%2];" : "=r"(v.x), "=r"(v.y) : "l"(cp) : "memory");
                if (__all_sync(0xffffffffu, v.y == tag)) break;
            }
            uint32_t k[1] = {v.x}, b0, b1;
            top2<1>(k, b0, b1);
            sts64(sb + OFF_CST + 24, b0, b1);
            __syncwarp();
            e_arrive(BAR(B_SEL));
        }
    } else {
        reg_inc<232>();
        float a0[96], a1[96];
        {
            const int g = lane >> 2, c = lane & 3;
            uint4* stp = p.s->llstat + b * 16 + warp * 2 + (lane >> 4);
            if ((lane & 15) == 0) stg_zero(stp);
            spin_until(cstart + XD + XSTEP * warp);
            e_arrive_tx(BAR(B_XP + warp), 4096);
            bulk_load(sb + OFF_R0 + warp * 4096u, p.x + (size_t)(b * 16 + 2 * warp) * 1024, 4096, BAR(B_XP + warp));
            const uint32_t tag = get_tag(sb);
            if (tid < 64) sts128(sb + OFF_ONES + tid * 16, make_uint4(ONE2, ONE2, ONE2, ONE2));
            if (tid == 64) sts64(sb + OFF_CST, role, tag);
            if (AWAKE & 1) mbar_wait_awake(BAR(B_XP + warp), 0); else mbar_wait(BAR(B_XP + warp), 0);
            e_arrive(BAR(B_STP));
            if (warp == 7) TS(14);
            float s[2][4], q0[2][4], q1[2][4];
            #pragma unroll
            for (int i = 0; i < 4; i++) s[0][i] = s[1][i] = q0[0][i] = q0[1][i] = q1[0][i] = q1[1][i] = 0.f;
            #pragma unroll
            for (int i = 0; i < 4; i++) {
                const uint4 x0 = lds128(sb + OFF_R0 + warp * 4096u + (lane + 32 * i) * 16u), x1 = lds128(sb + OFF_R0 + warp * 4096u + 2048u + (lane + 32 * i) * 16u);
                mma16816(s[0], x0.x, x1.x, x0.y, x1.y, ONE2, ONE2); mma16816(s[1], x0.z, x1.z, x0.w, x1.w, ONE2, ONE2);
                mma16816(q0[0], x0.x, x1.x, x0.y, x1.y, x0.x, x0.y); mma16816(q0[1], x0.z, x1.z, x0.w, x1.w, x0.z, x0.w);
                mma16816(q1[0], x0.x, x1.x, x0.y, x1.y, x1.x, x1.y); mma16816(q1[1], x0.z, x1.z, x0.w, x1.w, x1.z, x1.w);
            }
            const bool dg = c == (g >> 1);
            const float s0 = dg ? s[0][0] + s[1][0] : 0.f, s1 = dg ? s[0][2] + s[1][2] : 0.f;
            const float sq0 = dg ? ((g & 1) ? q0[0][1] + q0[1][1] : q0[0][0] + q0[1][0]) : 0.f, sq1 = dg ? ((g & 1) ? q1[0][3] + q1[1][3] : q1[0][2] + q1[1][2]) : 0.f;
            const bool up = lane >= 16;
            float sm = (up ? s1 : s0) + shfl_x(up ? s0 : s1, 16), sq = (up ? sq1 : sq0) + shfl_x(up ? sq0 : sq1, 16);
            #pragma unroll
            for (int m = 8; m >= 1; m >>= 1) { sm += shfl_x(sm, m); sq += shfl_x(sq, m); }
            uint32_t m2, rh, rl; float rinv;
            ln_final(sm, sq, m2, rinv);
            split_rcp(rinv, rh, rl);
            if ((lane & 15) == 0) st_ll(stp, m2, rh, rl, tag);
            if (warp == 7) TS(15);
            uint4 st[2];
            if (PWAIT) { mbar_wait(BAR(B_STP), 0); if (warp < 7) spin_until(clk32() + PWAIT); }
            #pragma unroll 1
            for (int it = 0; it < POLL_MAX; it++) {
                st[0] = ld_ll(p.s->llstat + (b >> 3) * 128 + warp * 16 + g); st[1] = ld_ll(p.s->llstat + (b >> 3) * 128 + warp * 16 + g + 8);
                const uint32_t o = RDV ? ld_rlx(&p.s->llstat[((b >> 5) * 4 + c) * 128 + warp * 16 + 15].w) : tag;
                if (__all_sync(0xffffffffu, !tag_bad(tag_bad(o ^ tag, st[0].w, tag), st[1].w, tag))) break;
                if (AWAKE & 1) it += awake_zero();
            }
            e_arrive(BAR(B_STS));
            if (warp == 0) TS(16);
            const uint32_t lrow = warp * 16 + (lane & 15);
            uint32_t aad = sb + OFF_A + lrow * 128u + (((lane >> 4) ^ (lrow & 7)) << 4);
            uint32_t tad = sb + OFF_TAB + c * 16, ab = BAR(B_FA), pa = 0;
            uint32_t f0[4], f1[4];
            #define PREP(f, q) do { \
                const uint4 t = lds128(tad + (q) * 64); \
                ldsm4(f, aad ^ ((q) << 5)); \
                f[0] = lnmod(f[0], st[0].x, st[0].y, st[0].z, t.x, t.z); f[1] = lnmod(f[1], st[1].x, st[1].y, st[1].z, t.x, t.z); \
                f[2] = lnmod(f[2], st[0].x, st[0].y, st[0].z, t.y, t.w); f[3] = lnmod(f[3], st[1].x, st[1].y, st[1].z, t.y, t.w); } while (0)
            #define MMA(f, off) do { wg_fence(); mma192_rs<(off), H128>(a0, f, blo); mma192_rs<(off) + 768, H128>(a1, f, blo); wg_commit(); wg_wait<1>(); } while (0)
            mbar_wait(ab, 0);
            PREP(f0, 0);
            if (RDV) mbar_wait(BAR(B_STS), 0);
            #pragma unroll 1
            for (int j = 0; j < 16; j++) {
                const uint32_t bb = BAR(B_FB) + (j & 1) * 16, blo = desc_lo(sb + OFF_B, 4096) + (j & 1) * 3072, pb = (j >> 1) & 1;
                mbar_wait(bb, pb);
                wg_fence(); mma192_rsp<0, H128>(a0, f0, blo, j); mma192_rsp<768, H128>(a1, f0, blo, j); wg_commit(); wg_wait<1>();
                if (j) e_arrive((bb ^ 16) + 8 * (B_EB - B_FB) + 8);
                PREP(f1, 1);
                MMA(f1, 128);
                PREP(f0, 2);
                mbar_wait(bb + 8, pb);
                MMA(f0, 1536);
                e_arrive(bb + 8 * (B_EB - B_FB));
                PREP(f1, 3);
                MMA(f1, 1536 + 128);
                e_arrive(ab + 8 * (B_EA - B_FA));
                ab += 8; aad += 16384; tad += 256;
                if (ab == BAR(B_FA + 3)) { ab -= 24; aad -= 49152; pa ^= 1; }
                if (j < 15) mbar_wait(ab, pa);
                PREP(f0, 0);
            }
            #undef PREP
            #undef MMA
        }
        int tid_o; asm volatile("mov.u32 %0, %%tid.x;" : "=r"(tid_o) :: "memory");
        const int tid = tid_o, lane = tid & 31, warp = __shfl_sync(0xffffffffu, tid >> 5, 0), wgi = warp >> 2, g = lane >> 2, c = lane & 3;
        const uint32_t srow = warp * 16 + (lane & 15);
        #define T128(t) (sb + (((t) >> 5) * 16 + ((t) & 15)) * 128u + (((((t) >> 4) & 1) ^ ((t) & 7)) << 4))
        const uint32_t pa = T128(tid);
        mbar_wait(BAR(B_WPHI), 0);
        mbar_wait(BAR(B_EA), 1);
        wg_wait<0>();
        acc_fence(a0); acc_fence(a1);
        e_arrive(BAR(B_QE));
        if (warp == 0) TS(18);
        uint32_t ph0[16], ph1[16], kq[32];
        {
        uint32_t pk[16], mm[4];
        float ea[32], eb[32];
        #define PIN() do { acc_fence(ea); acc_fence(eb); pin<16>(pk); pin<4>(mm); } while (0)
        {
            float p0[16], p1[16];
            const uint32_t dw = desc_lo(sb + OFF_WPHI, 16);
            #define PMMA(f, o) do { wg_fence(); mma32_rs0<(o), H64>(p0, f, dw); mma32_rs0<(o) + 128, H64>(p1, f + 8, dw); \
                mma32_rs<(o) + 64, H64>(p0, f + 4, dw); mma32_rs<(o) + 192, H64>(p1, f + 12, dw); wg_commit(); } while (0)
            #define V_OUT(lo) _Pragma("unroll") for (int i = lo; i < lo + 4; i++) { const int o = 32 + 8 * i; \
                stsm4(sb + OFF_V + (i >> 1) * 8192u + srow * 64u + (((2 * (i & 1) + (lane >> 4)) ^ ((srow >> 1) & 3)) << 4), \
                      pack2(a1[o], a1[o + 1]), pack2(a1[o + 2], a1[o + 3]), pack2(a1[o + 4], a1[o + 5]), pack2(a1[o + 6], a1[o + 7])); }
            V_OUT(0);
            #pragma unroll
            for (int i = 0; i < 16; i++) ph0[i] = pack2(a0[64 + 2 * i], a0[65 + 2 * i]);
            PMMA(ph0, 0);
            V_OUT(4);
            #undef V_OUT
            wg_wait<0>();
            acc_fence(p0); acc_fence(p1);
            fm_max(p0, pk, mm); fm_max(p1, pk + 8, mm + 2);
            #pragma unroll
            for (int i = 0; i < 16; i++) ph1[i] = pack2(a1[2 * i], a1[2 * i + 1]);
            PMMA(ph1, 256);
            fm_args(pk, mm, ea);
            if (warp == 0) TS(19);
            fm_exp<0, 16>(ea);
            #pragma unroll
            for (int i = 0; i < 32; i++) kq[i] = pack2(a0[2 * i], a0[2 * i + 1]);
            acc_fence(ea); pin<32>(kq);
            wg_wait<0>();
            acc_fence(p0); acc_fence(p1);
            #define PHI_OUT(ph, i) do { if (u < 2) { \
                    mbar_wait(u ? BAR(B_PE + (i)) : (i) ? BAR(B_LMD) : BAR(B_QE), 0);          \
                    _Pragma("unroll") for (int q = 0; q < 4; q++) stsm4((pa ^ (q << 5)) + OFF_PHI + (i) * 16384u, ph[4 * q], ph[4 * q + 1], ph[4 * q + 2], ph[4 * q + 3]); \
                    __syncwarp(); \
                    e_arrive(BAR(B_PF + (i)) + u * 16); } } while (0)
            reg_dec<216>();
            #pragma unroll 1
            for (int u = 0; u < 4; u++) {
                fm_exp<16, 32>(ea); fm_args(pk + 8, mm + 2, eb);
                PIN();
                if (warp == 0) TR(129 + (u & 1) * 6);
                fm_exp<0, 16>(eb); fm_norm(ea, ph0); fm_max(p0, pk, mm);
                acc_fence(eb); pin<8>(pk); pin<2>(mm);
                PHI_OUT(ph0, 0);
                if (warp == 0) TR(130 + (u & 1) * 6);
                fm_exp<16, 32>(eb); fm_args(pk, mm, ea); fm_max(p1, pk + 8, mm + 2);
                PIN();
                if (warp == 0) TR(131 + (u & 1) * 6);
                if (u == 0) PMMA(kq, 0); else PMMA(kq + 16, 256);
                fm_exp<0, 16>(ea); fm_norm(eb, ph1);
                acc_fence(ea);
                if (warp == 0) TR(132 + (u & 1) * 6);
                PHI_OUT(ph1, 1);
                wg_wait<0>();
                acc_fence(p0); acc_fence(p1);
                if (u == 1) e_arrive(BAR(B_STP));
                if (u == 2) {
                    #pragma unroll
                    for (int i = 0; i < 16; i++) { kq[i] = ph0[i]; kq[16 + i] = ph1[i]; }
                }
                if (warp == 0) TR(133 + (u & 1) * 6);
                if (warp == 0) TS(21 + u);
            }
            #undef PHI_OUT
            #undef PMMA
        }
        }
        uint32_t gf[16][4], uf[16][4];
        const uint32_t fo = (warp >> 1) * 16384u + ((lane & 7) + (lane >> 4) * 8) * 64u + (((2 * (warp & 1) + ((lane >> 3) & 1)) ^ ((lane >> 1) & 3)) << 4);
        mbar_wait(BAR(B_GF), 0);
        #pragma unroll
        for (int i = 0; i < 16; i++) ldsm4t(gf[i], sb + OFF_R0 + fo + i * 1024u);
        e_arrive(BAR(B_STS));
        #define O_BLOCK(pp, ph0, ph1) do { \
            if ((AWAKE & 2) && !(pp)) mbar_wait_awake(BAR(B_KVT + (pp)), 0); else mbar_wait(BAR(B_KVT + (pp)), 0); \
            if (warp == 0) TS(25 + 3 * (pp)); \
            const uint32_t oa = T128(tid + (lds32(sb + OFF_CST) >> 16)); \
            float o0[20], o1[20]; \
            const uint32_t dk = (pp) ? desc_lo(sb + OFF_KL, OFF_Z + 32 - OFF_KL) : desc_lo(sb + OFF_KVT, OFF_Z - OFF_KVT); \
            constexpr uint32_t K1 = 256u - (255u << 16);          \
            wg_fence(); \
            mma40_rs0<0, H64>(o0, ph0, dk); mma40_rs0<K1, H64>(o1, ph1, dk); \
            mma40_rs<64, H64>(o0, ph0 + 4, dk); mma40_rs<K1 + 64, H64>(o1, ph1 + 4, dk); \
            mma40_rs<128, H64>(o0, ph0 + 8, dk); mma40_rs<K1 + 128, H64>(o1, ph1 + 8, dk); \
            mma40_rs<192, H64>(o0, ph0 + 12, dk); mma40_rs<K1 + 192, H64>(o1, ph1 + 12, dk); \
            wg_commit(); \
            wg_wait<0>(); \
            acc_fence(o0); acc_fence(o1); \
            if (warp == 0) TS(26 + 3 * (pp)); \
            if (!(pp)) mbar_wait(BAR(B_STS), 1);          \
            _Pragma("unroll") for (int hh = 0; hh < 2; hh++) { \
                const float (&o)[20] = hh ? o1 : o0; \
                uint32_t h0, l0, h1, l1; \
                split_rcp(rcp(rbf(rbf(o[16]) + 1e-6f)), h0, l0); split_rcp(rcp(rbf(rbf(o[18]) + 1e-6f)), h1, l1); \
                _Pragma("unroll") for (int q = 0; q < 2; q++) \
                    stsm4((oa ^ ((2 * hh + q) << 5)) + OFF_R0 + (pp) * 16384u, hdiv2(pack2(o[8 * q], o[8 * q + 1]), h0, l0), hdiv2(pack2(o[8 * q + 2], o[8 * q + 3]), h1, l1), \
                          hdiv2(pack2(o[8 * q + 4], o[8 * q + 5]), h0, l0), hdiv2(pack2(o[8 * q + 6], o[8 * q + 7]), h1, l1)); \
            } \
            fence_async_smem(); \
            __syncwarp(); \
            e_arrive(BAR(B_OWN + (pp))); \
            if (warp == 0) TS(27 + 3 * (pp)); \
        } while (0)
        float acc[64];
        const uint32_t da = desc_lo(sb + OFF_R0 + wgi * 8192u, 16), db = desc_lo(sb + OFF_DB, 8192);
        #define D_MMA(first, s) do { \
            wg_fence(); \
            first<(s) * 1024, H128, (s) * 1024, H128>(acc, da, db); mma128_ss<(s) * 1024 + 2, H128, (s) * 1024 + 128, H128>(acc, da, db); \
            mma128_ss<(s) * 1024 + 4, H128, (s) * 1024 + 256, H128>(acc, da, db); mma128_ss<(s) * 1024 + 6, H128, (s) * 1024 + 384, H128>(acc, da, db); \
            wg_commit(); } while (0)
        O_BLOCK(0, kq, (kq + 16));
        O_BLOCK(1, ph0, ph1);
        reg_inc<232>();
        mbar_wait(BAR(B_OWN), 0);
        mbar_wait(BAR(B_FD), 0);
        D_MMA(mma128_ss0, 0);
        mbar_wait(BAR(B_OWN + 1), 0);
        #undef PIN
        #undef O_BLOCK
        #define D_STEP(n) do { \
            mbar_wait(BAR(B_FD + ((n) & 3)), ((n) >> 2) & 1); \
            if (warp == 0) TR(112 + (n)); \
            D_MMA(mma128_ss, (n) & 3); \
            if ((n) == 3) mbar_wait(BAR(B_UF), 0); \
            if ((n) >= 3 && (n) < 7) { ldsm4t(uf[2 * (((n) + 5) & 7)], sb + OFF_F2 + fo + (((n) + 5) & 7) * 2048u); ldsm4t(uf[2 * (((n) + 5) & 7) + 1], sb + OFF_F2 + fo + (((n) + 5) & 7) * 2048u + 1024u); } \
            wg_wait<1>(); \
            if ((n) != 2) e_arrive(BAR(B_ED + (((n) + 3) & 3))); } while (0)
        D_STEP(1);
        wg_wait<0>();
        e_arrive(BAR(B_ED + 1));
        D_STEP(2);
        if (warp == 0) TS(31);
        D_STEP(3); D_STEP(4); D_STEP(5); D_STEP(6); D_STEP(7); D_STEP(8); D_STEP(9); D_STEP(10); D_STEP(11); D_STEP(12); D_STEP(13); D_STEP(14); D_STEP(15);
        #undef D_STEP
        #undef D_MMA
        #define XADDR(i) ((xa ^ (((i) & 3) << 5)) + ((i) < 4 ? OFF_R0 : OFF_X1))
        mbar_wait(BAR(B_PAR), 0);
        const uint4 cst = lds128(sb + OFF_CST);
        const int b = cst.x & 255;
        const uint32_t tag = cst.y, xa = T128(tid + (cst.x >> 16));
        uint4 w[4];
        const uint32_t rl = warp * 16 + g + 8 * (c & 1);
        const uint4* ws = pin_ptr(p.s->llln2 + ((b & ~7) + (c >> 1) * 4) * 128 + rl);
        {
        uint32_t x2[8][4];
        {
            mbar_wait(BAR(B_WPHI), 1); mbar_wait(BAR(B_FD), 0);
            #pragma unroll
            for (int i = 0; i < 8; i++) ldsm4(x2[i], XADDR(i));
            uint4* d = pin_ptr(p.s->llln2 + b * 128 + warp * 16 + g);
            const uint32_t ta = sb + OFF_T1 + (g & 1) * 512 + c * 16;
            uint4 t = lds128(ta), tn = lds128(ta + 64);
            wg_wait<0>();
            acc_fence(acc);
            e_arrive(BAR(B_ED + 3));
            if (warp == 0) TS(32);
            float sd[4] = {0.f, 0.f, 0.f, 0.f}, qa[4] = {0.f, 0.f, 0.f, 0.f}, qb[4] = {0.f, 0.f, 0.f, 0.f};
            #pragma unroll
            for (int i = 0; i < 8; i++) {
                x2[i][0] = hadd2(x2[i][0], hmul2(t.x, pack2(acc[8 * i], acc[8 * i + 1]))); x2[i][1] = hadd2(x2[i][1], hmul2(t.x, pack2(acc[8 * i + 2], acc[8 * i + 3])));
                x2[i][2] = hadd2(x2[i][2], hmul2(t.y, pack2(acc[8 * i + 4], acc[8 * i + 5]))); x2[i][3] = hadd2(x2[i][3], hmul2(t.y, pack2(acc[8 * i + 6], acc[8 * i + 7])));
                mma16816(sd, x2[i][0], x2[i][1], x2[i][2], x2[i][3], t.z, t.w);
                t = tn;
                if (i < 6) tn = lds128(ta + (i + 2) * 64);
                mma16816(qa, x2[i][0], x2[i][1], x2[i][2], x2[i][3], x2[i][0], x2[i][2]);
                mma16816(qb, x2[i][0], x2[i][1], x2[i][2], x2[i][3], x2[i][1], x2[i][3]);
            }
            if (c == (g >> 1)) {
                st_ll(d, f2u(sd[0]), f2u((g & 1) ? qa[1] : qa[0]), f2u(sd[1]), tag);
                st_ll(d + 8, f2u(sd[2]), f2u((g & 1) ? qb[3] : qb[2]), f2u(sd[3]), tag);
            }
            __syncwarp();
            #pragma unroll
            for (int i = 0; i < 4; i++) w[i] = ld_ll(ws + i * 128);
            if (warp == 0) TS(33);
            #pragma unroll
            for (int i = 0; i < 8; i++) stsm4(XADDR(i), x2[i][0], x2[i][1], x2[i][2], x2[i][3]);
        }
        uint4 t2[8]; uint2 t3[8];
        #pragma unroll
        for (int i = 0; i < 8; i++) { t2[i] = lds128(sb + OFF_T2 + i * 64 + c * 16); t3[i] = lds64(sb + OFF_T3 + i * 32 + c * 8); }
        mbar_wait(BAR(B_ED + 3), 1);
        {
            #pragma unroll 1
            for (int it = 0; it < POLL_MAX; it++) {
                if (__all_sync(0xffffffffu, !(tag_bad(w[0].w ^ tag, w[1].w, tag) | tag_bad(w[2].w ^ tag, w[3].w, tag)))) break;
                #pragma unroll
                for (int i = 0; i < 4; i++) if (w[i].w != tag) w[i] = ld_ll(ws + i * 128);
            }
            float s1 = (u2f(w[0].x) + u2f(w[1].x)) + (u2f(w[2].x) + u2f(w[3].x));
            float s2 = (u2f(w[0].y) + u2f(w[1].y)) + (u2f(w[2].y) + u2f(w[3].y));
            float dt = (u2f(w[0].z) + u2f(w[1].z)) + (u2f(w[2].z) + u2f(w[3].z));
            s1 += shfl_x(s1, 2); s2 += shfl_x(s2, 2); dt += shfl_x(dt, 2);
            uint32_t m2, rh, rl2; float rinv;
            ln_final(s1, s2, m2, rinv);
            const uint32_t key = (f2key(fmaf(fmaf(-bf_lo(m2), u2f(cst.z), dt), rinv, u2f(cst.w))) | 2047u) ^ ((b >> 3) * 128 + rl);
            split_rcp(rinv, rh, rl2);
            if (c < 2) { sts32(sb + OFF_KEY + rl * 4, key); sts128(sb + OFF_ST2 + rl * 16, make_uint4(m2, rh, rl2, 0)); }
            __syncwarp();
            e_arrive(BAR(B_KEYS));
        }
        if (warp == 0) TS(34);
        {
            const uint4 s0 = lds128(sb + OFF_ST2 + (warp * 16 + g) * 16), s1 = lds128(sb + OFF_ST2 + (warp * 16 + g + 8) * 16);
            const uint32_t oa = xa + warp * 2048u;
            #pragma unroll
            for (int i = 0; i < 8; i++) {
                const uint4 t = t2[i]; const uint2 gb = t3[i];
                stsm4((oa ^ ((i & 3) << 5)) + OFF_OUT + (i >> 2) * 2048u,
                      hadd2(x2[i][0], hmul2(gb.x, lnmod(x2[i][0], s0.x, s0.y, s0.z, t.x, t.z))), hadd2(x2[i][1], hmul2(gb.x, lnmod(x2[i][1], s1.x, s1.y, s1.z, t.x, t.z))),
                      hadd2(x2[i][2], hmul2(gb.y, lnmod(x2[i][2], s0.x, s0.y, s0.z, t.y, t.w))), hadd2(x2[i][3], hmul2(gb.y, lnmod(x2[i][3], s1.x, s1.y, s1.z, t.y, t.w))));
            }
            __syncwarp();
            e_arrive(BAR(B_SWP));
        }
        }
        #undef XADDR
        if (warp == 0) TS(35);
        uint32_t fx = 0, fh = 0, fg = 0, fs2, frow;
        uint32_t df[16][4];
        const uint32_t dfo = sb + ((lane & 7) + (lane >> 4) * 8) * 128u + ((((lane >> 3) & 1) ^ (lane & 7)) << 4);
        #define DF_LOAD(i) ldsm4t(df[i], (dfo + ((i) < 8 ? OFF_F2 + (warp >> 1) * 16384u + (warp & 1) * 4096u : OFF_DB + warp * 4096u) + ((i) & 1) * 2048u) ^ ((((i) >> 1) & 3) << 5))
        {
            const uint4* rh = pin_ptr(p.s->llrowh + tid);
            #pragma unroll
            for (int i = 8; i < 16; i++) ldsm4t(uf[i], sb + OFF_F2 + fo + i * 1024u);
            mbar_wait(BAR(B_SEL) + ((AWAKE & 4) ? awake_zero() : 0), 0);
            const uint2 bb = lds64(sb + OFF_CST + 24);
            const uint32_t b0 = bb.x, b1 = bb.y;
            if (warp == 0) TS(36);
            const uint32_t o0 = (~b0 & 0x780u) * 4, o1 = (~b1 & 0x780u) * 4, slot0 = o0, slot1 = o1 + (o0 == o1 ? 256 : 0);
            const int wd = ((g & 1) ? slot1 : slot0) + b * 2 + (c >> 1) - tid;
            uint4 hv[2], fv[2];
            #pragma unroll 1
            for (int it = 0; it < POLL_MAX; it++) {
                hv[0] = ld_ll(rh + slot0); hv[1] = ld_ll(rh + slot1);
                uint32_t bad = 0;
                if (warp == 0) {
                    fv[0] = ld_ll(rh + wd + 8192); fv[1] = ld_ll(rh + wd);
                    bad = tag_bad(fv[0].w ^ tag, fv[1].w, tag);
                    fx = (g & 2) ? fv[0].y : fv[0].x; fh = (g & 2) ? fv[1].y : fv[1].x; fg = (g & 2) ? fv[0].z : fv[1].z;
                }
                if (it == 0) {
                    mbar_wait(BAR(B_WD), 0);
                    #pragma unroll
                    for (int i = 0; i < NDF; i++) DF_LOAD(i);
                }
                if (__all_sync(0xffffffffu, !ll_bad<1>(ll_bad<1>(bad, hv[0], tag), hv[1], tag))) break;
            }
            const uint32_t ha = sb + OFF_HSEL + (tid >> 3) * 128u + c * 16u + (g & 1) * 8u;
            sts64(ha, hv[0].x, hv[0].y); sts64(ha + 64, hv[1].x, hv[1].y);
            bar_sync(2 + (warp >> 1), 64);
            const uint32_t bk = (g & 1) ? b1 : b0;
            frow = ~bk & 2047u;
            const float sg = sigmoid_f(rbf(key2f((bk & ~2047u) | 1024u)));
            fs2 = pack2(sg, sg);
        }
        if (warp == 0) TS(37);
        uint4* yd = p.s->lly + (cst.x >> 8) * 512 + (warp * 8 + c) * 8 + g;
        const uint4* ys = p.s->lly + (tid >> 2) * 512 + b * 4 + c;
        uint16_t* od = (uint16_t*)p.out + (size_t)frow * 1024 + (b >> 1) * 16 + (b & 1) * 4 + c + 8 * (g >> 1);
        {
            float ag[2][4], au[2][4];
            #pragma unroll
            for (int i = 0; i < 4; i++) ag[0][i] = ag[1][i] = au[0][i] = au[1][i] = 0.f;
            const uint32_t ha = sb + OFF_HSEL + (warp >> 1) * 1024u + (lane & 7) * 16u;
            uint4 hn = lds128(ha), hm = lds128(ha + 128);
            #pragma unroll
            for (int i = 0; i < 8; i++) {
                const uint4 h = hn;
                hn = hm;
                if (i < 6) hm = lds128(ha + (i + 2) * 128u);
                mma16816(ag[0], gf[2 * i][0], gf[2 * i][1], gf[2 * i][2], gf[2 * i][3], h.x, h.y);
                mma16816(au[0], uf[2 * i][0], uf[2 * i][1], uf[2 * i][2], uf[2 * i][3], h.x, h.y);
                mma16816(ag[1], gf[2 * i + 1][0], gf[2 * i + 1][1], gf[2 * i + 1][2], gf[2 * i + 1][3], h.z, h.w);
                mma16816(au[1], uf[2 * i + 1][0], uf[2 * i + 1][1], uf[2 * i + 1][2], uf[2 * i + 1][3], h.z, h.w);
                if (NDF + 2 * i < 16) { DF_LOAD((NDF + 2 * i) & 15); DF_LOAD((NDF + 2 * i + 1) & 15); }
            }
            sts64(sb + OFF_RED + (warp >> 1) * 512u + (c & 1) * 256u + ((warp & 1) * 16 + (c >> 1) * 8 + g) * 8u,
                  f2u(sel4(c, ag[0][0], ag[0][1], ag[0][2], ag[0][3]) + sel4(c, ag[1][0], ag[1][1], ag[1][2], ag[1][3])),
                  f2u(sel4(c, au[0][0], au[0][1], au[0][2], au[0][3]) + sel4(c, au[1][0], au[1][1], au[1][2], au[1][3])));
        }
        yd = pin_ptr(yd); ys = pin_ptr(ys); od = pin_ptr(od); pin<1>(&fs2);
        bar_sync(1, 256);
        {
            const uint32_t ra = sb + OFF_RED + lane * 16u;
            const uint4 r0 = lds128(ra), r1 = lds128(ra + 512), r2 = lds128(ra + 1024), r3 = lds128(ra + 1536);
            #define F4(f) ((u2f(r0.f) + u2f(r1.f)) + (u2f(r2.f) + u2f(r3.f)))
            const uint32_t hid = hmul2(silu2(pack2(F4(x), F4(z))), pack2(F4(y), F4(w)));
            #undef F4
            if (warp == 0) TS(38);
            const int src = (g & 1) * 16 + c;
            const uint32_t b0 = __shfl_sync(0xffffffffu, hid, src), b1 = __shfl_sync(0xffffffffu, hid, src + 4), b2 = __shfl_sync(0xffffffffu, hid, src + 8), b3 = __shfl_sync(0xffffffffu, hid, src + 12);
            float y[8][4];
            #pragma unroll
            for (int i = 0; i < 8; i++) {
                y[i][0] = y[i][1] = y[i][2] = y[i][3] = 0.f;
                mma16816(y[i], df[2 * i][0], df[2 * i][1], df[2 * i][2], df[2 * i][3], b0, b1);
            }
            #pragma unroll
            for (int i = 0; i < 8; i++) mma16816(y[i], df[2 * i + 1][0], df[2 * i + 1][1], df[2 * i + 1][2], df[2 * i + 1][3], b2, b3);
            if (cst.x < 112 * 256) {
                #pragma unroll
                for (int h = 0; h < 2; h++) {
                    #define YS(e) sel4(c, y[4 * h][e], y[4 * h + 1][e], y[4 * h + 2][e], y[4 * h + 3][e])
                    st_ll4(yd + 32 * h, YS(0), YS(1), YS(2), YS(3), tag);
                    #undef YS
                }
            }
        }
        if (warp == 0) TS(39);
        if (warp < 7) {
            uint4 v[2];
            v[0].w = v[1].w = 0;
            spin_until(clk32() + YWAIT);
            #pragma unroll 1
            for (int it = 0; it < POLL_MAX; it++) {
                if ((v[0].w ^ tag) & 3) v[0] = ld_ll(ys);
                if ((v[1].w ^ tag) & 3) v[1] = ld_ll(ys + 56 * 512);
                if (__all_sync(0xffffffffu, !(tag_bad(v[0].w ^ tag, v[1].w, tag) & 3))) break;
            }
            float y0 = u2f(v[0].x) + u2f(v[1].x), y1 = u2f(v[0].y) + u2f(v[1].y), y2 = u2f(v[0].z) + u2f(v[1].z), y3 = u2f(v[0].w) + u2f(v[1].w);
            const bool g0 = g & 1, g1 = g & 2;
            const float k0 = (g0 ? y1 : y0) + shfl_x(g0 ? y0 : y1, 4), k1 = (g0 ? y3 : y2) + shfl_x(g0 ? y2 : y3, 4);
            const float y = (g1 ? k1 : k0) + shfl_x(g1 ? k0 : k1, 8);
            stsf(sb + OFF_RED2 + (lane & 15) * 64u + (lane >> 4) * 32u + warp * 4u, y);
            bar_sync(6, 224);
            if (tid < 16) {
                const uint32_t a = sb + OFF_RED2 + lane * 64u;
                const uint4 ya = lds128(a), yb = lds128(a + 16), yc = lds128(a + 32), ye = lds128(a + 48);
                const float s = (((u2f(ya.x) + u2f(ya.y)) + (u2f(ya.z) + u2f(ya.w))) + ((u2f(yb.x) + u2f(yb.y)) + u2f(yb.z)))
                              + (((u2f(yc.x) + u2f(yc.y)) + (u2f(yc.z) + u2f(yc.w))) + ((u2f(ye.x) + u2f(ye.y)) + u2f(ye.z)));
                const uint32_t o = hadd2(fx, hmul2(fg, hadd2(fh, hmul2(pack2(s, s), fs2))));
                *od = (c & 1) ? o >> 16 : o;
                if (b == 0 && tid == 0) p.s->done[0] = tag;
                TS(40);
            }
        }
    }
}

typedef CUresult (*EncodeFn)(CUtensorMap*, CUtensorMapDataType, cuuint32_t, void*, const cuuint64_t*, const cuuint64_t*, const cuuint32_t*,
                             const cuuint32_t*, CUtensorMapInterleave, CUtensorMapSwizzle, CUtensorMapL2promotion, CUtensorMapFloatOOBfill);

CUtensorMap make_map(EncodeFn enc, const void* ptr, uint64_t cols, uint64_t rows, uint32_t bc, uint32_t br, CUtensorMapSwizzle swz, CUtensorMapL2promotion promo) {
    CUtensorMap m;
    cuuint64_t dims[2] = {cols, rows}, strides[1] = {cols * 2};
    cuuint32_t box[2] = {bc, br}, es[2] = {1, 1};
    enc(&m, CU_TENSOR_MAP_DATA_TYPE_BFLOAT16, 2, const_cast<void*>(ptr), dims, strides, box, es, CU_TENSOR_MAP_INTERLEAVE_NONE, swz, promo,
        CU_TENSOR_MAP_FLOAT_OOB_FILL_NONE);
    return m;
}
CUtensorMap make_map4(EncodeFn enc, const void* ptr, uint32_t groups, uint64_t rows, uint32_t br, CUtensorMapL2promotion promo) {
    CUtensorMap m;
    cuuint64_t dims[4] = {64, rows, 16, groups}, strides[3] = {groups * 2048ull, 128, 2048};
    cuuint32_t box[4] = {64, br, 2, groups}, es[4] = {1, 1, 1, 1};
    enc(&m, CU_TENSOR_MAP_DATA_TYPE_BFLOAT16, 4, const_cast<void*>(ptr), dims, strides, box, es, CU_TENSOR_MAP_INTERLEAVE_NONE, CU_TENSOR_MAP_SWIZZLE_128B, promo,
        CU_TENSOR_MAP_FLOAT_OOB_FILL_NONE);
    return m;
}

}

extern "C" void kernel_launch(void* const* d_in, const int* in_sizes, int n_in, void* d_out, int out_size) {
    (void)in_sizes; (void)n_in; (void)out_size;
    void* fn = nullptr; cudaDriverEntryPointQueryResult qr;
    cudaGetDriverEntryPoint("cuTensorMapEncodeTiled", &fn, cudaEnableDefault, &qr);
    EncodeFn enc = (EncodeFn)fn;
    void* hs = nullptr;
    cudaGetSymbolAddress(&hs, g_scratch);
    int dev = 0, sms = 0;
    cudaGetDevice(&dev);
    cudaDeviceGetAttribute(&sms, cudaDevAttrMultiProcessorCount, dev);
    const CUtensorMapL2promotion P256 = CU_TENSOR_MAP_L2_PROMOTION_L2_256B, P128 = CU_TENSOR_MAP_L2_PROMOTION_L2_128B, P0 = CU_TENSOR_MAP_L2_PROMOTION_NONE;
    CUtensorMap tmW = make_map4(enc, d_in[1], 3, 1024, 32, P256);
    CUtensorMap tmWo = make_map4(enc, d_in[3], 1, 1024, 64, P256);
    CUtensorMap tmO = make_map4(enc, d_out, 1, 2048, 16, P0);
    CUtensorMap tmPhi = make_map(enc, d_in[2], 32, 1024, 32, 128, CU_TENSOR_MAP_SWIZZLE_64B, P128);
    CUtensorMap tmG = make_map(enc, d_in[6], 3584, 1024, 32, 128, CU_TENSOR_MAP_SWIZZLE_64B, P0);
    CUtensorMap tmU = make_map(enc, d_in[7], 3584, 1024, 32, 128, CU_TENSOR_MAP_SWIZZLE_64B, P0);
    CUtensorMap tmD = make_map(enc, d_in[8], 1024, 3584, 64, 32, CU_TENSOR_MAP_SWIZZLE_128B, P128);
    CUtensorMap tmX = make_map(enc, d_in[0], 1024, 2048, 64, 128, CU_TENSOR_MAP_SWIZZLE_128B, P128);
    CUtensorMap tmM = make_map(enc, d_in[10], 6144, 1024, 64, 256, CU_TENSOR_MAP_SWIZZLE_128B, MPROMO);
    Ptrs p;
    p.x = (const bf16*)d_in[0]; p.c = (const bf16*)d_in[9]; p.wmod = (const bf16*)d_in[10]; p.wr = (const bf16*)d_in[5];
    p.wg = (const bf16*)d_in[6]; p.wu = (const bf16*)d_in[7]; p.wd = (const bf16*)d_in[8]; p.out = (bf16*)d_out; p.s = (Scratch*)hs;
    p.wqkv = (const bf16*)d_in[1]; p.wo = (const bf16*)d_in[3];
    p.by_sm = sms == 132;
    for (int sm = 0; sm < 132; sm++) {
        const int tp = sm >> 1, u = tp - 32;
        const int gp = (GPERM >> (4 * (tp < 32 ? tp & 7 : tp < 60 ? 1 + u % 7 : 0))) & 7, sl = 2 * (tp < 32 ? tp >> 3 : tp < 60 ? 4 + u / 7 : tp - 58) + (sm & 1);
        const int b = (tp >> 1) == 30 ? sm + 8 : ((gp >> 1) * 4 + (sl & 3)) * 8 + (gp & 1) * 4 + (sl >> 2);
        const int f = FMODE == 0 ? (b < 112 ? b : 255) : FMODE == 1 ? (sl < 14 && b < 128 ? gp * 14 + sl : 255) : (sm < 112 ? sm : 255);
        p.role[sm] = (uint16_t)(b | f << 8);
    }
    cudaFuncSetAttribute(fused_kernel, cudaFuncAttributeMaxDynamicSharedMemorySize, SMEM_BYTES);
    fused_kernel<<<132, NTHREADS, SMEM_BYTES, cudaStreamPerThread>>>(p, tmM, tmX, tmW, tmWo, tmPhi, tmG, tmU, tmD, tmO);
}
```

```cpp
#include <cuda_runtime.h>
#include <cuda.h>
#include <cuda_bf16.h>
#include <stdint.h>

namespace {

typedef __nv_bfloat16 bf16;

#define NFREE 4
constexpr int NTHREADS = 512;
constexpr int POLL_MAX = 400000;

constexpr uint32_t OFF_R0   = 0;
constexpr uint32_t OFF_A    = 65536;
constexpr uint32_t OFF_B    = 114688;
constexpr uint32_t OFF_V    = 65536;
constexpr uint32_t OFF_PHI  = 98304;
constexpr uint32_t OFF_F2   = 65536;
constexpr uint32_t OFF_DB   = 131072;
constexpr uint32_t OFF_KL   = 196608;
constexpr uint32_t OFF_WPHI = 214016;
constexpr uint32_t OFF_KVT  = OFF_WPHI;
constexpr uint32_t OFF_Z    = 222208;
constexpr uint32_t OFF_TAB  = OFF_Z;
constexpr uint32_t OFF_ONES = 226304;
constexpr uint32_t OFF_BAR  = 227328;
constexpr uint32_t OFF_CST  = OFF_BAR + 640;
constexpr uint32_t OFF_T1   = OFF_ONES;
constexpr uint32_t OFF_T2   = OFF_CST + 64;
constexpr uint32_t OFF_T3   = OFF_T2 + 512;
constexpr uint32_t OFF_KEY  = OFF_T3 + 256;
constexpr uint32_t OFF_ST2  = OFF_KEY + 512;
constexpr uint32_t OFF_ZS   = OFF_ST2;
constexpr uint32_t SMEM_BYTES = 232448;
constexpr uint32_t OFF_X1   = OFF_KL;
constexpr uint32_t OFF_OUT  = OFF_R0 + 32768;
constexpr uint32_t OFF_HSEL = OFF_WPHI;
constexpr uint32_t OFF_RED  = OFF_WPHI + 4096;
constexpr uint32_t OFF_RED2 = OFF_RED + 2048;
static_assert(OFF_ST2 + 2048 <= SMEM_BYTES, "layout");

enum {
    B_O1 = 0, B_UF = 1, B_UD = 2, B_WPHI = 3, B_FB = 4  , B_OST = 8, B_GF = 9, B_WD = 10, B_KVL = 11  , B_KZ = 13, B_LMF = 14, B_SEL = 15, B_XP = 16  , B_TAG = 24,
    B_FA = 25  , B_FD = 30  , B_CAND = 34,
    B_PE = 35  , B_KST = 37  , B_KVT = 41  , B_LMD = 43, B_PAR = 44,
    B_EA = 45  , B_EB = 48  , B_ED = 52  , B_PF = 56  , B_OWN = 60  , B_QE = 62, B_STP = 63, B_KEYS = 64, B_SWP = 65, B_STS = 66, B_GE = 67
};

struct Scratch {
    uint4 os[16 * 16 * 1024];
    uint4 kvacc[8 * 4 * 528];
    uint4 flk[3 * 128 * 2];
    uint4 llstat[2048];
    uint4 llm1[16 * 64];
    uint4 flo[16 * 16 * 2];
    uint4 llmod2[2 * 256];
    uint4 llg[2 * 4 * 256];
    uint4 llln2[16 * 8 * 128];
    uint4 llcand[16 * 2];
    uint4 llrowh[32 * 256];
    uint4 llrowx[32 * 256];
    uint4 lly[128 * 512];
    unsigned done[4];
};
__device__ __align__(1024) Scratch g_scratch;
#define GT(i) do {} while (0)
#define TS(i) do {} while (0)
#define TR(i) do {} while (0)

__device__ __forceinline__ uint32_t smem_u32(const void* p) { return (uint32_t)__cvta_generic_to_shared(p); }
__device__ __forceinline__ uint32_t clk32() { uint32_t c; asm volatile("mov.u32 %0, %%clock;" : "=r"(c) :: "memory"); return c; }
__device__ __forceinline__ void spin_until(uint32_t t) { while ((int)(clk32() - t) < 0) {} }
__device__ __forceinline__ void sleep_until(uint32_t t) { while ((int)(clk32() - t) < 0) __nanosleep(40); }
__device__ __forceinline__ void mbar_init_fence() { asm volatile("fence.mbarrier_init.release.cluster;" ::: "memory"); }
__device__ __forceinline__ void mbar_wait(uint32_t bar, uint32_t parity) {
    asm volatile("{\n.reg .pred P1;\nLAB_WAIT:\nmbarrier.try_wait.parity.shared::cta.b64 P1, [%0], %1;\n@!P1 bra LAB_WAIT;\n}" :: "r"(bar), "r"(parity) : "memory");
}
__device__ __forceinline__ uint64_t policy_evict_first() { uint64_t p; asm("createpolicy.fractional.L2::evict_first.b64 %0, 1.0;" : "=l"(p)); return p; }
#define ELECT "{\n.reg .pred e;\nelect.sync _|e, 0xffffffff;\n@e "
__device__ __forceinline__ void e_arrive(uint32_t bar) { asm volatile(ELECT "mbarrier.arrive.shared::cta.b64 _, [%0];\n}" :: "r"(bar) : "memory"); }
__device__ __forceinline__ void e_arrive_tx(uint32_t bar, uint32_t bytes) { asm volatile(ELECT "mbarrier.arrive.expect_tx.shared::cta.b64 _, [%0], %1;\n}" :: "r"(bar), "r"(bytes) : "memory"); }
__device__ __forceinline__ void e_init(uint32_t bar, uint32_t cnt) { asm volatile(ELECT "mbarrier.init.shared::cta.b64 [%0], %1;\n}" :: "r"(bar), "r"(cnt) : "memory"); }
__device__ __forceinline__ void tma_load_ef(uint32_t dst, const CUtensorMap* tm, int c0, int c1, uint32_t bar) {
    asm volatile(ELECT "cp.async.bulk.tensor.2d.shared::cluster.global.mbarrier::complete_tx::bytes.L2::cache_hint [%0], [%1, {%3, %4}], [%2], %5;\n}"
        :: "r"(dst), "l"(tm), "r"(bar), "r"(c0), "r"(c1), "l"(policy_evict_first()) : "memory");
}
__device__ __forceinline__ void tma_load(uint32_t dst, const CUtensorMap* tm, int c0, int c1, uint32_t bar) {
    asm volatile(ELECT "cp.async.bulk.tensor.2d.shared::cluster.global.mbarrier::complete_tx::bytes [%0], [%1, {%3, %4}], [%2];\n}"
        :: "r"(dst), "l"(tm), "r"(bar), "r"(c0), "r"(c1) : "memory");
}
__device__ __forceinline__ void tma_load4(uint32_t dst, const CUtensorMap* tm, int row, int blk, uint32_t bar) {
    asm volatile(ELECT "cp.async.bulk.tensor.4d.shared::cluster.global.mbarrier::complete_tx::bytes [%0], [%1, {0, %3, %4, 0}], [%2];\n}"
        :: "r"(dst), "l"(tm), "r"(bar), "r"(row), "r"(blk) : "memory");
}
__device__ __forceinline__ void tma_store4(const CUtensorMap* tm, int row, int blk, uint32_t src) {
    asm volatile(ELECT "cp.async.bulk.tensor.4d.global.shared::cta.bulk_group [%0, {0, %2, %3, 0}], [%1];\n}" :: "l"(tm), "r"(src), "r"(row), "r"(blk) : "memory");
}
__device__ __forceinline__ void bulk_load(uint32_t dst, const void* src, uint32_t bytes, uint32_t bar) {
    asm volatile(ELECT "cp.async.bulk.shared::cluster.global.mbarrier::complete_tx::bytes [%0], [%1], %2, [%3];\n}" :: "r"(dst), "l"(src), "r"(bytes), "r"(bar) : "memory");
}
__device__ __forceinline__ void bulk_store(void* dst, uint32_t src, uint32_t bytes) {
    asm volatile(ELECT "cp.async.bulk.global.shared::cta.bulk_group [%0], [%1], %2;\n}" :: "l"(dst), "r"(src), "r"(bytes) : "memory");
}
__device__ __forceinline__ void bulk_reduce(void* dst, uint32_t src, uint32_t bytes) {
    asm volatile(ELECT "cp.reduce.async.bulk.global.shared::cta.bulk_group.add.f32 [%0], [%1], %2;\n}" :: "l"(dst), "r"(src), "r"(bytes) : "memory");
}
__device__ __forceinline__ void tma_prefetch(const CUtensorMap* tm, int c0, int c1) {
    asm volatile(ELECT "cp.async.bulk.prefetch.tensor.2d.L2.global [%0, {%1, %2}];\n}" :: "l"(tm), "r"(c0), "r"(c1) : "memory");
}
__device__ __forceinline__ void l2_prefetch(const void* p, uint32_t bytes) {
    asm volatile(ELECT "cp.async.bulk.prefetch.L2.global [%0], %1;\n}" :: "l"(p), "r"(bytes) : "memory");
}
__device__ __forceinline__ void bulk_wait_read() { asm volatile("cp.async.bulk.commit_group;\ncp.async.bulk.wait_group.read 0;" ::: "memory"); }
__device__ __forceinline__ void bulk_wait() { asm volatile("cp.async.bulk.commit_group;\ncp.async.bulk.wait_group 0;" ::: "memory"); }
__device__ __forceinline__ void tmap_prefetch(const CUtensorMap* tm) { asm volatile("prefetch.tensormap [%0];" :: "l"(tm) : "memory"); }
__device__ __forceinline__ void wg_fence() { asm volatile("wgmma.fence.sync.aligned;" ::: "memory"); }
__device__ __forceinline__ void wg_commit() { asm volatile("wgmma.commit_group.sync.aligned;" ::: "memory"); }
template<int N> __device__ __forceinline__ void wg_wait() { asm volatile("wgmma.wait_group.sync.aligned %0;" :: "n"(N) : "memory"); }
template<int N> __device__ __forceinline__ void acc_fence(float (&d)[N]) {
    #pragma unroll
    for (int i = 0; i < N; i++) asm volatile("" : "+f"(d[i]) :: "memory");
}
__device__ __forceinline__ uint32_t desc_lo(uint32_t addr, uint32_t lbo) { return (addr >> 4) | ((lbo >> 4) << 16); }
constexpr uint32_t H128 = 0x40000040u;
constexpr uint32_t H64 = 0x80000020u;
__device__ __forceinline__ void fence_async_smem() { asm volatile("fence.proxy.async.shared::cta;" ::: "memory"); }
__device__ __forceinline__ void bar_sync(int id, int n) { asm volatile("bar.sync %0, %1;" :: "r"(id), "r"(n) : "memory"); }
template<int R> __device__ __forceinline__ void reg_inc() { asm volatile("setmaxnreg.inc.sync.aligned.u32 %0;" :: "n"(R)); }
template<int R> __device__ __forceinline__ void reg_dec() { asm volatile("setmaxnreg.dec.sync.aligned.u32 %0;" :: "n"(R)); }

__device__ __forceinline__ void stsm4(uint32_t addr, uint32_t r0, uint32_t r1, uint32_t r2, uint32_t r3) {
    asm volatile("stmatrix.sync.aligned.m8n8.x4.shared.b16 [%0], {%1,%2,%3,%4};" :: "r"(addr), "r"(r0), "r"(r1), "r"(r2), "r"(r3) : "memory");
}
__device__ __forceinline__ void ldsm4(uint32_t* r, uint32_t addr) {
    asm volatile("ldmatrix.sync.aligned.m8n8.x4.shared.b16 {%0,%1,%2,%3}, [%4];" : "=r"(r[0]), "=r"(r[1]), "=r"(r[2]), "=r"(r[3]) : "r"(addr) : "memory");
}
__device__ __forceinline__ void ldsm4t(uint32_t* r, uint32_t addr) {
    asm volatile("ldmatrix.sync.aligned.m8n8.x4.trans.shared.b16 {%0,%1,%2,%3}, [%4];" : "=r"(r[0]), "=r"(r[1]), "=r"(r[2]), "=r"(r[3]) : "r"(addr) : "memory");
}
__device__ __forceinline__ void mma16816(float (&d)[4], uint32_t a0, uint32_t a1, uint32_t a2, uint32_t a3, uint32_t b0, uint32_t b1) {
    asm volatile("mma.sync.aligned.m16n8k16.row.col.f32.bf16.bf16.f32 {%0,%1,%2,%3}, {%4,%5,%6,%7}, {%8,%9}, {%0,%1,%2,%3};"
        : "+f"(d[0]), "+f"(d[1]), "+f"(d[2]), "+f"(d[3]) : "r"(a0), "r"(a1), "r"(a2), "r"(a3), "r"(b0), "r"(b1));
}
__device__ __forceinline__ uint32_t awake_zero() {
    uint32_t r;
    asm volatile("{\n.reg .f32 d<4>;\nmma.sync.aligned.m16n8k8.row.col.f32.bf16.bf16.f32 {d0,d1,d2,d3}, {%1,%1}, {%1}, {%2,%2,%2,%2};\nmov.b32 %0, d0;\n}" : "=r"(r) : "r"(0), "f"(0.f));
    return r;
}
__device__ __forceinline__ void mbar_wait_awake(uint32_t bar, uint32_t parity) {
    #pragma unroll 1
    for (int it = 0; it < POLL_MAX; it++) {
        uint32_t ok;
        asm volatile("{\n.reg .pred p;\nmbarrier.try_wait.parity.shared::cta.b64 p, [%1], %2;\nselp.u32 %0, 0, 1, p;\n}" : "=r"(ok) : "r"(bar), "r"(parity) : "memory");
        if (__all_sync(0xffffffffu, ok == 0)) break;
        it += awake_zero();
    }
}
__device__ __forceinline__ uint4 lds128(uint32_t a) { uint4 v; asm volatile("ld.shared.v4.b32 {%0,%1,%2,%3}, [%4];" : "=r"(v.x), "=r"(v.y), "=r"(v.z), "=r"(v.w) : "r"(a) : "memory"); return v; }
__device__ __forceinline__ uint32_t lds32(uint32_t a) { uint32_t v; asm volatile("ld.shared.b32 %0, [%1];" : "=r"(v) : "r"(a) : "memory"); return v; }
__device__ __forceinline__ uint2 lds64(uint32_t a) { uint2 v; asm volatile("ld.shared.v2.b32 {%0,%1}, [%2];" : "=r"(v.x), "=r"(v.y) : "r"(a) : "memory"); return v; }
__device__ __forceinline__ float ldsf(uint32_t a) { float v; asm volatile("ld.shared.f32 %0, [%1];" : "=f"(v) : "r"(a) : "memory"); return v; }
__device__ __forceinline__ void sts128(uint32_t a, uint4 v) { asm volatile("st.shared.v4.b32 [%0], {%1,%2,%3,%4};" :: "r"(a), "r"(v.x), "r"(v.y), "r"(v.z), "r"(v.w) : "memory"); }
__device__ __forceinline__ void sts64(uint32_t a, uint32_t x, uint32_t y) { asm volatile("st.shared.v2.b32 [%0], {%1,%2};" :: "r"(a), "r"(x), "r"(y) : "memory"); }
__device__ __forceinline__ void sts32(uint32_t a, uint32_t x) { asm volatile("st.shared.b32 [%0], %1;" :: "r"(a), "r"(x) : "memory"); }
__device__ __forceinline__ void stsf(uint32_t a, float x) { asm volatile("st.shared.f32 [%0], %1;" :: "r"(a), "f"(x) : "memory"); }
__device__ __forceinline__ float u2f(uint32_t v) { return __uint_as_float(v); }
__device__ __forceinline__ uint32_t f2u(float v) { return __float_as_uint(v); }

__device__ __forceinline__ uint32_t ldg32(const void* p) { uint32_t v; asm volatile("ld.global.nc.b32 %0, [%1];" : "=r"(v) : "l"(p)); return v; }
__device__ __forceinline__ void stg128(void* p, uint4 v) { asm volatile("st.global.v4.b32 [%0], {%1,%2,%3,%4};" :: "l"(p), "r"(v.x), "r"(v.y), "r"(v.z), "r"(v.w) : "memory"); }
__device__ __forceinline__ void stg_zero(void* p) { stg128(p, make_uint4(0, 0, 0, 0)); }
__device__ __forceinline__ void fence_gpu() { asm volatile("fence.acq_rel.gpu;" ::: "memory"); }
__device__ __forceinline__ void st_ll(uint4* p, uint32_t x, uint32_t y, uint32_t z, uint32_t w) {
    asm volatile("st.relaxed.gpu.global.v4.b32 [%0], {%1,%2,%3,%4};" :: "l"(p), "r"(x), "r"(y), "r"(z), "r"(w) : "memory");
}
__device__ __forceinline__ uint4 ld_ll(const uint4* p) {
    uint4 v;
    asm volatile("ld.relaxed.gpu.global.v4.b32 {%0,%1,%2,%3}, [%4];" : "=r"(v.x), "=r"(v.y), "=r"(v.z), "=r"(v.w) : "l"(p) : "memory");
    return v;
}
template<uint32_t LUT> __device__ __forceinline__ uint32_t lop3(uint32_t a, uint32_t b, uint32_t c) { uint32_t d; asm("lop3.b32 %0, %1, %2, %3, %4;" : "=r"(d) : "r"(a), "r"(b), "r"(c), "n"(LUT)); return d; }
__device__ __forceinline__ uint32_t tag_bad(uint32_t bad, uint32_t w, uint32_t tag) { return lop3<0xF6>(bad, w, tag); }
__device__ __forceinline__ void st_ll4(uint4* p, float a, float b, float c, float d, uint32_t tag) { st_ll(p, f2u(a), f2u(b), f2u(c), lop3<0xD8>(f2u(d), tag, 3u)); }
__device__ __forceinline__ unsigned ld_rlx(const void* p) { unsigned v; asm volatile("ld.relaxed.gpu.global.u32 %0, [%1];" : "=r"(v) : "l"(p) : "memory"); return v; }
__device__ __forceinline__ void st_flag(uint4* p, uint32_t v, int lane) { if (lane < 2) st_ll(p + lane, v, v, v, v); }
__device__ __forceinline__ void poll_flags(const uint4* f, uint32_t tag) {
    unsigned v0 = ld_rlx(f), v1;
    spin_until(clk32() + 140);
    #pragma unroll 1
    for (int it = 0; it < POLL_MAX; it++) {
        v1 = ld_rlx(f);
        if (__all_sync(0xffffffffu, v0 == tag)) break;
        v0 = ld_rlx(f);
        if (__all_sync(0xffffffffu, v1 == tag)) break;
    }
}
template<int Z> __device__ __forceinline__ uint32_t ll_bad(uint32_t bad, const uint4& v, uint32_t tag) {
    bad = tag_bad(bad, v.w, tag);
    return Z && lop3<0x80>(v.x, v.y, v.z) == ~0u ? 1u : bad;
}
template<int N, int Z, uint32_t M = ~0u, int AW = 0> __device__ __forceinline__ void poll_words(uint4 (&v)[N], const uint4* p, int stride, uint32_t tag) {
    #pragma unroll 1
    for (int it = 0; it < POLL_MAX; it++) {
        uint32_t bad = 0;
        #pragma unroll
        for (int i = 0; i < N; i++) v[i] = ld_ll(p + i * stride);
        #pragma unroll
        for (int i = 0; i < N; i++) bad = ll_bad<Z>(bad, v[i], tag);
        if (__all_sync(0xffffffffu, !(bad & M))) break;
        if (AW) it += awake_zero();
    }
}
constexpr uint32_t ONE2 = 0x3F803F80u;
__device__ __forceinline__ uint32_t pack2(float lo, float hi) { uint32_t d; asm("cvt.rn.bf16x2.f32 %0, %1, %2;" : "=r"(d) : "f"(hi), "f"(lo)); return d; }
__device__ __forceinline__ float bf_lo(uint32_t v) { return u2f(v << 16); }
__device__ __forceinline__ float bf_hi(uint32_t v) { return u2f(v & 0xffff0000u); }
__device__ __forceinline__ float rbf(float x) { return bf_lo(pack2(x, 0.f)); }
__device__ __forceinline__ uint32_t hsub2(uint32_t a, uint32_t b) { uint32_t d; asm("sub.rn.bf16x2 %0, %1, %2;" : "=r"(d) : "r"(a), "r"(b)); return d; }
__device__ __forceinline__ uint32_t hadd2(uint32_t a, uint32_t b) { uint32_t d; asm("add.rn.bf16x2 %0, %1, %2;" : "=r"(d) : "r"(a), "r"(b)); return d; }
__device__ __forceinline__ uint32_t hmul2(uint32_t a, uint32_t b) { uint32_t d; asm("mul.rn.bf16x2 %0, %1, %2;" : "=r"(d) : "r"(a), "r"(b)); return d; }
__device__ __forceinline__ uint32_t hfma2(uint32_t a, uint32_t b, uint32_t c) { uint32_t d; asm("fma.rn.bf16x2 %0, %1, %2, %3;" : "=r"(d) : "r"(a), "r"(b), "r"(c)); return d; }
__device__ __forceinline__ uint32_t hmax2(uint32_t a, uint32_t b) { uint32_t d; asm("max.bf16x2 %0, %1, %2;" : "=r"(d) : "r"(a), "r"(b)); return d; }
__device__ __forceinline__ uint32_t hmin2(uint32_t a, uint32_t b) { uint32_t d; asm("min.bf16x2 %0, %1, %2;" : "=r"(d) : "r"(a), "r"(b)); return d; }
__device__ __forceinline__ float ex2(float x) { float y; asm("ex2.approx.ftz.f32 %0, %1;" : "=f"(y) : "f"(x)); return y; }
__device__ __forceinline__ float rcp(float x) { float y; asm("rcp.approx.ftz.f32 %0, %1;" : "=f"(y) : "f"(x)); return y; }
__device__ __forceinline__ float shfl_x(float v, int m) { return __shfl_xor_sync(0xffffffffu, v, m); }
__device__ __forceinline__ uint32_t hdiv2(uint32_t d, uint32_t rh, uint32_t rl) { return hfma2(d, rh, hmul2(d, rl)); }
__device__ __forceinline__ void split_rcp(float r, uint32_t& rh, uint32_t& rl) { rh = pack2(r, r); const float l = r - bf_lo(rh); rl = pack2(l, l); }
__device__ __forceinline__ uint32_t lnmod(uint32_t x, uint32_t m, uint32_t rh, uint32_t rl, uint32_t a, uint32_t s) { return hadd2(hmul2(hdiv2(hsub2(x, m), rh, rl), a), s); }
__device__ __forceinline__ void ln_final(float s1, float s2, uint32_t& m2, float& rinv) {
    const float mean = s1 * (1.0f / 1024.0f), var = fmaf(-mean, mean, s2 * (1.0f / 1024.0f));
    m2 = pack2(mean, mean);
    float sd;
    asm("sqrt.approx.ftz.f32 %0, %1;" : "=f"(sd) : "f"(rbf(rbf(fmaxf(var, 0.f)) + 1e-5f)));
    rinv = rcp(rbf(sd));
}
__device__ __forceinline__ float sigmoid_f(float x) { return rcp(1.0f + ex2(-1.4426950408889634f * x)); }
__device__ __forceinline__ uint32_t silu2(uint32_t v) { return pack2(bf_lo(v) * sigmoid_f(bf_lo(v)), bf_hi(v) * sigmoid_f(bf_hi(v))); }
__device__ __forceinline__ uint32_t f2key(float f) { uint32_t u = f2u(f); return (u & 0x80000000u) ? ~u : (u | 0x80000000u); }
__device__ __forceinline__ float key2f(uint32_t k) { return u2f((k & 0x80000000u) ? k ^ 0x80000000u : ~k); }
template<int N> __device__ __forceinline__ void top2(uint32_t (&k)[N], uint32_t& b0, uint32_t& b1) {
    uint32_t m = k[0];
    #pragma unroll
    for (int i = 1; i < N; i++) m = max(m, k[i]);
    b0 = __reduce_max_sync(0xffffffffu, m);
    m = 0;
    #pragma unroll
    for (int i = 0; i < N; i++) m = max(m, k[i] == b0 ? 0u : k[i]);
    b1 = __reduce_max_sync(0xffffffffu, m);
}
template<class T> __device__ __forceinline__ T sel4(int c, T a0, T a1, T a2, T a3) { return (c & 2) ? ((c & 1) ? a3 : a2) : ((c & 1) ? a1 : a0); }

__device__ __forceinline__ void fm_max(const float (&a)[16], uint32_t* p, uint32_t* mm) {
    #pragma unroll
    for (int i = 0; i < 8; i++) p[i] = pack2(a[2 * i], a[2 * i + 1]);
    #pragma unroll
    for (int h = 0; h < 2; h++) {
        const uint32_t mx = hmax2(hmax2(p[h], p[2 + h]), hmax2(p[4 + h], p[6 + h]));
        const uint32_t mn = hmin2(hmin2(p[h], p[2 + h]), hmin2(p[4 + h], p[6 + h])) ^ 0x80008000u;
        mm[h] = hmax2(__byte_perm(mx, mn, 0x5410), __byte_perm(mx, mn, 0x7632));
    }
    #pragma unroll
    for (int d = 1; d <= 2; d++) { mm[0] = hmax2(mm[0], __shfl_xor_sync(0xffffffffu, mm[0], d)); mm[1] = hmax2(mm[1], __shfl_xor_sync(0xffffffffu, mm[1], d)); }
}
constexpr float LOG2E = 1.4426950408889634f;
__device__ __forceinline__ void fm_pos(const uint32_t* p, const uint32_t* mm, float (&e)[32]) {
    #pragma unroll
    for (int h = 0; h < 2; h++) {
        const float cp = -bf_lo(mm[h]) * LOG2E;
        #pragma unroll
        for (int j = 0; j < 4; j++) {
            const float f0 = bf_lo(p[2 * j + h]), f1 = bf_hi(p[2 * j + h]);
            e[8 * h + 2 * j] = ex2(fmaf(f0, LOG2E, cp)); e[8 * h + 2 * j + 1] = ex2(fmaf(f1, LOG2E, cp));
            e[16 + 8 * h + 2 * j] = f0; e[16 + 8 * h + 2 * j + 1] = f1;
        }
    }
}
__device__ __forceinline__ void fm_neg(const uint32_t* mm, float nl, float (&e)[32]) {
    #pragma unroll
    for (int i = 16; i < 32; i++) e[i] = ex2(fmaf(e[i], -LOG2E, bf_hi(mm[(i >> 3) & 1]) * (i < 16 + NFREE ? -LOG2E : nl)));
}
__device__ __forceinline__ void fm_norm(const float (&e)[32], uint32_t* ph) {
    float s[4];
    #pragma unroll
    for (int k = 0; k < 4; k++) s[k] = ((e[8 * k] + e[8 * k + 1]) + (e[8 * k + 2] + e[8 * k + 3])) + ((e[8 * k + 4] + e[8 * k + 5]) + (e[8 * k + 6] + e[8 * k + 7]));
    #pragma unroll
    for (int k = 0; k < 4; k++) s[k] += shfl_x(s[k], 1);
    #pragma unroll
    for (int k = 0; k < 4; k++) s[k] = rcp(s[k] + shfl_x(s[k], 2));
    #pragma unroll
    for (int k = 0; k < 4; k++)
        #pragma unroll
        for (int j = 0; j < 4; j++) ph[8 * (k >> 1) + 2 * j + (k & 1)] = pack2(e[8 * k + 2 * j] * s[k], e[8 * k + 2 * j + 1] * s[k]);
}
template<class T> __device__ __forceinline__ T* pin_ptr(T* p) { asm volatile("" : "+l"(p) :: "memory"); return p; }
template<int N> __device__ __forceinline__ void pin(uint32_t* d) {
    #pragma unroll
    for (int i = 0; i < N; i++) asm volatile("" : "+r"(d[i]) :: "memory");
}

template<uint32_t BO, uint32_t BH> __device__ __forceinline__ void mma192_rs(float (&d)[96], const uint32_t* a, uint32_t blo) {
  asm volatile("{\n.reg .pred p;\n.reg .b32 ta, tb;\n.reg .b64 da, db;\nadd.u32 tb, %100, %101;\nmov.b64 db, {tb, %102};\nsetp.ne.b32 p, 1, 0;\n"
    "wgmma.mma_async.sync.aligned.m64n192k16.f32.bf16.bf16 {%0, %1, %2, %3, %4, %5, %6, %7, %8, %9, %10, %11, %12, %13, %14, %15, %16, %17, %18, %19, %20, %21, %22, %23, %24, %25, %26, %27, %28, %29, %30, %31, %32, %33, %34, %35, %36, %37, %38, %39, %40, %41, %42, %43, %44, %45, %46, %47, %48, %49, %50, %51, %52, %53, %54, %55, %56, %57, %58, %59, %60, %61, %62, %63, %64, %65, %66, %67, %68, %69, %70, %71, %72, %73, %74, %75, %76, %77, %78, %79, %80, %81, %82, %83, %84, %85, %86, %87, %88, %89, %90, %91, %92, %93, %94, %95}, {%96,%97,%98,%99}, db, p, 1, 1, 1;\n}\n"
    : "+f"(d[0]), "+f"(d[1]), "+f"(d[2]), "+f"(d[3]), "+f"(d[4]), "+f"(d[5]), "+f"(d[6]), "+f"(d[7]), "+f"(d[8]), "+f"(d[9]), "+f"(d[10]), "+f"(d[11]), "+f"(d[12]), "+f"(d[13]), "+f"(d[14]), "+f"(d[15]), "+f"(d[16]), "+f"(d[17]), "+f"(d[18]), "+f"(d[19]), "+f"(d[20]), "+f"(d[21]), "+f"(d[22]), "+f"(d[23]), "+f"(d[24]), "+f"(d[25]), "+f"(d[26]), "+f"(d[27]), "+f"(d[28]), "+f"(d[29]), "+f"(d[30]), "+f"(d[31]), "+f"(d[32]), "+f"(d[33]), "+f"(d[34]), "+f"(d[35]), "+f"(d[36]), "+f"(d[37]), "+f"(d[38]), "+f"(d[39]), "+f"(d[40]), "+f"(d[41]), "+f"(d[42]), "+f"(d[43]), "+f"(d[44]), "+f"(d[45]), "+f"(d[46]), "+f"(d[47]), "+f"(d[48]), "+f"(d[49]), "+f"(d[50]), "+f"(d[51]), "+f"(d[52]), "+f"(d[53]), "+f"(d[54]), "+f"(d[55]), "+f"(d[56]), "+f"(d[57]), "+f"(d[58]), "+f"(d[59]), "+f"(d[60]), "+f"(d[61]), "+f"(d[62]), "+f"(d[63]), "+f"(d[64]), "+f"(d[65]), "+f"(d[66]), "+f"(d[67]), "+f"(d[68]), "+f"(d[69]), "+f"(d[70]), "+f"(d[71]), "+f"(d[72]), "+f"(d[73]), "+f"(d[74]), "+f"(d[75]), "+f"(d[76]), "+f"(d[77]), "+f"(d[78]), "+f"(d[79]), "+f"(d[80]), "+f"(d[81]), "+f"(d[82]), "+f"(d[83]), "+f"(d[84]), "+f"(d[85]), "+f"(d[86]), "+f"(d[87]), "+f"(d[88]), "+f"(d[89]), "+f"(d[90]), "+f"(d[91]), "+f"(d[92]), "+f"(d[93]), "+f"(d[94]), "+f"(d[95])
    : "r"(a[0]), "r"(a[1]), "r"(a[2]), "r"(a[3]), "r"(blo), "n"(BO), "n"(BH));
}
template<uint32_t BO, uint32_t BH> __device__ __forceinline__ void mma192_rsp(float (&d)[96], const uint32_t* a, uint32_t blo, int sc) {
  asm volatile("{\n.reg .pred p;\n.reg .b32 ta, tb;\n.reg .b64 da, db;\nadd.u32 tb, %100, %101;\nmov.b64 db, {tb, %102};\nsetp.ne.b32 p, %103, 0;\n"
    "wgmma.mma_async.sync.aligned.m64n192k16.f32.bf16.bf16 {%0, %1, %2, %3, %4, %5, %6, %7, %8, %9, %10, %11, %12, %13, %14, %15, %16, %17, %18, %19, %20, %21, %22, %23, %24, %25, %26, %27, %28, %29, %30, %31, %32, %33, %34, %35, %36, %37, %38, %39, %40, %41, %42, %43, %44, %45, %46, %47, %48, %49, %50, %51, %52, %53, %54, %55, %56, %57, %58, %59, %60, %61, %62, %63, %64, %65, %66, %67, %68, %69, %70, %71, %72, %73, %74, %75, %76, %77, %78, %79, %80, %81, %82, %83, %84, %85, %86, %87, %88, %89, %90, %91, %92, %93, %94, %95}, {%96,%97,%98,%99}, db, p, 1, 1, 1;\n}\n"
    : "+f"(d[0]), "+f"(d[1]), "+f"(d[2]), "+f"(d[3]), "+f"(d[4]), "+f"(d[5]), "+f"(d[6]), "+f"(d[7]), "+f"(d[8]), "+f"(d[9]), "+f"(d[10]), "+f"(d[11]), "+f"(d[12]), "+f"(d[13]), "+f"(d[14]), "+f"(d[15]), "+f"(d[16]), "+f"(d[17]), "+f"(d[18]), "+f"(d[19]), "+f"(d[20]), "+f"(d[21]), "+f"(d[22]), "+f"(d[23]), "+f"(d[24]), "+f"(d[25]), "+f"(d[26]), "+f"(d[27]), "+f"(d[28]), "+f"(d[29]), "+f"(d[30]), "+f"(d[31]), "+f"(d[32]), "+f"(d[33]), "+f"(d[34]), "+f"(d[35]), "+f"(d[36]), "+f"(d[37]), "+f"(d[38]), "+f"(d[39]), "+f"(d[40]), "+f"(d[41]), "+f"(d[42]), "+f"(d[43]), "+f"(d[44]), "+f"(d[45]), "+f"(d[46]), "+f"(d[47]), "+f"(d[48]), "+f"(d[49]), "+f"(d[50]), "+f"(d[51]), "+f"(d[52]), "+f"(d[53]), "+f"(d[54]), "+f"(d[55]), "+f"(d[56]), "+f"(d[57]), "+f"(d[58]), "+f"(d[59]), "+f"(d[60]), "+f"(d[61]), "+f"(d[62]), "+f"(d[63]), "+f"(d[64]), "+f"(d[65]), "+f"(d[66]), "+f"(d[67]), "+f"(d[68]), "+f"(d[69]), "+f"(d[70]), "+f"(d[71]), "+f"(d[72]), "+f"(d[73]), "+f"(d[74]), "+f"(d[75]), "+f"(d[76]), "+f"(d[77]), "+f"(d[78]), "+f"(d[79]), "+f"(d[80]), "+f"(d[81]), "+f"(d[82]), "+f"(d[83]), "+f"(d[84]), "+f"(d[85]), "+f"(d[86]), "+f"(d[87]), "+f"(d[88]), "+f"(d[89]), "+f"(d[90]), "+f"(d[91]), "+f"(d[92]), "+f"(d[93]), "+f"(d[94]), "+f"(d[95])
    : "r"(a[0]), "r"(a[1]), "r"(a[2]), "r"(a[3]), "r"(blo), "n"(BO), "n"(BH), "r"(sc));
}
template<uint32_t BO, uint32_t BH> __device__ __forceinline__ void mma32_rs(float (&d)[16], const uint32_t* a, uint32_t blo) {
  asm volatile("{\n.reg .pred p;\n.reg .b32 ta, tb;\n.reg .b64 da, db;\nadd.u32 tb, %20, %21;\nmov.b64 db, {tb, %22};\nsetp.ne.b32 p, 1, 0;\n"
    "wgmma.mma_async.sync.aligned.m64n32k16.f32.bf16.bf16 {%0, %1, %2, %3, %4, %5, %6, %7, %8, %9, %10, %11, %12, %13, %14, %15}, {%16,%17,%18,%19}, db, p, 1, 1, 1;\n}\n"
    : "+f"(d[0]), "+f"(d[1]), "+f"(d[2]), "+f"(d[3]), "+f"(d[4]), "+f"(d[5]), "+f"(d[6]), "+f"(d[7]), "+f"(d[8]), "+f"(d[9]), "+f"(d[10]), "+f"(d[11]), "+f"(d[12]), "+f"(d[13]), "+f"(d[14]), "+f"(d[15])
    : "r"(a[0]), "r"(a[1]), "r"(a[2]), "r"(a[3]), "r"(blo), "n"(BO), "n"(BH));
}
template<uint32_t BO, uint32_t BH> __device__ __forceinline__ void mma32_rs0(float (&d)[16], const uint32_t* a, uint32_t blo) {
  asm volatile("{\n.reg .pred p;\n.reg .b32 ta, tb;\n.reg .b64 da, db;\nadd.u32 tb, %20, %21;\nmov.b64 db, {tb, %22};\nsetp.ne.b32 p, 0, 0;\n"
    "wgmma.mma_async.sync.aligned.m64n32k16.f32.bf16.bf16 {%0, %1, %2, %3, %4, %5, %6, %7, %8, %9, %10, %11, %12, %13, %14, %15}, {%16,%17,%18,%19}, db, p, 1, 1, 1;\n}\n"
    : "=f"(d[0]), "=f"(d[1]), "=f"(d[2]), "=f"(d[3]), "=f"(d[4]), "=f"(d[5]), "=f"(d[6]), "=f"(d[7]), "=f"(d[8]), "=f"(d[9]), "=f"(d[10]), "=f"(d[11]), "=f"(d[12]), "=f"(d[13]), "=f"(d[14]), "=f"(d[15])
    : "r"(a[0]), "r"(a[1]), "r"(a[2]), "r"(a[3]), "r"(blo), "n"(BO), "n"(BH));
}
template<uint32_t BO, uint32_t BH> __device__ __forceinline__ void mma40_rs(float (&d)[20], const uint32_t* a, uint32_t blo) {
  asm volatile("{\n.reg .pred p;\n.reg .b32 ta, tb;\n.reg .b64 da, db;\nadd.u32 tb, %24, %25;\nmov.b64 db, {tb, %26};\nsetp.ne.b32 p, 1, 0;\n"
    "wgmma.mma_async.sync.aligned.m64n40k16.f32.bf16.bf16 {%0, %1, %2, %3, %4, %5, %6, %7, %8, %9, %10, %11, %12, %13, %14, %15, %16, %17, %18, %19}, {%20,%21,%22,%23}, db, p, 1, 1, 1;\n}\n"
    : "+f"(d[0]), "+f"(d[1]), "+f"(d[2]), "+f"(d[3]), "+f"(d[4]), "+f"(d[5]), "+f"(d[6]), "+f"(d[7]), "+f"(d[8]), "+f"(d[9]), "+f"(d[10]), "+f"(d[11]), "+f"(d[12]), "+f"(d[13]), "+f"(d[14]), "+f"(d[15]), "+f"(d[16]), "+f"(d[17]), "+f"(d[18]), "+f"(d[19])
    : "r"(a[0]), "r"(a[1]), "r"(a[2]), "r"(a[3]), "r"(blo), "n"(BO), "n"(BH));
}
template<uint32_t BO, uint32_t BH> __device__ __forceinline__ void mma40_rs0(float (&d)[20], const uint32_t* a, uint32_t blo) {
  asm volatile("{\n.reg .pred p;\n.reg .b32 ta, tb;\n.reg .b64 da, db;\nadd.u32 tb, %24, %25;\nmov.b64 db, {tb, %26};\nsetp.ne.b32 p, 0, 0;\n"
    "wgmma.mma_async.sync.aligned.m64n40k16.f32.bf16.bf16 {%0, %1, %2, %3, %4, %5, %6, %7, %8, %9, %10, %11, %12, %13, %14, %15, %16, %17, %18, %19}, {%20,%21,%22,%23}, db, p, 1, 1, 1;\n}\n"
    : "=f"(d[0]), "=f"(d[1]), "=f"(d[2]), "=f"(d[3]), "=f"(d[4]), "=f"(d[5]), "=f"(d[6]), "=f"(d[7]), "=f"(d[8]), "=f"(d[9]), "=f"(d[10]), "=f"(d[11]), "=f"(d[12]), "=f"(d[13]), "=f"(d[14]), "=f"(d[15]), "=f"(d[16]), "=f"(d[17]), "=f"(d[18]), "=f"(d[19])
    : "r"(a[0]), "r"(a[1]), "r"(a[2]), "r"(a[3]), "r"(blo), "n"(BO), "n"(BH));
}
template<uint32_t AO, uint32_t AH, uint32_t BO, uint32_t BH> __device__ __forceinline__ void mma40_tt(float (&d)[20], uint32_t alo, uint32_t blo) {
  asm volatile("{\n.reg .pred p;\n.reg .b32 ta, tb;\n.reg .b64 da, db;\nadd.u32 ta, %20, %21;\nmov.b64 da, {ta, %22};\nadd.u32 tb, %23, %24;\nmov.b64 db, {tb, %25};\nsetp.ne.b32 p, 1, 0;\n"
    "wgmma.mma_async.sync.aligned.m64n40k16.f32.bf16.bf16 {%0, %1, %2, %3, %4, %5, %6, %7, %8, %9, %10, %11, %12, %13, %14, %15, %16, %17, %18, %19}, da, db, p, 1, 1, 1, 1;\n}\n"
    : "+f"(d[0]), "+f"(d[1]), "+f"(d[2]), "+f"(d[3]), "+f"(d[4]), "+f"(d[5]), "+f"(d[6]), "+f"(d[7]), "+f"(d[8]), "+f"(d[9]), "+f"(d[10]), "+f"(d[11]), "+f"(d[12]), "+f"(d[13]), "+f"(d[14]), "+f"(d[15]), "+f"(d[16]), "+f"(d[17]), "+f"(d[18]), "+f"(d[19])
    : "r"(alo), "n"(AO), "n"(AH), "r"(blo), "n"(BO), "n"(BH));
}
template<uint32_t AO, uint32_t AH, uint32_t BO, uint32_t BH> __device__ __forceinline__ void mma40_tt0(float (&d)[20], uint32_t alo, uint32_t blo) {
  asm volatile("{\n.reg .pred p;\n.reg .b32 ta, tb;\n.reg .b64 da, db;\nadd.u32 ta, %20, %21;\nmov.b64 da, {ta, %22};\nadd.u32 tb, %23, %24;\nmov.b64 db, {tb, %25};\nsetp.ne.b32 p, 0, 0;\n"
    "wgmma.mma_async.sync.aligned.m64n40k16.f32.bf16.bf16 {%0, %1, %2, %3, %4, %5, %6, %7, %8, %9, %10, %11, %12, %13, %14, %15, %16, %17, %18, %19}, da, db, p, 1, 1, 1, 1;\n}\n"
    : "=f"(d[0]), "=f"(d[1]), "=f"(d[2]), "=f"(d[3]), "=f"(d[4]), "=f"(d[5]), "=f"(d[6]), "=f"(d[7]), "=f"(d[8]), "=f"(d[9]), "=f"(d[10]), "=f"(d[11]), "=f"(d[12]), "=f"(d[13]), "=f"(d[14]), "=f"(d[15]), "=f"(d[16]), "=f"(d[17]), "=f"(d[18]), "=f"(d[19])
    : "r"(alo), "n"(AO), "n"(AH), "r"(blo), "n"(BO), "n"(BH));
}
template<uint32_t AO, uint32_t AH, uint32_t BO, uint32_t BH> __device__ __forceinline__ void mma8_tn(float (&d)[4], uint32_t alo, uint32_t blo) {
  asm volatile("{\n.reg .pred p;\n.reg .b32 ta, tb;\n.reg .b64 da, db;\nadd.u32 ta, %4, %5;\nmov.b64 da, {ta, %6};\nadd.u32 tb, %7, %8;\nmov.b64 db, {tb, %9};\nsetp.ne.b32 p, 1, 0;\n"
    "wgmma.mma_async.sync.aligned.m64n8k16.f32.bf16.bf16 {%0, %1, %2, %3}, da, db, p, 1, 1, 1, 0;\n}\n"
    : "+f"(d[0]), "+f"(d[1]), "+f"(d[2]), "+f"(d[3])
    : "r"(alo), "n"(AO), "n"(AH), "r"(blo), "n"(BO), "n"(BH));
}
template<uint32_t AO, uint32_t AH, uint32_t BO, uint32_t BH> __device__ __forceinline__ void mma8_tn0(float (&d)[4], uint32_t alo, uint32_t blo) {
  asm volatile("{\n.reg .pred p;\n.reg .b32 ta, tb;\n.reg .b64 da, db;\nadd.u32 ta, %4, %5;\nmov.b64 da, {ta, %6};\nadd.u32 tb, %7, %8;\nmov.b64 db, {tb, %9};\nsetp.ne.b32 p, 0, 0;\n"
    "wgmma.mma_async.sync.aligned.m64n8k16.f32.bf16.bf16 {%0, %1, %2, %3}, da, db, p, 1, 1, 1, 0;\n}\n"
    : "=f"(d[0]), "=f"(d[1]), "=f"(d[2]), "=f"(d[3])
    : "r"(alo), "n"(AO), "n"(AH), "r"(blo), "n"(BO), "n"(BH));
}
template<uint32_t AO, uint32_t AH, uint32_t BO, uint32_t BH> __device__ __forceinline__ void mma128_ss(float (&d)[64], uint32_t alo, uint32_t blo) {
  asm volatile("{\n.reg .pred p;\n.reg .b32 ta, tb;\n.reg .b64 da, db;\nadd.u32 ta, %64, %65;\nmov.b64 da, {ta, %66};\nadd.u32 tb, %67, %68;\nmov.b64 db, {tb, %69};\nsetp.ne.b32 p, 1, 0;\n"
    "wgmma.mma_async.sync.aligned.m64n128k16.f32.bf16.bf16 {%0, %1, %2, %3, %4, %5, %6, %7, %8, %9, %10, %11, %12, %13, %14, %15, %16, %17, %18, %19, %20, %21, %22, %23, %24, %25, %26, %27, %28, %29, %30, %31, %32, %33, %34, %35, %36, %37, %38, %39, %40, %41, %42, %43, %44, %45, %46, %47, %48, %49, %50, %51, %52, %53, %54, %55, %56, %57, %58, %59, %60, %61, %62, %63}, da, db, p, 1, 1, 0, 1;\n}\n"
    : "+f"(d[0]), "+f"(d[1]), "+f"(d[2]), "+f"(d[3]), "+f"(d[4]), "+f"(d[5]), "+f"(d[6]), "+f"(d[7]), "+f"(d[8]), "+f"(d[9]), "+f"(d[10]), "+f"(d[11]), "+f"(d[12]), "+f"(d[13]), "+f"(d[14]), "+f"(d[15]), "+f"(d[16]), "+f"(d[17]), "+f"(d[18]), "+f"(d[19]), "+f"(d[20]), "+f"(d[21]), "+f"(d[22]), "+f"(d[23]), "+f"(d[24]), "+f"(d[25]), "+f"(d[26]), "+f"(d[27]), "+f"(d[28]), "+f"(d[29]), "+f"(d[30]), "+f"(d[31]), "+f"(d[32]), "+f"(d[33]), "+f"(d[34]), "+f"(d[35]), "+f"(d[36]), "+f"(d[37]), "+f"(d[38]), "+f"(d[39]), "+f"(d[40]), "+f"(d[41]), "+f"(d[42]), "+f"(d[43]), "+f"(d[44]), "+f"(d[45]), "+f"(d[46]), "+f"(d[47]), "+f"(d[48]), "+f"(d[49]), "+f"(d[50]), "+f"(d[51]), "+f"(d[52]), "+f"(d[53]), "+f"(d[54]), "+f"(d[55]), "+f"(d[56]), "+f"(d[57]), "+f"(d[58]), "+f"(d[59]), "+f"(d[60]), "+f"(d[61]), "+f"(d[62]), "+f"(d[63])
    : "r"(alo), "n"(AO), "n"(AH), "r"(blo), "n"(BO), "n"(BH));
}
template<uint32_t AO, uint32_t AH, uint32_t BO, uint32_t BH> __device__ __forceinline__ void mma128_ss0(float (&d)[64], uint32_t alo, uint32_t blo) {
  asm volatile("{\n.reg .pred p;\n.reg .b32 ta, tb;\n.reg .b64 da, db;\nadd.u32 ta, %64, %65;\nmov.b64 da, {ta, %66};\nadd.u32 tb, %67, %68;\nmov.b64 db, {tb, %69};\nsetp.ne.b32 p, 0, 0;\n"
    "wgmma.mma_async.sync.aligned.m64n128k16.f32.bf16.bf16 {%0, %1, %2, %3, %4, %5, %6, %7, %8, %9, %10, %11, %12, %13, %14, %15, %16, %17, %18, %19, %20, %21, %22, %23, %24, %25, %26, %27, %28, %29, %30, %31, %32, %33, %34, %35, %36, %37, %38, %39, %40, %41, %42, %43, %44, %45, %46, %47, %48, %49, %50, %51, %52, %53, %54, %55, %56, %57, %58, %59, %60, %61, %62, %63}, da, db, p, 1, 1, 0, 1;\n}\n"
    : "=f"(d[0]), "=f"(d[1]), "=f"(d[2]), "=f"(d[3]), "=f"(d[4]), "=f"(d[5]), "=f"(d[6]), "=f"(d[7]), "=f"(d[8]), "=f"(d[9]), "=f"(d[10]), "=f"(d[11]), "=f"(d[12]), "=f"(d[13]), "=f"(d[14]), "=f"(d[15]), "=f"(d[16]), "=f"(d[17]), "=f"(d[18]), "=f"(d[19]), "=f"(d[20]), "=f"(d[21]), "=f"(d[22]), "=f"(d[23]), "=f"(d[24]), "=f"(d[25]), "=f"(d[26]), "=f"(d[27]), "=f"(d[28]), "=f"(d[29]), "=f"(d[30]), "=f"(d[31]), "=f"(d[32]), "=f"(d[33]), "=f"(d[34]), "=f"(d[35]), "=f"(d[36]), "=f"(d[37]), "=f"(d[38]), "=f"(d[39]), "=f"(d[40]), "=f"(d[41]), "=f"(d[42]), "=f"(d[43]), "=f"(d[44]), "=f"(d[45]), "=f"(d[46]), "=f"(d[47]), "=f"(d[48]), "=f"(d[49]), "=f"(d[50]), "=f"(d[51]), "=f"(d[52]), "=f"(d[53]), "=f"(d[54]), "=f"(d[55]), "=f"(d[56]), "=f"(d[57]), "=f"(d[58]), "=f"(d[59]), "=f"(d[60]), "=f"(d[61]), "=f"(d[62]), "=f"(d[63])
    : "r"(alo), "n"(AO), "n"(AH), "r"(blo), "n"(BO), "n"(BH));
}

#define XD 600
#define XSTEP 300
#define XPD 450
#define XPB 8192
#define SPG 5600
#define WL0 1800
#define WLS 350
#define NB0 2
#define WP1 2000
#define PF_START 5600
#define PFP 126
#define GPERM 0x76543210u
#define FMODE 1
#define NM0 3
#define PWAIT 600
#define AWAKE 3
#define O1H 2
#define NG1 8
#define X1E 0
#define WDW 3
#define WDGAP 300
#define YWAIT 500
#define OUTW 0
#define CWAIT 500
#define NDF 8
#define O0ALL 0
#define O1ALL 0
#define RDV 1
#define MSTEP 1200
#define MSLP 1000
#define MPOLL 3200
#define LMP 8
#define WD0 10
#define CLR0 22000
#define UPGAP 200
#define OUTGAP 150
#define MPROMO P128
#define MLOAD tma_load_ef
struct Ptrs { const bf16 *x, *wmod, *c, *wr, *wqkv; int by_sm; Scratch* s; const bf16 *wg, *wu, *wd, *wo; bf16* out; uint16_t role[132]; };

#define BAR(i) (sb + OFF_BAR + 8u * (i))

__device__ __forceinline__ uint32_t get_tag(uint32_t sb) { mbar_wait(BAR(B_TAG), 0); const uint32_t d = __shfl_sync(0xffffffffu, lds32(sb + OFF_CST + 32), 0); return d + 1 + (d & 2); }
__device__ __forceinline__ int d_kb(int n, int hg) {
    if (n < 2) return 2 * hg + n;
    const int h = n >= 9, q = n - 2 - 7 * h;
    return 2 * (q + (q >= hg)) + h;
}

__global__ void __launch_bounds__(NTHREADS, 1)
fused_kernel(const Ptrs p, const __grid_constant__ CUtensorMap tmM, const __grid_constant__ CUtensorMap tmX, const __grid_constant__ CUtensorMap tmW,
             const __grid_constant__ CUtensorMap tmWo, const __grid_constant__ CUtensorMap tmPhi, const __grid_constant__ CUtensorMap tmG,
             const __grid_constant__ CUtensorMap tmU, const __grid_constant__ CUtensorMap tmD, const __grid_constant__ CUtensorMap tmO)
{
    extern __shared__ __align__(1024) uint8_t smem_raw[];
    const uint32_t sb = smem_u32(smem_raw);
    const uint32_t cstart = __shfl_sync(0xffffffffu, clk32(), 0);
    const int tid = threadIdx.x, lane = tid & 31, warp = __shfl_sync(0xffffffffu, tid >> 5, 0);
    if (blockIdx.x < 128) {
        if (warp == 8) asm volatile("prefetch.global.L2 [%0];" :: "l"(p.wmod + (size_t)(blockIdx.x * 8 + (lane >> 2)) * 6144 + (lane & 1) * 64 + (lane & 2) * 512));
        if (warp == 13 && (lane & 1) < NM0 - 2) asm volatile("prefetch.global.L2 [%0];" :: "l"(p.wmod + (size_t)(blockIdx.x * 8 + (lane >> 2)) * 6144 + 128 + (lane & 1) * 64 + (lane & 2) * 512));
        if (warp == 12) l2_prefetch(p.wqkv + (size_t)blockIdx.x * 1536, 3072);
        if (warp == 9) { spin_until(cstart + XPD); l2_prefetch(p.x + (size_t)blockIdx.x * 16384, XPB); }
    }
    if (warp == 10) { tmap_prefetch(&tmM); tmap_prefetch(&tmX); tmap_prefetch(&tmW); }
    if (warp == 11) asm volatile("prefetch.global.L2 [%0];" :: "l"((lane < 16 ? p.c : p.wr) + (lane & 15) * 64));
    #pragma unroll
    for (int i = 0; i < 5; i++) e_init(BAR(5 * warp + i), warp < 5 ? 1 : warp < 7 ? 2 : warp < 9 ? 4 : 8);
    mbar_init_fence();
    if (warp == B_TAG / 5) { e_arrive_tx(BAR(B_TAG), 16); bulk_load(sb + OFF_CST + 32, p.s->done, 16, BAR(B_TAG)); }
    uint32_t role;
    asm("mov.u32 %0, %%smid;" : "=r"(role));
    role = p.role[p.by_sm ? role : blockIdx.x];
    const int b = role & 255;
    if (b >= 128 && warp == 0) {
        #pragma unroll
        for (int i = 0; i < 2; i++) { e_arrive_tx(BAR(i), 32768); MLOAD(sb + i * 32768u, &tmM, (b & 1) * 1024, (b & 2) * 256 + i * 256, BAR(i)); }
    }
    __syncthreads();

    if (b >= 128) {
        const int sp = b & 3;
        if (warp == 8) {
            #pragma unroll 1
            for (int j = 2, st = 2, ph = 1; j < 64; j++) {
                if (j == 2 * NM0) spin_until(cstart + SPG);
                mbar_wait(BAR(B_EA + st), ph);
                e_arrive_tx(BAR(st), 32768);
                MLOAD(sb + st * 32768u, &tmM, j < 32 ? (sp & 1) * 1024 + (j >> 1) * 64 : 2560 + sp * 512 + (j >> 2) * 64, (j < 32 ? (sp & 2) + (j & 1) : j & 3) * 256, BAR(st));
                if (++st == 6) { st = 0; ph ^= 1; }
            }
        } else if (warp < 8) {
            const int g = lane >> 2, c = lane & 3;
            {
                const bf16* cp = p.c + (tid >> 3) * 32 + (tid & 1) * 16 + (tid & 6);
                const uint32_t c0 = ldg32(cp), c1 = ldg32(cp + 8);
                stg_zero(p.s->llm1 + (tid >> 4) * 64 + sp * 16 + (tid & 15));
                if (tid < 128) stg_zero(p.s->llmod2 + sp * 128 + tid);
                sts64(sb + 200704u + tid * 8, silu2(c0), silu2(c1));
                bar_sync(1, 256);
                TR(57);
            }
            const uint32_t tag = get_tag(sb);
            const uint32_t wa = sb + (warp * 32 + (lane & 7) + (lane >> 4) * 8) * 128u + ((((lane >> 3) & 1) ^ (lane & 7)) << 4);
            float m[4][4];
            #pragma unroll
            for (int i = 0; i < 4; i++) m[i][0] = m[i][1] = m[i][2] = m[i][3] = 0.f;
            #pragma unroll 1
            for (int r = 0, st = 0, ph = 0; r < 32; r++) {
                const int n = r < 16 ? r : (r >> 1) + 8;
                const bf16* wr = p.wr + (sp & 1) * 512 + (n & 7) * 64 + (g & 3) * 16 + 2 * c;
                const uint32_t wr0 = ldg32(wr), wr1 = ldg32(wr + 8);
                const uint32_t sa = sb + 200704u + ((r < 16 ? sp >> 1 : r & 1) * 16 + warp) * 64 + c * 16;
                const uint4 sv0 = lds128(sa), sv1 = lds128(sa + 512);
                uint32_t f[16][4];
                #pragma unroll
                for (int q = 0; q < 2; q++) {
                    mbar_wait(BAR(st + q), ph);
                    if (r == 0 && warp == 0) TR(60 + q);
                    #pragma unroll
                    for (int i = 0; i < 8; i++) ldsm4t(f[8 * q + i], (wa + (st + q) * 32768u + (i >> 2) * 2048u) ^ ((i & 3) << 5));
                }
                #pragma unroll
                for (int i = 0; i < 16; i++) {
                    const uint4& sv = i < 8 ? sv0 : sv1;
                    mma16816(m[i & 3], f[i][0], f[i][1], f[i][2], f[i][3], (i & 4) ? sv.z : sv.x, (i & 4) ? sv.w : sv.y);
                    if ((i & 7) == 7) e_arrive(BAR(B_EA + st + (i >> 3)));
                }
                st += 2; if (st == 6) { st = 0; ph ^= 1; }
                if (r >= 16 && !(r & 1)) continue;
                const uint32_t red = sb + 196608u + (n & 1) * 2048u;
                const uint32_t a = red + warp * 256u + (c * 16 + (g >> 1) * 4 + (g & 1)) * 4u;
                stsf(a, sel4(c, m[0][0], m[1][0], m[2][0], m[3][0])); stsf(a + 8, sel4(c, m[0][2], m[1][2], m[2][2], m[3][2]));
                #pragma unroll
                for (int i = 0; i < 4; i++) m[i][0] = m[i][1] = m[i][2] = m[i][3] = 0.f;
                bar_sync(1, 256);
                if (warp == (n & 7)) {
                    const uint32_t ra = red + (lane >> 4) * 1024u + (lane & 15) * 16u;
                    const uint4 r0 = lds128(ra), r1 = lds128(ra + 256), r2 = lds128(ra + 512), r3 = lds128(ra + 768);
                    #define F4(f) ((u2f(r0.f) + u2f(r1.f)) + (u2f(r2.f) + u2f(r3.f)))
                    float x = F4(x), y = F4(y), z = F4(z), w = F4(w);
                    #undef F4
                    x += shfl_x(x, 16); y += shfl_x(y, 16); z += shfl_x(z, 16); w += shfl_x(w, 16);
                    if (n < 16) {
                        if (lane < 16) st_ll4(p.s->llm1 + n * 64 + sp * 16 + lane, x, y, z, w, tag);
                    } else {
                        uint32_t lo = pack2(x, y), hi2 = pack2(z, w);
                        float d = fmaf(bf_lo(lo), bf_lo(wr0), bf_hi(lo) * bf_hi(wr0)) + fmaf(bf_lo(hi2), bf_lo(wr1), bf_hi(hi2) * bf_hi(wr1));
                        if (sp >= 2) {
                            lo = hadd2(lo, ONE2); hi2 = hadd2(hi2, ONE2);
                            const uint32_t r0 = hmul2(lo, wr0), r1 = hmul2(hi2, wr1);
                            d = (bf_lo(r0) + bf_hi(r0)) + (bf_lo(r1) + bf_hi(r1));
                        }
                        #pragma unroll 1
                        for (int k = 1; k < 16; k <<= 1) d += shfl_x(d, k);
                        if (lane < 16) st_ll(p.s->llmod2 + sp * 128 + (n & 7) * 16 + lane, lo, hi2, f2u(d), tag);
                    }
                    TR(n);
                }
            }
        }
    } else if (warp >= 12) {
        reg_dec<24>();
        const int rb = b >> 3, hg = b & 7, fs = role >> 8;
        const bool ffn = fs < 112;
        if (warp == 12) {
            #pragma unroll 1
            for (int j = 0, s = 0, ph = 1; j < 16; j++) {
                if (j < 2) mbar_wait(j ? BAR(B_STS) : BAR(B_STP), 0);
                mbar_wait(BAR(B_EA + s), ph);
                e_arrive_tx(BAR(B_FA + s), 16384); tma_load(sb + OFF_A + s * 16384u, &tmX, j * 64, rb * 128, BAR(B_FA + s));
                if (j == 0) TS(2);
                if (j == 1) GT(0);
                if (j == 6) GT(1);
                if (j == 11) GT(2);
                if (++s == 3) { s = 0; ph ^= 1; }
            }
            tmap_prefetch(&tmO);
            const uint32_t tag = get_tag(sb);
            e_arrive(BAR(B_FD)); e_arrive(BAR(B_FD + 1));
            const uint4* osrc = pin_ptr(p.s->os + (size_t)rb * 16 * 1024);
            #pragma unroll 1
            for (int q = 0; q < 3; q++) {
                mbar_wait(q < 2 ? BAR(B_KST + 1 + 2 * q) : BAR(B_OWN), 0);
                poll_flags(q < 2 ? p.s->flk + (q + 1) * 256 + (hg * 16 + (lane & 15)) * 2 : p.s->flo + (O0ALL ? (rb & 12) * 16 + lane * 2 : rb * 16 + (lane & 7) * 2) * 2, tag);
                if (q == 2) break;
                e_arrive_tx(BAR(B_KVL + q), 16896); bulk_load(sb + (q ? OFF_PHI : OFF_KL), p.s->kvacc + hg * 2112 + q * 1056, 16896, BAR(B_KVL + q));
                TS(12 + q);
                if (!q) GT(4);
            }
            TS(3); GT(5);
            #pragma unroll
            for (int n = 2; n < 6; n++) {
                if (n >= 4) mbar_wait(BAR(B_ED + (n & 3)), 0); else mbar_wait(BAR(B_GE + (4 * n <= NG1 ? 1 : 2)), 0);
                e_arrive_tx(BAR(B_FD + (n & 3)), 16384);
                bulk_load(sb + (n == 5 ? OFF_X1 : OFF_R0 + (n & 3) * 16384u), osrc + (n - 2 >= hg ? n - 1 : n - 2) * 2048, 16384, BAR(B_FD + (n & 3)));
                TR(32 + n);
            }
            #pragma unroll 1
            for (int n = 6; n < 16; n++) {
                const uint32_t s = n & 3, fb = BAR(B_FD + s);
                const uint4* src = osrc + d_kb(n, hg) * 1024;
                if (n == 9) mbar_wait(BAR(B_O1), 0);
                mbar_wait(BAR(B_ED + s), ((n >> 2) - 1) & 1);
                e_arrive_tx(fb, 16384);
                bulk_load(sb + OFF_R0 + s * 16384u, src, 16384, fb);
                TR(32 + n);
            }
            e_arrive_tx(BAR(B_WPHI), 32768);
            if (X1E) tma_load(sb + OFF_X1, &tmX, hg * 128 + 64, rb * 128, BAR(B_WPHI));
            mbar_wait(BAR(B_ED), 1);
            tma_load(sb + OFF_R0, &tmX, hg * 128, rb * 128, BAR(B_WPHI));
            if (!X1E) tma_load(sb + OFF_X1, &tmX, hg * 128 + 64, rb * 128, BAR(B_WPHI));
            GT(6);
            mbar_wait(BAR(B_CAND), 0);
            GT(7);
            const uint2 lc = lds64(sb + OFF_CST + 16);
            const uint32_t w0 = __shfl_sync(0xffffffffu, lc.x >> 4, 0), w1 = __shfl_sync(0xffffffffu, lc.y >> 4, 0);
            mbar_wait(BAR(B_SWP), 0);
            fence_async_smem();
            if (OUTW) mbar_wait(BAR(B_SEL), 0);
            #pragma unroll 1
            for (uint32_t w = 0; w < 8; w++)
                if (w != w0 && w != w1) { tma_store4(&tmO, rb * 128 + w * 16, hg * 2, sb + OFF_OUT + w * 4096u); spin_until(clk32() + OUTGAP); }
            mbar_wait(BAR(B_SEL), 0);
            const uint2 sel = lds64(sb + OFF_CST + 24);
            #pragma unroll 1
            for (uint32_t i = 0; i < (w0 == w1 ? 8u : 16u); i++) {
                const uint32_t w = i < 8 ? w0 : w1, r = (i & 7) * 2 + (lane >> 4), row = rb * 128 + w * 16 + r;
                const uint4 o = lds128(sb + OFF_OUT + w * 4096u + ((lane >> 3) & 1) * 2048u + r * 128u + (((lane ^ r) & 7) << 4));
                if (row != (~sel.x & 2047u) && row != (~sel.y & 2047u)) stg128(p.out + (size_t)row * 1024 + hg * 128 + (lane & 15) * 8, o);
            }
            bulk_wait_read();
        } else if (warp == 14) {
            const uint32_t fb = ffn ? 65536 : 0;
            e_arrive_tx(BAR(B_GF), fb); e_arrive_tx(BAR(B_UD), fb); e_arrive_tx(BAR(B_UF), fb); e_arrive_tx(BAR(B_WD), fb);
            uint32_t due = cstart + WP1;
            #pragma unroll 1
            for (int i = -2; i < 26; i++) {
                if (i >= 0) {
                    const bf16* a = i < 8 ? p.wg + (size_t)(i * 128 + b) * 3584 : i < 16 ? p.wu + (size_t)((i - 8) * 128 + b) * 3584
                                  : i < 18 ? p.wo + (size_t)(b * 2 + i - 16) * 4096 : p.wd + (size_t)(b * 8 + i - 18) * 3584;
                    sleep_until(due);
                    l2_prefetch(a, (i >> 1) == 8 ? 8192 : 7168);
                    due += 7 * PFP;
                }
                if (i == 1) { tmap_prefetch(&tmPhi); tmap_prefetch(&tmG); tmap_prefetch(&tmWo); tmap_prefetch(&tmU); tmap_prefetch(&tmD); mbar_wait(BAR(B_STS), 0); }
                if (ffn && (uint32_t)(i - 3) < 8u) tma_load_ef(sb + OFF_R0 + (i - 3) * 8192u, &tmG, fs * 32, (i - 3) * 128, BAR(B_GF));
                if (ffn && (uint32_t)(i - 11) < 8u) tma_load(sb + OFF_WPHI, &tmU, fs * 32, (i - 11) * 128, BAR(B_UD));
                if (i == 19) { mbar_wait(BAR(B_UD), 0); e_arrive_tx(BAR(B_WPHI), 8192); tma_load(sb + OFF_WPHI, &tmPhi, 0, hg * 128, BAR(B_WPHI)); }
                if (i == LMP + 2 * (b & 3) + (b >> 6)) tma_prefetch(&tmM, 2048 + (b >> 6) * 2048 + (b >> 2) * 64, (b & 3) * 256);
                if (i < 13) {
                    sleep_until(due);
                    l2_prefetch(p.wqkv + (size_t)((i + 3) * 128 + b) * 1536, 3072);
                    due += i == -2 ? PF_START - WP1 : 3 * PFP;
                }
            }
            if (lane < 4) stg_zero(p.s->flo + b * 4 + lane);
            const uint32_t tag = get_tag(sb);
            #pragma unroll 1
            for (int q = 0; q < 2; q++) {
                mbar_wait(BAR(B_OWN + q), 0);
                if (q) { if (O1H >= 4) mbar_wait(BAR(B_FD + 2), 0); mbar_wait(BAR(B_FD + (O1H & 3)), O1H >> 2); }
                bulk_store(p.s->os + ((size_t)b * 2 + q) * 1024, sb + OFF_R0 + q * 16384u, 16384);
                bulk_wait();
                __syncwarp();
                st_flag(p.s->flo + (b * 2 + q) * 2, tag, lane);
                TS(7 + q);
            }
            e_arrive(BAR(B_OST));
        } else {
            uint4* fk = p.s->flk + (hg * 16 + rb) * 2;
            if (warp == 13) {
                #pragma unroll 1
                for (int i = 0; i < 32; i++) {
                    const uint32_t s = i & 3;
                    if (i < NB0) spin_until(cstart + WL0 + WLS * i); else if (i == NB0) mbar_wait(BAR(B_STS), 0);
                    mbar_wait(BAR(B_EB + s), ((i >> 2) - 1) & 1);
                    e_arrive_tx(BAR(B_FB + s), 24576); tma_load4(sb + OFF_B + s * 24576u, &tmW, i * 32, hg * 2, BAR(B_FB + s));
                    TR(64 + i);
                }
                mbar_wait(BAR(B_EB), 1); mbar_wait(BAR(B_EB + 1), 1);
                e_arrive_tx(BAR(B_LMF), 32768); tma_load_ef(sb + OFF_B, &tmM, 2048 + (b >> 6) * 2048 + (b >> 2) * 64, (b & 3) * 256, BAR(B_LMF));
                mbar_wait(BAR(B_LMD), 0);
                #pragma unroll 1
                for (int n = 0; n < 4; n++) {
                    e_arrive_tx(BAR(B_FD + n), 16384); tma_load4(sb + OFF_DB + n * 16384u, &tmWo, d_kb(n, hg) * 64, hg * 2, BAR(B_FD + n));
                }
            } else {
                sleep_until(cstart + CLR0);
                const uint32_t tag = get_tag(sb);
                #pragma unroll 1
                for (int i = lane; i < 132; i += 32) stg_zero(p.s->kvacc + hg * 2112 + rb * 132 + i);
                if (lane < 4) stg_zero(fk + 256 + (lane >> 1) * 256 + (lane & 1));
                fence_gpu();
                __syncwarp();
                st_flag(fk, tag, lane);
                sleep_until(clk32() + 2000);
                poll_flags(p.s->flk + (hg * 16 + (lane & 15)) * 2, tag);
                mbar_wait(BAR(B_QE), 0);
                #pragma unroll 1
                for (int i = 0; i < 4; i++) {
                    stg_zero(p.s->llln2 + b * 128 + i * 32 + lane);
                    stg_zero(p.s->llrowh + (i >> 1) * 8192 + (rb * 2 + (i & 1)) * 256 + hg * 32 + lane);
                    #pragma unroll
                    for (int k = 0; k < 4; k++) stg_zero(p.s->lly + (fs & 127) * 512 + i * 128 + k * 32 + lane);
                }
                if (lane < 2 && hg == (rb & 7)) stg_zero(p.s->llcand + rb * 2 + lane);
                __syncwarp();
                e_arrive(BAR(B_KZ));
            }
            const int q = warp == 13;
            const uint32_t tag = get_tag(sb);
            mbar_wait(BAR(B_KZ), 0);
            #pragma unroll 1
            for (int h = 2 * q; h < 2 * q + 2; h++) {
                mbar_wait(BAR(B_KST + h), 0);
                uint4* acc = p.s->kvacc + (hg * 4 + h) * 528;
                bulk_reduce(acc, sb + OFF_V + h * 8192u, 8192); bulk_reduce(acc + 512, sb + OFF_ZS + h * 256u, 256);
            }
            bulk_wait();
            if (q) e_arrive(BAR(B_KZ));
            TR(158 + q);
            fence_gpu();
            __syncwarp();
            st_flag(fk + 256 + q * 256, tag, lane);
            TS(10 + q);
            if (q) {
                #pragma unroll 1
                for (int n = 4; n < 16; n++) {
                    const uint32_t s = n & 3;
                    mbar_wait(BAR(B_ED + s), ((n >> 2) - 1) & 1);
                    e_arrive_tx(BAR(B_FD + s), 16384);
                    tma_load4(sb + OFF_DB + s * 16384u, &tmWo, d_kb(n, hg) * 64, hg * 2, BAR(B_FD + s));
                    TR(96 + n);
                    if (ffn && (uint32_t)(n - WD0) < 4u) {
                        #pragma unroll
                        for (int k = 0; k < 2; k++) tma_load_ef(sb + OFF_F2 + (n - WD0) * 8192u + k * 4096u, &tmD, (n - WD0) * 256 + k * 128, fs * 32, BAR(B_WD));
                    }
                }
                if (ffn) {
                    mbar_wait(BAR(B_ED + WDW), 1);
                    #pragma unroll 1
                    for (int z = 0; z < 8; z++) { tma_load_ef(sb + OFF_DB + z * 4096u, &tmD, z * 128 + 64, fs * 32, BAR(B_WD)); sleep_until(clk32() + WDGAP); }
                }
            } else {
                if (ffn) {
                    mbar_wait(BAR(B_KZ), 1);
                    #pragma unroll 1
                    for (int i = 7; i < 15; i++) {
                        if (i == 12) mbar_wait(BAR(B_KVT + 1), 0);
                        tma_load_ef(sb + OFF_F2 + (i & 7) * 8192u, &tmU, fs * 32, (i & 7) * 128, BAR(B_UF));
                        sleep_until(clk32() + UPGAP);
                    }
                }
                mbar_wait(BAR(B_OST), 0);
                poll_flags(p.s->flo + (O1ALL ? (rb & 12) * 16 + lane * 2 + 1 : rb * 16 + (lane & 7) * 2 + 1) * 2, tag);
                e_arrive(BAR(B_O1));
                TS(4);
            }
        }
    } else if (warp >= 8) {
        reg_dec<24>();
        const int rb = b >> 3, hg = b & 7, w4 = warp & 3, g = lane >> 2, c = lane & 3, t = tid & 127;
        const uint32_t sv = silu2(ldg32(p.c + (b & 3) * 256 + 2 * t)), tag = get_tag(sb);
        if (w4 < 3) {
            spin_until(cstart + MPOLL + MSTEP * w4);
            #pragma unroll 1
            for (int j = w4, ph = 1; j < 16; j += 3, ph ^= 1) {
                uint4 w[2];
                poll_words<2, 0, 3>(w, p.s->llm1 + j * 64 + lane, 32, tag);
                uint32_t lo = pack2(u2f(w[0].x) + u2f(w[1].x), u2f(w[0].y) + u2f(w[1].y)), hi = pack2(u2f(w[0].z) + u2f(w[1].z), u2f(w[0].w) + u2f(w[1].w));
                if (lane >= 16) { lo = hadd2(lo, ONE2); hi = hadd2(hi, ONE2); }
                sts64(sb + OFF_TAB + j * 256 + (lane & 15) * 16 + (lane < 16 ? 8 : 0), lo, hi);
                __syncwarp();
                if (j == 0) TS(5);
                TR(16 + j);
                mbar_wait(BAR(B_EA + w4), ph);
                e_arrive(BAR(B_FA + w4));
                __nanosleep(MSLP);
            }
        }
        mbar_wait(BAR(B_QE), 0);
        if (warp == 8) GT(3);
        sts32(sb + OFF_KL + w4 * 1024u + lane * 4, sv);
        fence_async_smem();
        bar_sync(2, 128);
        reg_inc<56>();
        {
            float m0[4], m1[4];
            const uint32_t da = desc_lo(sb + OFF_B, 16), db = desc_lo(sb + OFF_KL, 16);
            mbar_wait(BAR(B_LMF), 0);
            wg_fence();
            #define LMS(f, i) f<(i) * 256, H128, ((i) >> 1) * 64 + ((i) & 1) * 4, H128>(m0, da, db); f<(i) * 256 + 128, H128, ((i) >> 1) * 64 + ((i) & 1) * 4 + 2, H128>(m1, da, db)
            LMS(mma8_tn0, 0); LMS(mma8_tn, 1); LMS(mma8_tn, 2); LMS(mma8_tn, 3); LMS(mma8_tn, 4); LMS(mma8_tn, 5); LMS(mma8_tn, 6); LMS(mma8_tn, 7);
            #undef LMS
            wg_commit();
            wg_wait<0>();
            acc_fence(m0); acc_fence(m1);
            e_arrive(BAR(B_LMD));
            const float v0 = m0[0] + m1[0], v1 = m0[2] + m1[2], u0 = shfl_x(v0, 4), u1 = shfl_x(v1, 4);
            if (!(lane & 7)) st_ll4(p.s->llg + (b >> 6) * 1024 + (b & 3) * 256 + ((b >> 2) & 15) * 16 + w4 * 4 + (lane >> 3), v0, u0, v1, u1, tag);
            if (warp == 8) TR(150);
        }
        #pragma unroll 1
        for (int h = 0; h < 4; h++) {
            float okv[20];
            const uint32_t vb = OFF_V + h * 8192u, dp = desc_lo(sb + OFF_PHI + (h & 1) * 16384u, 16), dv = desc_lo(sb + vb, OFF_ONES - vb);
            mbar_wait(BAR(B_PF + h), 0);
            fence_async_smem();
            wg_fence();
            #define KVS(i) mma40_tt<(i) * 128, H128, (i) * (64u - (64u << 16)), H64>(okv, dp, dv)
            mma40_tt0<0, H128, 0, H64>(okv, dp, dv); KVS(1); KVS(2); KVS(3); KVS(4); KVS(5); KVS(6); KVS(7);
            #undef KVS
            wg_commit();
            wg_wait<0>();
            acc_fence(okv);
            if (h < 2) e_arrive(BAR(B_PE + h));
            bar_sync(2, 128);
            #pragma unroll
            for (int k = 0; k < 4; k++) sts128(sb + vb + (k * 128 + t) * 16u, make_uint4(f2u(okv[4 * k]), f2u(okv[4 * k + 1]), f2u(okv[4 * k + 2]), f2u(okv[4 * k + 3])));
            if (c == 0) sts64(sb + OFF_ZS + h * 256u + (w4 * 8 + g) * 8u, f2u(okv[16]), f2u(okv[18]));
            fence_async_smem();
            __syncwarp();
            e_arrive(BAR(B_KST + h));
            if (warp == 8) TR(151 + h);
        }
        #pragma unroll 1
        for (int q = 0; q < 2; q++) {
            const uint32_t f = w4 * 16 + g, kl = sb + (q ? OFF_PHI : OFF_KL), ta = sb + (q ? OFF_KL : OFF_KVT) + f * 64u + ((g >> 1) << 4) + 4 * c;
            const uint32_t za = sb + OFF_Z + (f + 8 * (c & 1)) * 64u + (((2 * q) ^ (g >> 1)) << 4) + (c >> 1) * 8;
            mbar_wait(q ? BAR(B_KVT) : BAR(B_STP), q ^ 1);
            mbar_wait(BAR(B_KVL + q), 0);
            uint4 v[8]; float z[2];
            #pragma unroll
            for (int k = 0; k < 8; k++) v[k] = lds128(kl + (k >> 2) * 8448u + (k & 3) * 2048u + t * 16u);
            #pragma unroll
            for (int hh = 0; hh < 2; hh++) z[hh] = ldsf(kl + hh * 8448u + 8192u + (w4 * 8 + g) * 8u + (c & 1) * 4);
            #pragma unroll
            for (int k = 0; k < 8; k++) {
                sts32((ta ^ ((k & 3) << 4)) + (k >> 2) * 4096u, pack2(u2f(v[k].x), u2f(v[k].y))); sts32((ta ^ ((k & 3) << 4)) + (k >> 2) * 4096u + 512, pack2(u2f(v[k].z), u2f(v[k].w)));
            }
            #pragma unroll
            for (int hh = 0; hh < 2; hh++) { const uint32_t zz = pack2(z[hh], z[hh]); sts64(za ^ (hh << 4), zz, zz); }
            fence_async_smem();
            __syncwarp();
            e_arrive(BAR(B_KVT + q));
            if (warp == 8) TR(155 + q);
        }
        reg_dec<24>();
        mbar_wait(BAR(B_O1), 0);
        if (w4 == 0 || w4 == 3) {
            float s[4] = {0.f, 0.f, 0.f, 0.f};
            #pragma unroll 1
            for (int k = 0; k < 2; k++) {
                uint4 w[2];
                poll_words<2, 0, 3>(w, p.s->llg + (w4 & 1) * 1024 + k * 512 + hg * 32 + lane, 256, tag);
                s[0] += u2f(w[0].x) + u2f(w[1].x); s[1] += u2f(w[0].y) + u2f(w[1].y); s[2] += u2f(w[0].z) + u2f(w[1].z); s[3] += u2f(w[0].w) + u2f(w[1].w);
            }
            const uint32_t lo = pack2(s[0], s[1]), hi = pack2(s[2], s[3]);
            sts64(w4 ? sb + OFF_T3 + lane * 8 : sb + OFF_T1 + lane * 16, lo, hi);
            if (!w4) sts64(sb + OFF_T1 + 512 + lane * 16, lo, hi);
        } else {
            const bf16* wr = p.wr + hg * 128 + g * 16 + 2 * c;
            const uint32_t wr0 = ldg32(wr), wr1 = ldg32(wr + 8);
            uint4 w[2];
            poll_words<2, 1>(w, p.s->llmod2 + (w4 - 1) * 256 + hg * 32 + lane, (lane & 15) * 16 - hg * 32 - lane, tag);
            sts64(sb + OFF_T2 + lane * 16 + (w4 & 1) * 8, w[0].x, w[0].y);
            if (w4 == 2) sts64(sb + OFF_T1 + 512 + lane * 16 + 8, hmul2(w[0].x, wr0), hmul2(w[0].y, wr1));
            float d = u2f(w[1].z);
            #pragma unroll 1
            for (int k = 1; k < 16; k <<= 1) d += shfl_x(d, k);
            stsf(sb + OFF_CST + 8 + (w4 & 1) * 4, d);
        }
        __syncwarp();
        e_arrive(BAR(B_PAR));
        if (warp == 9) TS(6);
        if (w4 < 2) {
            mbar_wait(BAR(B_PAR), 0);
            const uint4 ta = lds128(sb + OFF_T2 + lane * 16);
            const uint2 gb = lds64(sb + OFF_T3 + lane * 8);
            uint4* d = pin_ptr(p.s->llrowh + (rb * 2 + w4) * 256 + hg * 32 + lane);
            mbar_wait(BAR(B_KEYS), 0);
            const uint4 kk = lds128(sb + OFF_KEY + lane * 16);
            uint32_t k[4] = {kk.x, kk.y, kk.z, kk.w}, b0, b1;
            top2<4>(k, b0, b1);
            const uint32_t cd = ~(w4 ? b1 : b0) & 127u;
            const uint32_t xa = sb + OFF_R0 + (g >> 2) * (OFF_X1 - OFF_R0) + cd * 128u + ((((g & 3) * 2) ^ (cd & 7)) << 4) + c * 4;
            const uint32_t x0 = lds32(xa), x1 = lds32(xa ^ 16);
            const uint4 st = lds128(sb + OFF_ST2 + cd * 16);
            st_ll(d, lnmod(x0, st.x, st.y, st.z, ta.x, ta.z), lnmod(x1, st.x, st.y, st.z, ta.y, ta.w), gb.x, tag);
            st_ll(d + 8192, x0, x1, gb.y, tag);
            sts32(sb + OFF_CST + 16 + w4 * 4, cd);
            __syncwarp();
            e_arrive(BAR(B_CAND));
            if (warp == 8) TS(9);
        } else if (w4 == 2) {
            uint4* cp = pin_ptr(p.s->llcand + lane);
            mbar_wait(BAR(B_KEYS), 0);
            if (hg == (rb & 7)) {
                const uint4 kk = lds128(sb + OFF_KEY + lane * 16);
                uint32_t k[4] = {kk.x, kk.y, kk.z, kk.w}, b0, b1;
                top2<4>(k, b0, b1);
                if ((lane >> 1) == rb) st_ll(cp, (lane & 1) ? b1 : b0, tag, tag, tag);
            } else spin_until(clk32() + CWAIT);
            uint2 v = make_uint2(0, 0);
            #pragma unroll 1
            for (int it = 0; it < POLL_MAX; it++) {
                if (v.y != tag) asm volatile("ld.relaxed.gpu.global.v2.b32 {%0,%1}, [%2];" : "=r"(v.x), "=r"(v.y) : "l"(cp) : "memory");
                if (__all_sync(0xffffffffu, v.y == tag)) break;
            }
            uint32_t k[1] = {v.x}, b0, b1;
            top2<1>(k, b0, b1);
            sts64(sb + OFF_CST + 24, b0, b1);
            __syncwarp();
            e_arrive(BAR(B_SEL));
        }
    } else {
        reg_inc<232>();
        float a0[96], a1[96];
        {
            const int g = lane >> 2, c = lane & 3;
            uint4* stp = p.s->llstat + b * 16 + warp * 2 + (lane >> 4);
            if ((lane & 15) == 0) stg_zero(stp);
            spin_until(cstart + XD + XSTEP * warp);
            e_arrive_tx(BAR(B_XP + warp), 4096);
            bulk_load(sb + OFF_R0 + warp * 4096u, p.x + (size_t)(b * 16 + 2 * warp) * 1024, 4096, BAR(B_XP + warp));
            const uint32_t tag = get_tag(sb);
            if (tid < 64) sts128(sb + OFF_ONES + tid * 16, make_uint4(ONE2, ONE2, ONE2, ONE2));
            if (tid == 64) { sts64(sb + OFF_CST, role, tag); stsf(sb + OFF_CST + 48, -LOG2E); }
            if (AWAKE & 1) mbar_wait_awake(BAR(B_XP + warp), 0); else mbar_wait(BAR(B_XP + warp), 0);
            e_arrive(BAR(B_STP));
            if (warp == 7) TS(14);
            float s[2][4], q0[2][4], q1[2][4];
            #pragma unroll
            for (int i = 0; i < 4; i++) s[0][i] = s[1][i] = q0[0][i] = q0[1][i] = q1[0][i] = q1[1][i] = 0.f;
            #pragma unroll
            for (int i = 0; i < 4; i++) {
                const uint4 x0 = lds128(sb + OFF_R0 + warp * 4096u + (lane + 32 * i) * 16u), x1 = lds128(sb + OFF_R0 + warp * 4096u + 2048u + (lane + 32 * i) * 16u);
                mma16816(s[0], x0.x, x1.x, x0.y, x1.y, ONE2, ONE2); mma16816(s[1], x0.z, x1.z, x0.w, x1.w, ONE2, ONE2);
                mma16816(q0[0], x0.x, x1.x, x0.y, x1.y, x0.x, x0.y); mma16816(q0[1], x0.z, x1.z, x0.w, x1.w, x0.z, x0.w);
                mma16816(q1[0], x0.x, x1.x, x0.y, x1.y, x1.x, x1.y); mma16816(q1[1], x0.z, x1.z, x0.w, x1.w, x1.z, x1.w);
            }
            const bool dg = c == (g >> 1);
            const float s0 = dg ? s[0][0] + s[1][0] : 0.f, s1 = dg ? s[0][2] + s[1][2] : 0.f;
            const float sq0 = dg ? ((g & 1) ? q0[0][1] + q0[1][1] : q0[0][0] + q0[1][0]) : 0.f, sq1 = dg ? ((g & 1) ? q1[0][3] + q1[1][3] : q1[0][2] + q1[1][2]) : 0.f;
            const bool up = lane >= 16;
            float sm = (up ? s1 : s0) + shfl_x(up ? s0 : s1, 16), sq = (up ? sq1 : sq0) + shfl_x(up ? sq0 : sq1, 16);
            #pragma unroll
            for (int m = 8; m >= 1; m >>= 1) { sm += shfl_x(sm, m); sq += shfl_x(sq, m); }
            uint32_t m2, rh, rl; float rinv;
            ln_final(sm, sq, m2, rinv);
            split_rcp(rinv, rh, rl);
            if ((lane & 15) == 0) st_ll(stp, m2, rh, rl, tag);
            if (warp == 7) TS(15);
            uint4 st[2];
            if (PWAIT) { mbar_wait(BAR(B_STP), 0); if (warp < 7) spin_until(clk32() + PWAIT); }
            #pragma unroll 1
            for (int it = 0; it < POLL_MAX; it++) {
                st[0] = ld_ll(p.s->llstat + (b >> 3) * 128 + warp * 16 + g); st[1] = ld_ll(p.s->llstat + (b >> 3) * 128 + warp * 16 + g + 8);
                const uint32_t o = RDV ? ld_rlx(&p.s->llstat[((b >> 5) * 4 + c) * 128 + warp * 16 + 15].w) : tag;
                if (__all_sync(0xffffffffu, !tag_bad(tag_bad(o ^ tag, st[0].w, tag), st[1].w, tag))) break;
                if (AWAKE & 1) it += awake_zero();
            }
            e_arrive(BAR(B_STS));
            if (warp == 0) TS(16);
            const uint32_t lrow = warp * 16 + (lane & 15);
            uint32_t aad = sb + OFF_A + lrow * 128u + (((lane >> 4) ^ (lrow & 7)) << 4);
            uint32_t tad = sb + OFF_TAB + c * 16, ab = BAR(B_FA), pa = 0;
            uint32_t f0[4], f1[4];
            #define PREP(f, q) do { \
                const uint4 t = lds128(tad + (q) * 64); \
                ldsm4(f, aad ^ ((q) << 5)); \
                f[0] = lnmod(f[0], st[0].x, st[0].y, st[0].z, t.x, t.z); f[1] = lnmod(f[1], st[1].x, st[1].y, st[1].z, t.x, t.z); \
                f[2] = lnmod(f[2], st[0].x, st[0].y, st[0].z, t.y, t.w); f[3] = lnmod(f[3], st[1].x, st[1].y, st[1].z, t.y, t.w); } while (0)
            #define MMA(f, off) do { wg_fence(); mma192_rs<(off), H128>(a0, f, blo); mma192_rs<(off) + 768, H128>(a1, f, blo); wg_commit(); wg_wait<1>(); } while (0)
            mbar_wait(ab, 0);
            PREP(f0, 0);
            if (RDV) mbar_wait(BAR(B_STS), 0);
            #pragma unroll 1
            for (int j = 0; j < 16; j++) {
                const uint32_t bb = BAR(B_FB) + (j & 1) * 16, blo = desc_lo(sb + OFF_B, 4096) + (j & 1) * 3072, pb = (j >> 1) & 1;
                mbar_wait(bb, pb);
                wg_fence(); mma192_rsp<0, H128>(a0, f0, blo, j); mma192_rsp<768, H128>(a1, f0, blo, j); wg_commit(); wg_wait<1>();
                if (j) e_arrive((bb ^ 16) + 8 * (B_EB - B_FB) + 8);
                PREP(f1, 1);
                MMA(f1, 128);
                PREP(f0, 2);
                mbar_wait(bb + 8, pb);
                MMA(f0, 1536);
                e_arrive(bb + 8 * (B_EB - B_FB));
                PREP(f1, 3);
                MMA(f1, 1536 + 128);
                e_arrive(ab + 8 * (B_EA - B_FA));
                ab += 8; aad += 16384; tad += 256;
                if (ab == BAR(B_FA + 3)) { ab -= 24; aad -= 49152; pa ^= 1; }
                if (j < 15) mbar_wait(ab, pa);
                PREP(f0, 0);
            }
            #undef PREP
            #undef MMA
        }
        int tid_o; asm volatile("mov.u32 %0, %%tid.x;" : "=r"(tid_o) :: "memory");
        const int tid = tid_o, lane = tid & 31, warp = __shfl_sync(0xffffffffu, tid >> 5, 0), wgi = warp >> 2, g = lane >> 2, c = lane & 3;
        const uint32_t srow = warp * 16 + (lane & 15);
        #define T128(t) (sb + (((t) >> 5) * 16 + ((t) & 15)) * 128u + (((((t) >> 4) & 1) ^ ((t) & 7)) << 4))
        const uint32_t pa = T128(tid);
        mbar_wait(BAR(B_WPHI), 0);
        mbar_wait(BAR(B_EA), 1);
        wg_wait<0>();
        acc_fence(a0); acc_fence(a1);
        e_arrive(BAR(B_QE));
        if (warp == 0) TS(18);
        uint32_t ph0[16], ph1[16], kq[32];
        {
        uint32_t pk[16], mm[4], mn[2];
        float ea[32], eb[32];
        {
            float p0[16], p1[16];
            const uint32_t dw = desc_lo(sb + OFF_WPHI, 16);
            #define PMMA(f, o) do { wg_fence(); mma32_rs0<(o), H64>(p0, f, dw); mma32_rs0<(o) + 128, H64>(p1, f + 8, dw); \
                mma32_rs<(o) + 64, H64>(p0, f + 4, dw); mma32_rs<(o) + 192, H64>(p1, f + 12, dw); wg_commit(); } while (0)
            #define V_OUT(lo) _Pragma("unroll") for (int i = lo; i < lo + 4; i++) { const int o = 32 + 8 * i; \
                stsm4(sb + OFF_V + (i >> 1) * 8192u + srow * 64u + (((2 * (i & 1) + (lane >> 4)) ^ ((srow >> 1) & 3)) << 4), \
                      pack2(a1[o], a1[o + 1]), pack2(a1[o + 2], a1[o + 3]), pack2(a1[o + 4], a1[o + 5]), pack2(a1[o + 6], a1[o + 7])); }
            V_OUT(0);
            #pragma unroll
            for (int i = 0; i < 16; i++) ph0[i] = pack2(a0[64 + 2 * i], a0[65 + 2 * i]);
            PMMA(ph0, 0);
            V_OUT(4);
            #undef V_OUT
            wg_wait<0>();
            acc_fence(p0); acc_fence(p1);
            fm_max(p0, pk, mm); fm_max(p1, pk + 8, mm + 2);
            #pragma unroll
            for (int i = 0; i < 16; i++) ph1[i] = pack2(a1[2 * i], a1[2 * i + 1]);
            PMMA(ph1, 256);
            if (warp == 0) TS(19);
            fm_pos(pk, mm, ea);
            #pragma unroll
            for (int i = 0; i < 32; i++) kq[i] = pack2(a0[2 * i], a0[2 * i + 1]);
            acc_fence(ea); pin<32>(kq);
            wg_wait<0>();
            acc_fence(p0); acc_fence(p1);
            #define PHI_OUT(ph, i) do { if (u < 2) { \
                    mbar_wait(u ? BAR(B_PE + (i)) : (i) ? BAR(B_LMD) : BAR(B_QE), 0);          \
                    _Pragma("unroll") for (int q = 0; q < 4; q++) stsm4((pa ^ (q << 5)) + OFF_PHI + (i) * 16384u, ph[4 * q], ph[4 * q + 1], ph[4 * q + 2], ph[4 * q + 3]); \
                    __syncwarp(); \
                    e_arrive(BAR(B_PF + (i)) + u * 16); } } while (0)
            reg_dec<216>();
            #pragma unroll 1
            for (int u = 0; u < 4; u++) {
                fm_neg(mm, ldsf(sb + OFF_CST + 48), ea); fm_pos(pk + 8, mm + 2, eb);
                fm_norm(ea, ph0); fm_max(p0, pk, mm); fm_max(p1, pk + 8, mn);
                PHI_OUT(ph0, 0);
                if (warp == 0) TR(130 + (u & 1) * 6);
                if (u == 0) PMMA(kq, 0); else PMMA(kq + 16, 256);
                fm_neg(mm + 2, ldsf(sb + OFF_CST + 48), eb); fm_pos(pk, mm, ea);
                fm_norm(eb, ph1);
                mm[2] = mn[0]; mm[3] = mn[1];
                PHI_OUT(ph1, 1);
                wg_wait<0>();
                acc_fence(p0); acc_fence(p1);
                if (u == 2) {
                    e_arrive(BAR(B_STP));
                    mbar_wait(BAR(B_GF), 0);
                    #pragma unroll
                    for (int i = 0; i < 16; i++) { kq[i] = ph0[i]; kq[16 + i] = ph1[i]; }
                }
                if (warp == 0) TR(133 + (u & 1) * 6);
                if (warp == 0) TS(21 + u);
            }
            #undef PHI_OUT
            #undef PMMA
        }
        }
        uint32_t gf[16][4], uf[16][4];
        const uint32_t fo = sb + (warp >> 1) * 2048u + ((lane & 7) + (lane >> 4) * 8) * 64u + (((2 * (warp & 1) + ((lane >> 3) & 1)) ^ ((lane >> 1) & 3)) << 4);
        #define F_LOAD(f, off, i) ldsm4t(f[i], fo + (off) + ((i) >> 1) * 8192u + ((i) & 1) * 1024u)
        #define G_LOAD(lo, n, k) do { _Pragma("unroll") for (int i = lo; i < lo + n; i++) F_LOAD(gf, OFF_R0, i); e_arrive(BAR(B_GE + k)); } while (0)
        #define O_BLOCK(pp, ph0, ph1) do { \
            if ((AWAKE & 2) && !(pp)) mbar_wait_awake(BAR(B_KVT + (pp)), 0); else mbar_wait(BAR(B_KVT + (pp)), 0); \
            if (warp == 0) TS(25 + 3 * (pp)); \
            const uint32_t oa = T128(tid + (lds32(sb + OFF_CST) >> 16)); \
            float o0[20], o1[20]; \
            const uint32_t dk = (pp) ? desc_lo(sb + OFF_KL, OFF_Z + 32 - OFF_KL) : desc_lo(sb + OFF_KVT, OFF_Z - OFF_KVT); \
            constexpr uint32_t K1 = 256u - (255u << 16);          \
            wg_fence(); \
            mma40_rs0<0, H64>(o0, ph0, dk); mma40_rs0<K1, H64>(o1, ph1, dk); \
            mma40_rs<64, H64>(o0, ph0 + 4, dk); mma40_rs<K1 + 64, H64>(o1, ph1 + 4, dk); \
            mma40_rs<128, H64>(o0, ph0 + 8, dk); mma40_rs<K1 + 128, H64>(o1, ph1 + 8, dk); \
            mma40_rs<192, H64>(o0, ph0 + 12, dk); mma40_rs<K1 + 192, H64>(o1, ph1 + 12, dk); \
            wg_commit(); \
            wg_wait<0>(); \
            acc_fence(o0); acc_fence(o1); \
            if (pp) e_arrive(BAR(B_ED)); \
            if (warp == 0) TS(26 + 3 * (pp)); \
            mbar_wait(BAR(B_GE + (pp)), 0); \
            _Pragma("unroll") for (int hh = 0; hh < 2; hh++) { \
                const float (&o)[20] = hh ? o1 : o0; \
                uint32_t h0, l0, h1, l1; \
                split_rcp(rcp(rbf(rbf(o[16]) + 1e-6f)), h0, l0); split_rcp(rcp(rbf(rbf(o[18]) + 1e-6f)), h1, l1); \
                _Pragma("unroll") for (int q = 0; q < 2; q++) \
                    stsm4((oa ^ ((2 * hh + q) << 5)) + OFF_R0 + (pp) * 16384u, hdiv2(pack2(o[8 * q], o[8 * q + 1]), h0, l0), hdiv2(pack2(o[8 * q + 2], o[8 * q + 3]), h1, l1), \
                          hdiv2(pack2(o[8 * q + 4], o[8 * q + 5]), h0, l0), hdiv2(pack2(o[8 * q + 6], o[8 * q + 7]), h1, l1)); \
            } \
            fence_async_smem(); \
            __syncwarp(); \
            e_arrive(BAR(B_OWN + (pp))); \
            if (warp == 0) TS(27 + 3 * (pp)); \
        } while (0)
        float acc[64];
        const uint32_t da = desc_lo(sb + OFF_R0 + wgi * 8192u, 16), db = desc_lo(sb + OFF_DB, 8192);
        #define D_MMA(first, a, s) do { \
            wg_fence(); \
            first<(a), H128, (s) * 1024, H128>(acc, da, db); mma128_ss<(a) + 2, H128, (s) * 1024 + 128, H128>(acc, da, db); \
            mma128_ss<(a) + 4, H128, (s) * 1024 + 256, H128>(acc, da, db); mma128_ss<(a) + 6, H128, (s) * 1024 + 384, H128>(acc, da, db); \
            wg_commit(); } while (0)
        G_LOAD(0, 4, 0);
        O_BLOCK(0, kq, (kq + 16));
        G_LOAD(4, NG1, 1);
        mbar_wait(BAR(B_OWN), 0);
        mbar_wait(BAR(B_FD), 0);
        D_MMA(mma128_ss0, 0, 0);
        O_BLOCK(1, ph0, ph1);
        G_LOAD(4 + NG1, 12 - NG1, 2);
        reg_inc<232>();
        mbar_wait(BAR(B_OWN + 1), 0);
        #undef O_BLOCK
        #define D_STEP(n) do { \
            mbar_wait(BAR(B_FD + ((n) & 3)), ((n) >> 2) & 1); \
            if (warp == 0) TR(112 + (n)); \
            D_MMA(mma128_ss, (n) == 5 ? OFF_X1 / 16 : ((n) & 3) * 1024, (n) & 3); \
            if ((n) == 3) mbar_wait(BAR(B_UF), 0); \
            if ((n) >= 3 && (n) < 7) { F_LOAD(uf, OFF_F2, 2 * (((n) + 5) & 7)); F_LOAD(uf, OFF_F2, 2 * (((n) + 5) & 7) + 1); } \
            wg_wait<1>(); \
            if ((n) > 2) e_arrive(BAR(B_ED + (((n) + 3) & 3))); } while (0)
        D_STEP(1);
        wg_wait<0>();
        e_arrive(BAR(B_ED + 1));
        D_STEP(2);
        if (warp == 0) TS(31);
        D_STEP(3); D_STEP(4); D_STEP(5); D_STEP(6); D_STEP(7); D_STEP(8); D_STEP(9); D_STEP(10); D_STEP(11); D_STEP(12); D_STEP(13); D_STEP(14); D_STEP(15);
        #undef D_STEP
        #undef D_MMA
        #define XADDR(i) ((xa ^ (((i) & 3) << 5)) + ((i) < 4 ? OFF_R0 : OFF_X1))
        mbar_wait(BAR(B_PAR), 0);
        const uint4 cst = lds128(sb + OFF_CST);
        const int b = cst.x & 255;
        const uint32_t tag = cst.y, xa = T128(tid + (cst.x >> 16));
        uint4 w[4];
        const uint32_t rl = warp * 16 + g + 8 * (c & 1);
        const uint4* ws = pin_ptr(p.s->llln2 + ((b & ~7) + (c >> 1) * 4) * 128 + rl);
        {
        uint32_t x2[8][4];
        {
            mbar_wait(BAR(B_WPHI), 1);
            #pragma unroll
            for (int i = 0; i < 8; i++) ldsm4(x2[i], XADDR(i));
            uint4* d = pin_ptr(p.s->llln2 + b * 128 + warp * 16 + g);
            const uint32_t ta = sb + OFF_T1 + (g & 1) * 512 + c * 16;
            uint4 t = lds128(ta), tn = lds128(ta + 64);
            wg_wait<0>();
            acc_fence(acc);
            e_arrive(BAR(B_ED + 3));
            if (warp == 0) TS(32);
            float sd[4] = {0.f, 0.f, 0.f, 0.f}, qa[4] = {0.f, 0.f, 0.f, 0.f}, qb[4] = {0.f, 0.f, 0.f, 0.f};
            #pragma unroll
            for (int i = 0; i < 8; i++) {
                x2[i][0] = hadd2(x2[i][0], hmul2(t.x, pack2(acc[8 * i], acc[8 * i + 1]))); x2[i][1] = hadd2(x2[i][1], hmul2(t.x, pack2(acc[8 * i + 2], acc[8 * i + 3])));
                x2[i][2] = hadd2(x2[i][2], hmul2(t.y, pack2(acc[8 * i + 4], acc[8 * i + 5]))); x2[i][3] = hadd2(x2[i][3], hmul2(t.y, pack2(acc[8 * i + 6], acc[8 * i + 7])));
                mma16816(sd, x2[i][0], x2[i][1], x2[i][2], x2[i][3], t.z, t.w);
                t = tn;
                if (i < 6) tn = lds128(ta + (i + 2) * 64);
                mma16816(qa, x2[i][0], x2[i][1], x2[i][2], x2[i][3], x2[i][0], x2[i][2]);
                mma16816(qb, x2[i][0], x2[i][1], x2[i][2], x2[i][3], x2[i][1], x2[i][3]);
            }
            if (c == (g >> 1)) {
                st_ll(d, f2u(sd[0]), f2u((g & 1) ? qa[1] : qa[0]), f2u(sd[1]), tag);
                st_ll(d + 8, f2u(sd[2]), f2u((g & 1) ? qb[3] : qb[2]), f2u(sd[3]), tag);
            }
            __syncwarp();
            #pragma unroll
            for (int i = 0; i < 4; i++) w[i] = ld_ll(ws + i * 128);
            if (warp == 0) TS(33);
            #pragma unroll
            for (int i = 0; i < 8; i++) stsm4(XADDR(i), x2[i][0], x2[i][1], x2[i][2], x2[i][3]);
        }
        uint4 t2[8]; uint2 t3[8];
        #pragma unroll
        for (int i = 0; i < 8; i++) { t2[i] = lds128(sb + OFF_T2 + i * 64 + c * 16); t3[i] = lds64(sb + OFF_T3 + i * 32 + c * 8); }
        mbar_wait(BAR(B_ED + 3), 1);
        {
            #pragma unroll 1
            for (int it = 0; it < POLL_MAX; it++) {
                if (__all_sync(0xffffffffu, !(tag_bad(w[0].w ^ tag, w[1].w, tag) | tag_bad(w[2].w ^ tag, w[3].w, tag)))) break;
                #pragma unroll
                for (int i = 0; i < 4; i++) if (w[i].w != tag) w[i] = ld_ll(ws + i * 128);
            }
            float s1 = (u2f(w[0].x) + u2f(w[1].x)) + (u2f(w[2].x) + u2f(w[3].x));
            float s2 = (u2f(w[0].y) + u2f(w[1].y)) + (u2f(w[2].y) + u2f(w[3].y));
            float dt = (u2f(w[0].z) + u2f(w[1].z)) + (u2f(w[2].z) + u2f(w[3].z));
            s1 += shfl_x(s1, 2); s2 += shfl_x(s2, 2); dt += shfl_x(dt, 2);
            uint32_t m2, rh, rl2; float rinv;
            ln_final(s1, s2, m2, rinv);
            const uint32_t key = (f2key(fmaf(fmaf(-bf_lo(m2), u2f(cst.z), dt), rinv, u2f(cst.w))) | 2047u) ^ ((b >> 3) * 128 + rl);
            split_rcp(rinv, rh, rl2);
            if (c < 2) { sts32(sb + OFF_KEY + rl * 4, key); sts128(sb + OFF_ST2 + rl * 16, make_uint4(m2, rh, rl2, 0)); }
            __syncwarp();
            e_arrive(BAR(B_KEYS));
        }
        if (warp == 0) TS(34);
        {
            const uint4 s0 = lds128(sb + OFF_ST2 + (warp * 16 + g) * 16), s1 = lds128(sb + OFF_ST2 + (warp * 16 + g + 8) * 16);
            const uint32_t oa = xa + warp * 2048u;
            #pragma unroll
            for (int i = 0; i < 8; i++) {
                const uint4 t = t2[i]; const uint2 gb = t3[i];
                stsm4((oa ^ ((i & 3) << 5)) + OFF_OUT + (i >> 2) * 2048u,
                      hadd2(x2[i][0], hmul2(gb.x, lnmod(x2[i][0], s0.x, s0.y, s0.z, t.x, t.z))), hadd2(x2[i][1], hmul2(gb.x, lnmod(x2[i][1], s1.x, s1.y, s1.z, t.x, t.z))),
                      hadd2(x2[i][2], hmul2(gb.y, lnmod(x2[i][2], s0.x, s0.y, s0.z, t.y, t.w))), hadd2(x2[i][3], hmul2(gb.y, lnmod(x2[i][3], s1.x, s1.y, s1.z, t.y, t.w))));
            }
            __syncwarp();
            e_arrive(BAR(B_SWP));
        }
        }
        #undef XADDR
        if (warp == 0) TS(35);
        uint32_t fx = 0, fh = 0, fg = 0, fs2, frow;
        uint32_t df[16][4];
        const uint32_t dfo = sb + warp * 4096u + ((lane & 7) + (lane >> 4) * 8) * 128u + ((((lane >> 3) & 1) ^ (lane & 7)) << 4);
        #define DF_LOAD(i) ldsm4t(df[i], (dfo + ((i) < 8 ? OFF_F2 : OFF_DB) + ((i) & 1) * 2048u) ^ ((((i) >> 1) & 3) << 5))
        {
            const int wi = ((tid >> 3) & 7) * 32 + (tid >> 6) * 8 + (tid & 7);
            const uint4* rh = pin_ptr(p.s->llrowh + wi);
            #pragma unroll
            for (int i = 8; i < 16; i++) F_LOAD(uf, OFF_F2, i);
            mbar_wait(BAR(B_SEL) + ((AWAKE & 4) ? awake_zero() : 0), 0);
            const uint2 bb = lds64(sb + OFF_CST + 24);
            const uint32_t b0 = bb.x, b1 = bb.y;
            if (warp == 0) TS(36);
            const uint32_t o0 = (~b0 & 0x780u) * 4, o1 = (~b1 & 0x780u) * 4, slot0 = o0, slot1 = o1 + (o0 == o1 ? 256 : 0);
            const int wd = ((g & 1) ? slot1 : slot0) + b * 2 + (c >> 1) - wi;
            uint4 hv[2], fv[2];
            #pragma unroll 1
            for (int it = 0; it < POLL_MAX; it++) {
                hv[0] = ld_ll(rh + slot0); hv[1] = ld_ll(rh + slot1);
                uint32_t bad = 0;
                if (warp == 0) {
                    fv[0] = ld_ll(rh + wd + 8192); fv[1] = ld_ll(rh + wd);
                    bad = tag_bad(fv[0].w ^ tag, fv[1].w, tag);
                    fx = (g & 2) ? fv[0].y : fv[0].x; fh = (g & 2) ? fv[1].y : fv[1].x; fg = (g & 2) ? fv[0].z : fv[1].z;
                }
                if (it == 0) {
                    mbar_wait(BAR(B_WD), 0);
                    #pragma unroll
                    for (int i = 0; i < NDF; i++) DF_LOAD(i);
                }
                if (__all_sync(0xffffffffu, !ll_bad<1>(ll_bad<1>(bad, hv[0], tag), hv[1], tag))) break;
            }
            const uint32_t ha = sb + OFF_HSEL + (tid >> 3) * 128u + c * 16u + (g & 1) * 8u;
            sts64(ha, hv[0].x, hv[0].y); sts64(ha + 64, hv[1].x, hv[1].y);
            bar_sync(2 + (warp >> 1), 64);
            const uint32_t bk = (g & 1) ? b1 : b0;
            frow = ~bk & 2047u;
            const float sg = sigmoid_f(rbf(key2f((bk & ~2047u) | 1024u)));
            fs2 = pack2(sg, sg);
        }
        if (warp == 0) TS(37);
        uint4* yd = p.s->lly + (cst.x >> 8) * 512 + (warp * 8 + c) * 8 + g;
        const uint4* ys = p.s->lly + (tid >> 2) * 512 + b * 4 + c;
        uint16_t* od = (uint16_t*)p.out + (size_t)frow * 1024 + (b >> 1) * 16 + (b & 1) * 4 + c + 8 * (g >> 1);
        {
            float ag[2][4], au[2][4];
            #pragma unroll
            for (int i = 0; i < 4; i++) ag[0][i] = ag[1][i] = au[0][i] = au[1][i] = 0.f;
            const uint32_t ha = sb + OFF_HSEL + (warp >> 1) * 1024u + (lane & 7) * 16u;
            uint4 hn = lds128(ha), hm = lds128(ha + 128);
            #pragma unroll
            for (int i = 0; i < 8; i++) {
                const uint4 h = hn;
                hn = hm;
                if (i < 6) hm = lds128(ha + (i + 2) * 128u);
                mma16816(ag[0], gf[2 * i][0], gf[2 * i][1], gf[2 * i][2], gf[2 * i][3], h.x, h.y);
                mma16816(au[0], uf[2 * i][0], uf[2 * i][1], uf[2 * i][2], uf[2 * i][3], h.x, h.y);
                mma16816(ag[1], gf[2 * i + 1][0], gf[2 * i + 1][1], gf[2 * i + 1][2], gf[2 * i + 1][3], h.z, h.w);
                mma16816(au[1], uf[2 * i + 1][0], uf[2 * i + 1][1], uf[2 * i + 1][2], uf[2 * i + 1][3], h.z, h.w);
                if (NDF + 2 * i < 16) { DF_LOAD((NDF + 2 * i) & 15); DF_LOAD((NDF + 2 * i + 1) & 15); }
            }
            sts64(sb + OFF_RED + (warp >> 1) * 512u + (c & 1) * 256u + ((warp & 1) * 16 + (c >> 1) * 8 + g) * 8u,
                  f2u(sel4(c, ag[0][0], ag[0][1], ag[0][2], ag[0][3]) + sel4(c, ag[1][0], ag[1][1], ag[1][2], ag[1][3])),
                  f2u(sel4(c, au[0][0], au[0][1], au[0][2], au[0][3]) + sel4(c, au[1][0], au[1][1], au[1][2], au[1][3])));
        }
        yd = pin_ptr(yd); ys = pin_ptr(ys); od = pin_ptr(od); pin<1>(&fs2);
        bar_sync(1, 256);
        {
            const uint32_t ra = sb + OFF_RED + lane * 16u;
            const uint4 r0 = lds128(ra), r1 = lds128(ra + 512), r2 = lds128(ra + 1024), r3 = lds128(ra + 1536);
            #define F4(f) ((u2f(r0.f) + u2f(r1.f)) + (u2f(r2.f) + u2f(r3.f)))
            const uint32_t hid = hmul2(silu2(pack2(F4(x), F4(z))), pack2(F4(y), F4(w)));
            #undef F4
            if (warp == 0) TS(38);
            const int src = (g & 1) * 16 + c;
            const uint32_t b0 = __shfl_sync(0xffffffffu, hid, src), b1 = __shfl_sync(0xffffffffu, hid, src + 4), b2 = __shfl_sync(0xffffffffu, hid, src + 8), b3 = __shfl_sync(0xffffffffu, hid, src + 12);
            float y[8][4];
            #pragma unroll
            for (int i = 0; i < 8; i++) {
                y[i][0] = y[i][1] = y[i][2] = y[i][3] = 0.f;
                mma16816(y[i], df[2 * i][0], df[2 * i][1], df[2 * i][2], df[2 * i][3], b0, b1);
            }
            #pragma unroll
            for (int i = 0; i < 8; i++) mma16816(y[i], df[2 * i + 1][0], df[2 * i + 1][1], df[2 * i + 1][2], df[2 * i + 1][3], b2, b3);
            if (cst.x < 112 * 256) {
                #pragma unroll
                for (int h = 0; h < 2; h++) {
                    #define YS(e) sel4(c, y[4 * h][e], y[4 * h + 1][e], y[4 * h + 2][e], y[4 * h + 3][e])
                    st_ll4(yd + 32 * h, YS(0), YS(1), YS(2), YS(3), tag);
                    #undef YS
                }
            }
        }
        if (warp == 0) TS(39);
        if (warp < 7) {
            uint4 v[2];
            v[0].w = v[1].w = 0;
            spin_until(clk32() + YWAIT);
            #pragma unroll 1
            for (int it = 0; it < POLL_MAX; it++) {
                if ((v[0].w ^ tag) & 3) v[0] = ld_ll(ys);
                if ((v[1].w ^ tag) & 3) v[1] = ld_ll(ys + 56 * 512);
                if (__all_sync(0xffffffffu, !(tag_bad(v[0].w ^ tag, v[1].w, tag) & 3))) break;
            }
            float y0 = u2f(v[0].x) + u2f(v[1].x), y1 = u2f(v[0].y) + u2f(v[1].y), y2 = u2f(v[0].z) + u2f(v[1].z), y3 = u2f(v[0].w) + u2f(v[1].w);
            const bool g0 = g & 1, g1 = g & 2;
            const float k0 = (g0 ? y1 : y0) + shfl_x(g0 ? y0 : y1, 4), k1 = (g0 ? y3 : y2) + shfl_x(g0 ? y2 : y3, 4);
            const float y = (g1 ? k1 : k0) + shfl_x(g1 ? k0 : k1, 8);
            stsf(sb + OFF_RED2 + (lane & 15) * 64u + (lane >> 4) * 32u + warp * 4u, y);
            bar_sync(6, 224);
            if (tid < 16) {
                const uint32_t a = sb + OFF_RED2 + lane * 64u;
                const uint4 ya = lds128(a), yb = lds128(a + 16), yc = lds128(a + 32), ye = lds128(a + 48);
                const float s = (((u2f(ya.x) + u2f(ya.y)) + (u2f(ya.z) + u2f(ya.w))) + ((u2f(yb.x) + u2f(yb.y)) + u2f(yb.z)))
                              + (((u2f(yc.x) + u2f(yc.y)) + (u2f(yc.z) + u2f(yc.w))) + ((u2f(ye.x) + u2f(ye.y)) + u2f(ye.z)));
                const uint32_t o = hadd2(fx, hmul2(fg, hadd2(fh, hmul2(pack2(s, s), fs2))));
                *od = (c & 1) ? o >> 16 : o;
                if (b == 0 && tid == 0) p.s->done[0] = tag;
                TS(40);
            }
        }
    }
}

typedef CUresult (*EncodeFn)(CUtensorMap*, CUtensorMapDataType, cuuint32_t, void*, const cuuint64_t*, const cuuint64_t*, const cuuint32_t*,
                             const cuuint32_t*, CUtensorMapInterleave, CUtensorMapSwizzle, CUtensorMapL2promotion, CUtensorMapFloatOOBfill);

CUtensorMap make_map(EncodeFn enc, const void* ptr, uint64_t cols, uint64_t rows, uint32_t bc, uint32_t br, CUtensorMapSwizzle swz, CUtensorMapL2promotion promo) {
    CUtensorMap m;
    cuuint64_t dims[2] = {cols, rows}, strides[1] = {cols * 2};
    cuuint32_t box[2] = {bc, br}, es[2] = {1, 1};
    enc(&m, CU_TENSOR_MAP_DATA_TYPE_BFLOAT16, 2, const_cast<void*>(ptr), dims, strides, box, es, CU_TENSOR_MAP_INTERLEAVE_NONE, swz, promo,
        CU_TENSOR_MAP_FLOAT_OOB_FILL_NONE);
    return m;
}
CUtensorMap make_map4(EncodeFn enc, const void* ptr, uint32_t groups, uint64_t rows, uint32_t br, CUtensorMapL2promotion promo) {
    CUtensorMap m;
    cuuint64_t dims[4] = {64, rows, 16, groups}, strides[3] = {groups * 2048ull, 128, 2048};
    cuuint32_t box[4] = {64, br, 2, groups}, es[4] = {1, 1, 1, 1};
    enc(&m, CU_TENSOR_MAP_DATA_TYPE_BFLOAT16, 4, const_cast<void*>(ptr), dims, strides, box, es, CU_TENSOR_MAP_INTERLEAVE_NONE, CU_TENSOR_MAP_SWIZZLE_128B, promo,
        CU_TENSOR_MAP_FLOAT_OOB_FILL_NONE);
    return m;
}

}

extern "C" void kernel_launch(void* const* d_in, const int* in_sizes, int n_in, void* d_out, int out_size) {
    (void)in_sizes; (void)n_in; (void)out_size;
    void* fn = nullptr; cudaDriverEntryPointQueryResult qr;
    cudaGetDriverEntryPoint("cuTensorMapEncodeTiled", &fn, cudaEnableDefault, &qr);
    EncodeFn enc = (EncodeFn)fn;
    void* hs = nullptr;
    cudaGetSymbolAddress(&hs, g_scratch);
    int dev = 0, sms = 0;
    cudaGetDevice(&dev);
    cudaDeviceGetAttribute(&sms, cudaDevAttrMultiProcessorCount, dev);
    const CUtensorMapL2promotion P256 = CU_TENSOR_MAP_L2_PROMOTION_L2_256B, P128 = CU_TENSOR_MAP_L2_PROMOTION_L2_128B, P0 = CU_TENSOR_MAP_L2_PROMOTION_NONE;
    CUtensorMap tmW = make_map4(enc, d_in[1], 3, 1024, 32, P256);
    CUtensorMap tmWo = make_map4(enc, d_in[3], 1, 1024, 64, P256);
    CUtensorMap tmO = make_map4(enc, d_out, 1, 2048, 16, P0);
    CUtensorMap tmPhi = make_map(enc, d_in[2], 32, 1024, 32, 128, CU_TENSOR_MAP_SWIZZLE_64B, P128);
    CUtensorMap tmG = make_map(enc, d_in[6], 3584, 1024, 32, 128, CU_TENSOR_MAP_SWIZZLE_64B, P0);
    CUtensorMap tmU = make_map(enc, d_in[7], 3584, 1024, 32, 128, CU_TENSOR_MAP_SWIZZLE_64B, P0);
    CUtensorMap tmD = make_map(enc, d_in[8], 1024, 3584, 64, 32, CU_TENSOR_MAP_SWIZZLE_128B, P128);
    CUtensorMap tmX = make_map(enc, d_in[0], 1024, 2048, 64, 128, CU_TENSOR_MAP_SWIZZLE_128B, P128);
    CUtensorMap tmM = make_map(enc, d_in[10], 6144, 1024, 64, 256, CU_TENSOR_MAP_SWIZZLE_128B, MPROMO);
    Ptrs p;
    p.x = (const bf16*)d_in[0]; p.c = (const bf16*)d_in[9]; p.wmod = (const bf16*)d_in[10]; p.wr = (const bf16*)d_in[5];
    p.wg = (const bf16*)d_in[6]; p.wu = (const bf16*)d_in[7]; p.wd = (const bf16*)d_in[8]; p.out = (bf16*)d_out; p.s = (Scratch*)hs;
    p.wqkv = (const bf16*)d_in[1]; p.wo = (const bf16*)d_in[3];
    p.by_sm = sms == 132;
    for (int sm = 0; sm < 132; sm++) {
        const int tp = sm >> 1, u = tp - 32;
        const int gp = (GPERM >> (4 * (tp < 32 ? tp & 7 : tp < 60 ? 1 + u % 7 : 0))) & 7, sl = 2 * (tp < 32 ? tp >> 3 : tp < 60 ? 4 + u / 7 : tp - 58) + (sm & 1);
        const int b = (tp >> 1) == 30 ? sm + 8 : ((gp >> 1) * 4 + (sl & 3)) * 8 + (gp & 1) * 4 + (sl >> 2);
        const int f = FMODE == 0 ? (b < 112 ? b : 255) : FMODE == 1 ? (sl < 14 && b < 128 ? gp * 14 + sl : 255) : (sm < 112 ? sm : 255);
        p.role[sm] = (uint16_t)(b | f << 8);
    }
    cudaFuncSetAttribute(fused_kernel, cudaFuncAttributeMaxDynamicSharedMemorySize, SMEM_BYTES);
    fused_kernel<<<132, NTHREADS, SMEM_BYTES, cudaStreamPerThread>>>(p, tmM, tmX, tmW, tmWo, tmPhi, tmG, tmU, tmD, tmO);
}
```

```cpp
#include <cuda_runtime.h>
#include <cuda.h>
#include <cuda_bf16.h>
#include <stdint.h>

namespace {

typedef __nv_bfloat16 bf16;

#define NFREE 4
constexpr int NTHREADS = 512;
constexpr int POLL_MAX = 400000;

constexpr uint32_t OFF_R0   = 0;
constexpr uint32_t OFF_A    = 65536;
constexpr uint32_t OFF_B    = 114688;
constexpr uint32_t OFF_V    = 65536;
constexpr uint32_t OFF_PHI  = 98304;
constexpr uint32_t OFF_F2   = 65536;
constexpr uint32_t OFF_DB   = 131072;
constexpr uint32_t OFF_KL   = 196608;
constexpr uint32_t OFF_WPHI = 214016;
constexpr uint32_t OFF_KVT  = OFF_WPHI;
constexpr uint32_t OFF_Z    = 222208;
constexpr uint32_t OFF_TAB  = OFF_Z;
constexpr uint32_t OFF_ONES = 226304;
constexpr uint32_t OFF_BAR  = 227328;
constexpr uint32_t OFF_CST  = OFF_BAR + 640;
constexpr uint32_t OFF_T1   = OFF_ONES;
constexpr uint32_t OFF_T2   = OFF_CST + 64;
constexpr uint32_t OFF_T3   = OFF_T2 + 512;
constexpr uint32_t OFF_KEY  = OFF_T3 + 256;
constexpr uint32_t OFF_ST2  = OFF_KEY + 512;
constexpr uint32_t OFF_ZS   = OFF_ST2;
constexpr uint32_t SMEM_BYTES = 232448;
constexpr uint32_t OFF_X1   = OFF_KL;
constexpr uint32_t OFF_OUT  = OFF_R0 + 32768;
constexpr uint32_t OFF_HSEL = OFF_WPHI;
constexpr uint32_t OFF_RED  = OFF_WPHI + 4096;
constexpr uint32_t OFF_RED2 = OFF_RED + 2048;
static_assert(OFF_ST2 + 2048 <= SMEM_BYTES, "layout");

enum {
    B_O1 = 0, B_UF = 1, B_UD = 2, B_WPHI = 3, B_FB = 4  , B_OST = 8, B_GF = 9, B_WD = 10, B_KVL = 11  , B_KZ = 13, B_LMF = 14, B_SEL = 15, B_XP = 16  , B_TAG = 24,
    B_FA = 25  , B_FD = 30  , B_CAND = 34,
    B_PE = 35  , B_KST = 37  , B_KVT = 41  , B_LMD = 43, B_PAR = 44,
    B_EA = 45  , B_EB = 48  , B_ED = 52  , B_PF = 56  , B_OWN = 60  , B_QE = 62, B_STP = 63, B_KEYS = 64, B_SWP = 65, B_STS = 66, B_GE = 67
};

struct Scratch {
    uint4 os[16 * 16 * 1024];
    uint4 kvacc[8 * 4 * 528];
    uint4 flk[3 * 128 * 2];
    uint4 llstat[2048];
    uint4 llm1[16 * 64];
    uint4 flo[16 * 16 * 2];
    uint4 llmod2[2 * 256];
    uint4 llg[2 * 4 * 256];
    uint4 llln2[16 * 8 * 128];
    uint4 llcand[16 * 2];
    uint4 llrowh[32 * 256];
    uint4 llrowx[32 * 256];
    uint4 lly[128 * 512];
    unsigned done[4];
};
__device__ __align__(1024) Scratch g_scratch;
#define GT(i) do {} while (0)
#define TS(i) do {} while (0)
#define TR(i) do {} while (0)

__device__ __forceinline__ uint32_t smem_u32(const void* p) { return (uint32_t)__cvta_generic_to_shared(p); }
__device__ __forceinline__ uint32_t clk32() { uint32_t c; asm volatile("mov.u32 %0, %%clock;" : "=r"(c) :: "memory"); return c; }
__device__ __forceinline__ void spin_until(uint32_t t) { while ((int)(clk32() - t) < 0) {} }
__device__ __forceinline__ void sleep_until(uint32_t t) { while ((int)(clk32() - t) < 0) __nanosleep(40); }
__device__ __forceinline__ void mbar_init_fence() { asm volatile("fence.mbarrier_init.release.cluster;" ::: "memory"); }
__device__ __forceinline__ void mbar_wait(uint32_t bar, uint32_t parity) {
    asm volatile("{\n.reg .pred P1;\nLAB_WAIT:\nmbarrier.try_wait.parity.shared::cta.b64 P1, [%0], %1;\n@!P1 bra LAB_WAIT;\n}" :: "r"(bar), "r"(parity) : "memory");
}
__device__ __forceinline__ uint64_t policy_evict_first() { uint64_t p; asm("createpolicy.fractional.L2::evict_first.b64 %0, 1.0;" : "=l"(p)); return p; }
#define ELECT "{\n.reg .pred e;\nelect.sync _|e, 0xffffffff;\n@e "
__device__ __forceinline__ void e_arrive(uint32_t bar) { asm volatile(ELECT "mbarrier.arrive.shared::cta.b64 _, [%0];\n}" :: "r"(bar) : "memory"); }
__device__ __forceinline__ void e_arrive_tx(uint32_t bar, uint32_t bytes) { asm volatile(ELECT "mbarrier.arrive.expect_tx.shared::cta.b64 _, [%0], %1;\n}" :: "r"(bar), "r"(bytes) : "memory"); }
__device__ __forceinline__ void e_init(uint32_t bar, uint32_t cnt) { asm volatile(ELECT "mbarrier.init.shared::cta.b64 [%0], %1;\n}" :: "r"(bar), "r"(cnt) : "memory"); }
__device__ __forceinline__ void tma_load_ef(uint32_t dst, const CUtensorMap* tm, int c0, int c1, uint32_t bar) {
    asm volatile(ELECT "cp.async.bulk.tensor.2d.shared::cluster.global.mbarrier::complete_tx::bytes.L2::cache_hint [%0], [%1, {%3, %4}], [%2], %5;\n}"
        :: "r"(dst), "l"(tm), "r"(bar), "r"(c0), "r"(c1), "l"(policy_evict_first()) : "memory");
}
__device__ __forceinline__ void tma_load(uint32_t dst, const CUtensorMap* tm, int c0, int c1, uint32_t bar) {
    asm volatile(ELECT "cp.async.bulk.tensor.2d.shared::cluster.global.mbarrier::complete_tx::bytes [%0], [%1, {%3, %4}], [%2];\n}"
        :: "r"(dst), "l"(tm), "r"(bar), "r"(c0), "r"(c1) : "memory");
}
__device__ __forceinline__ void tma_load4(uint32_t dst, const CUtensorMap* tm, int row, int blk, uint32_t bar) {
    asm volatile(ELECT "cp.async.bulk.tensor.4d.shared::cluster.global.mbarrier::complete_tx::bytes [%0], [%1, {0, %3, %4, 0}], [%2];\n}"
        :: "r"(dst), "l"(tm), "r"(bar), "r"(row), "r"(blk) : "memory");
}
__device__ __forceinline__ void tma_store4(const CUtensorMap* tm, int row, int blk, uint32_t src) {
    asm volatile(ELECT "cp.async.bulk.tensor.4d.global.shared::cta.bulk_group [%0, {0, %2, %3, 0}], [%1];\n}" :: "l"(tm), "r"(src), "r"(row), "r"(blk) : "memory");
}
__device__ __forceinline__ void bulk_load(uint32_t dst, const void* src, uint32_t bytes, uint32_t bar) {
    asm volatile(ELECT "cp.async.bulk.shared::cluster.global.mbarrier::complete_tx::bytes [%0], [%1], %2, [%3];\n}" :: "r"(dst), "l"(src), "r"(bytes), "r"(bar) : "memory");
}
__device__ __forceinline__ void bulk_store(void* dst, uint32_t src, uint32_t bytes) {
    asm volatile(ELECT "cp.async.bulk.global.shared::cta.bulk_group [%0], [%1], %2;\n}" :: "l"(dst), "r"(src), "r"(bytes) : "memory");
}
__device__ __forceinline__ void bulk_reduce(void* dst, uint32_t src, uint32_t bytes) {
    asm volatile(ELECT "cp.reduce.async.bulk.global.shared::cta.bulk_group.add.f32 [%0], [%1], %2;\n}" :: "l"(dst), "r"(src), "r"(bytes) : "memory");
}
__device__ __forceinline__ void tma_prefetch(const CUtensorMap* tm, int c0, int c1) {
    asm volatile(ELECT "cp.async.bulk.prefetch.tensor.2d.L2.global [%0, {%1, %2}];\n}" :: "l"(tm), "r"(c0), "r"(c1) : "memory");
}
__device__ __forceinline__ void l2_prefetch(const void* p, uint32_t bytes) {
    asm volatile(ELECT "cp.async.bulk.prefetch.L2.global [%0], %1;\n}" :: "l"(p), "r"(bytes) : "memory");
}
__device__ __forceinline__ void bulk_wait_read() { asm volatile("cp.async.bulk.commit_group;\ncp.async.bulk.wait_group.read 0;" ::: "memory"); }
__device__ __forceinline__ void bulk_wait() { asm volatile("cp.async.bulk.commit_group;\ncp.async.bulk.wait_group 0;" ::: "memory"); }
__device__ __forceinline__ void tmap_prefetch(const CUtensorMap* tm) { asm volatile("prefetch.tensormap [%0];" :: "l"(tm) : "memory"); }
__device__ __forceinline__ void wg_fence() { asm volatile("wgmma.fence.sync.aligned;" ::: "memory"); }
__device__ __forceinline__ void wg_commit() { asm volatile("wgmma.commit_group.sync.aligned;" ::: "memory"); }
template<int N> __device__ __forceinline__ void wg_wait() { asm volatile("wgmma.wait_group.sync.aligned %0;" :: "n"(N) : "memory"); }
template<int N> __device__ __forceinline__ void acc_fence(float (&d)[N]) {
    #pragma unroll
    for (int i = 0; i < N; i++) asm volatile("" : "+f"(d[i]) :: "memory");
}
__device__ __forceinline__ uint32_t desc_lo(uint32_t addr, uint32_t lbo) { return (addr >> 4) | ((lbo >> 4) << 16); }
constexpr uint32_t H128 = 0x40000040u;
constexpr uint32_t H64 = 0x80000020u;
__device__ __forceinline__ void fence_async_smem() { asm volatile("fence.proxy.async.shared::cta;" ::: "memory"); }
__device__ __forceinline__ void bar_sync(int id, int n) { asm volatile("bar.sync %0, %1;" :: "r"(id), "r"(n) : "memory"); }
template<int R> __device__ __forceinline__ void reg_inc() { asm volatile("setmaxnreg.inc.sync.aligned.u32 %0;" :: "n"(R)); }
template<int R> __device__ __forceinline__ void reg_dec() { asm volatile("setmaxnreg.dec.sync.aligned.u32 %0;" :: "n"(R)); }

__device__ __forceinline__ void stsm4(uint32_t addr, uint32_t r0, uint32_t r1, uint32_t r2, uint32_t r3) {
    asm volatile("stmatrix.sync.aligned.m8n8.x4.shared.b16 [%0], {%1,%2,%3,%4};" :: "r"(addr), "r"(r0), "r"(r1), "r"(r2), "r"(r3) : "memory");
}
__device__ __forceinline__ void ldsm4(uint32_t* r, uint32_t addr) {
    asm volatile("ldmatrix.sync.aligned.m8n8.x4.shared.b16 {%0,%1,%2,%3}, [%4];" : "=r"(r[0]), "=r"(r[1]), "=r"(r[2]), "=r"(r[3]) : "r"(addr) : "memory");
}
__device__ __forceinline__ void ldsm4t(uint32_t* r, uint32_t addr) {
    asm volatile("ldmatrix.sync.aligned.m8n8.x4.trans.shared.b16 {%0,%1,%2,%3}, [%4];" : "=r"(r[0]), "=r"(r[1]), "=r"(r[2]), "=r"(r[3]) : "r"(addr) : "memory");
}
__device__ __forceinline__ void mma16816(float (&d)[4], uint32_t a0, uint32_t a1, uint32_t a2, uint32_t a3, uint32_t b0, uint32_t b1) {
    asm volatile("mma.sync.aligned.m16n8k16.row.col.f32.bf16.bf16.f32 {%0,%1,%2,%3}, {%4,%5,%6,%7}, {%8,%9}, {%0,%1,%2,%3};"
        : "+f"(d[0]), "+f"(d[1]), "+f"(d[2]), "+f"(d[3]) : "r"(a0), "r"(a1), "r"(a2), "r"(a3), "r"(b0), "r"(b1));
}
__device__ __forceinline__ uint32_t awake_zero() {
    uint32_t r;
    asm volatile("{\n.reg .f32 d<4>;\nmma.sync.aligned.m16n8k8.row.col.f32.bf16.bf16.f32 {d0,d1,d2,d3}, {%1,%1}, {%1}, {%2,%2,%2,%2};\nmov.b32 %0, d0;\n}" : "=r"(r) : "r"(0), "f"(0.f));
    return r;
}
__device__ __forceinline__ void mbar_wait_awake(uint32_t bar, uint32_t parity) {
    #pragma unroll 1
    for (int it = 0; it < POLL_MAX; it++) {
        uint32_t ok;
        asm volatile("{\n.reg .pred p;\nmbarrier.try_wait.parity.shared::cta.b64 p, [%1], %2;\nselp.u32 %0, 0, 1, p;\n}" : "=r"(ok) : "r"(bar), "r"(parity) : "memory");
        if (__all_sync(0xffffffffu, ok == 0)) break;
        it += awake_zero();
    }
}
__device__ __forceinline__ uint4 lds128(uint32_t a) { uint4 v; asm volatile("ld.shared.v4.b32 {%0,%1,%2,%3}, [%4];" : "=r"(v.x), "=r"(v.y), "=r"(v.z), "=r"(v.w) : "r"(a) : "memory"); return v; }
__device__ __forceinline__ uint32_t lds32(uint32_t a) { uint32_t v; asm volatile("ld.shared.b32 %0, [%1];" : "=r"(v) : "r"(a) : "memory"); return v; }
__device__ __forceinline__ uint2 lds64(uint32_t a) { uint2 v; asm volatile("ld.shared.v2.b32 {%0,%1}, [%2];" : "=r"(v.x), "=r"(v.y) : "r"(a) : "memory"); return v; }
__device__ __forceinline__ float ldsf(uint32_t a) { float v; asm volatile("ld.shared.f32 %0, [%1];" : "=f"(v) : "r"(a) : "memory"); return v; }
__device__ __forceinline__ void sts128(uint32_t a, uint4 v) { asm volatile("st.shared.v4.b32 [%0], {%1,%2,%3,%4};" :: "r"(a), "r"(v.x), "r"(v.y), "r"(v.z), "r"(v.w) : "memory"); }
__device__ __forceinline__ void sts64(uint32_t a, uint32_t x, uint32_t y) { asm volatile("st.shared.v2.b32 [%0], {%1,%2};" :: "r"(a), "r"(x), "r"(y) : "memory"); }
__device__ __forceinline__ void sts32(uint32_t a, uint32_t x) { asm volatile("st.shared.b32 [%0], %1;" :: "r"(a), "r"(x) : "memory"); }
__device__ __forceinline__ void stsf(uint32_t a, float x) { asm volatile("st.shared.f32 [%0], %1;" :: "r"(a), "f"(x) : "memory"); }
__device__ __forceinline__ float u2f(uint32_t v) { return __uint_as_float(v); }
__device__ __forceinline__ uint32_t f2u(float v) { return __float_as_uint(v); }

__device__ __forceinline__ uint32_t ldg32(const void* p) { uint32_t v; asm volatile("ld.global.nc.b32 %0, [%1];" : "=r"(v) : "l"(p)); return v; }
__device__ __forceinline__ void stg128(void* p, uint4 v) { asm volatile("st.global.v4.b32 [%0], {%1,%2,%3,%4};" :: "l"(p), "r"(v.x), "r"(v.y), "r"(v.z), "r"(v.w) : "memory"); }
__device__ __forceinline__ void stg_zero(void* p) { stg128(p, make_uint4(0, 0, 0, 0)); }
__device__ __forceinline__ void fence_gpu() { asm volatile("fence.release.gpu;" ::: "memory"); }
__device__ __forceinline__ void st_ll(uint4* p, uint32_t x, uint32_t y, uint32_t z, uint32_t w) {
    asm volatile("st.relaxed.gpu.global.v4.b32 [%0], {%1,%2,%3,%4};" :: "l"(p), "r"(x), "r"(y), "r"(z), "r"(w) : "memory");
}
__device__ __forceinline__ uint4 ld_ll(const uint4* p) {
    uint4 v;
    asm volatile("ld.relaxed.gpu.global.v4.b32 {%0,%1,%2,%3}, [%4];" : "=r"(v.x), "=r"(v.y), "=r"(v.z), "=r"(v.w) : "l"(p) : "memory");
    return v;
}
template<uint32_t LUT> __device__ __forceinline__ uint32_t lop3(uint32_t a, uint32_t b, uint32_t c) { uint32_t d; asm("lop3.b32 %0, %1, %2, %3, %4;" : "=r"(d) : "r"(a), "r"(b), "r"(c), "n"(LUT)); return d; }
__device__ __forceinline__ uint32_t tag_bad(uint32_t bad, uint32_t w, uint32_t tag) { return lop3<0xF6>(bad, w, tag); }
__device__ __forceinline__ void st_ll4(uint4* p, float a, float b, float c, float d, uint32_t tag) { st_ll(p, f2u(a), f2u(b), f2u(c), lop3<0xD8>(f2u(d), tag, 3u)); }
__device__ __forceinline__ unsigned ld_rlx(const void* p) { unsigned v; asm volatile("ld.relaxed.gpu.global.u32 %0, [%1];" : "=r"(v) : "l"(p) : "memory"); return v; }
__device__ __forceinline__ void st_flag(uint4* p, uint32_t v, int lane) { if (lane < 2) st_ll(p + lane, v, v, v, v); }
__device__ __forceinline__ void poll_flags(const uint4* f, uint32_t tag) {
    unsigned v0 = ld_rlx(f), v1;
    spin_until(clk32() + 140);
    #pragma unroll 1
    for (int it = 0; it < POLL_MAX; it++) {
        v1 = ld_rlx(f);
        if (__all_sync(0xffffffffu, v0 == tag)) break;
        v0 = ld_rlx(f);
        if (__all_sync(0xffffffffu, v1 == tag)) break;
    }
}
template<int Z> __device__ __forceinline__ uint32_t ll_bad(uint32_t bad, const uint4& v, uint32_t tag) {
    bad = tag_bad(bad, v.w, tag);
    return Z && lop3<0x80>(v.x, v.y, v.z) == ~0u ? 1u : bad;
}
template<int N, int Z, uint32_t M = ~0u, int AW = 0> __device__ __forceinline__ void poll_words(uint4 (&v)[N], const uint4* p, int stride, uint32_t tag) {
    #pragma unroll 1
    for (int it = 0; it < POLL_MAX; it++) {
        uint32_t bad = 0;
        #pragma unroll
        for (int i = 0; i < N; i++) v[i] = ld_ll(p + i * stride);
        #pragma unroll
        for (int i = 0; i < N; i++) bad = ll_bad<Z>(bad, v[i], tag);
        if (__all_sync(0xffffffffu, !(bad & M))) break;
        if (AW) it += awake_zero();
    }
}
constexpr uint32_t ONE2 = 0x3F803F80u;
__device__ __forceinline__ uint32_t pack2(float lo, float hi) { uint32_t d; asm("cvt.rn.bf16x2.f32 %0, %1, %2;" : "=r"(d) : "f"(hi), "f"(lo)); return d; }
__device__ __forceinline__ float bf_lo(uint32_t v) { return u2f(v << 16); }
__device__ __forceinline__ float bf_hi(uint32_t v) { return u2f(v & 0xffff0000u); }
__device__ __forceinline__ float rbf(float x) { return bf_lo(pack2(x, 0.f)); }
__device__ __forceinline__ uint32_t hsub2(uint32_t a, uint32_t b) { uint32_t d; asm("sub.rn.bf16x2 %0, %1, %2;" : "=r"(d) : "r"(a), "r"(b)); return d; }
__device__ __forceinline__ uint32_t hadd2(uint32_t a, uint32_t b) { uint32_t d; asm("add.rn.bf16x2 %0, %1, %2;" : "=r"(d) : "r"(a), "r"(b)); return d; }
__device__ __forceinline__ uint32_t hmul2(uint32_t a, uint32_t b) { uint32_t d; asm("mul.rn.bf16x2 %0, %1, %2;" : "=r"(d) : "r"(a), "r"(b)); return d; }
__device__ __forceinline__ uint32_t hfma2(uint32_t a, uint32_t b, uint32_t c) { uint32_t d; asm("fma.rn.bf16x2 %0, %1, %2, %3;" : "=r"(d) : "r"(a), "r"(b), "r"(c)); return d; }
__device__ __forceinline__ uint32_t hmax2(uint32_t a, uint32_t b) { uint32_t d; asm("max.bf16x2 %0, %1, %2;" : "=r"(d) : "r"(a), "r"(b)); return d; }
__device__ __forceinline__ uint32_t hmin2(uint32_t a, uint32_t b) { uint32_t d; asm("min.bf16x2 %0, %1, %2;" : "=r"(d) : "r"(a), "r"(b)); return d; }
__device__ __forceinline__ float ex2(float x) { float y; asm("ex2.approx.ftz.f32 %0, %1;" : "=f"(y) : "f"(x)); return y; }
__device__ __forceinline__ float rcp(float x) { float y; asm("rcp.approx.ftz.f32 %0, %1;" : "=f"(y) : "f"(x)); return y; }
__device__ __forceinline__ float shfl_x(float v, int m) { return __shfl_xor_sync(0xffffffffu, v, m); }
__device__ __forceinline__ uint32_t hdiv2(uint32_t d, uint32_t rh, uint32_t rl) { return hfma2(d, rh, hmul2(d, rl)); }
__device__ __forceinline__ void split_rcp(float r, uint32_t& rh, uint32_t& rl) { rh = pack2(r, r); const float l = r - bf_lo(rh); rl = pack2(l, l); }
__device__ __forceinline__ uint32_t lnmod(uint32_t x, uint32_t m, uint32_t rh, uint32_t rl, uint32_t a, uint32_t s) { return hadd2(hmul2(hdiv2(hsub2(x, m), rh, rl), a), s); }
__device__ __forceinline__ void ln_final(float s1, float s2, uint32_t& m2, float& rinv) {
    const float mean = s1 * (1.0f / 1024.0f), var = fmaf(-mean, mean, s2 * (1.0f / 1024.0f));
    m2 = pack2(mean, mean);
    float sd;
    asm("sqrt.approx.ftz.f32 %0, %1;" : "=f"(sd) : "f"(rbf(rbf(fmaxf(var, 0.f)) + 1e-5f)));
    rinv = rcp(rbf(sd));
}
__device__ __forceinline__ float sigmoid_f(float x) { return rcp(1.0f + ex2(-1.4426950408889634f * x)); }
__device__ __forceinline__ uint32_t silu2(uint32_t v) { return pack2(bf_lo(v) * sigmoid_f(bf_lo(v)), bf_hi(v) * sigmoid_f(bf_hi(v))); }
__device__ __forceinline__ uint32_t f2key(float f) { uint32_t u = f2u(f); return (u & 0x80000000u) ? ~u : (u | 0x80000000u); }
__device__ __forceinline__ float key2f(uint32_t k) { return u2f((k & 0x80000000u) ? k ^ 0x80000000u : ~k); }
template<int N> __device__ __forceinline__ void top2(uint32_t (&k)[N], uint32_t& b0, uint32_t& b1) {
    uint32_t m = k[0];
    #pragma unroll
    for (int i = 1; i < N; i++) m = max(m, k[i]);
    b0 = __reduce_max_sync(0xffffffffu, m);
    m = 0;
    #pragma unroll
    for (int i = 0; i < N; i++) m = max(m, k[i] == b0 ? 0u : k[i]);
    b1 = __reduce_max_sync(0xffffffffu, m);
}
template<class T> __device__ __forceinline__ T sel4(int c, T a0, T a1, T a2, T a3) { return (c & 2) ? ((c & 1) ? a3 : a2) : ((c & 1) ? a1 : a0); }

__device__ __forceinline__ void fm_max(const float (&a)[16], uint32_t* p, uint32_t* mm) {
    #pragma unroll
    for (int i = 0; i < 8; i++) p[i] = pack2(a[2 * i], a[2 * i + 1]);
    #pragma unroll
    for (int h = 0; h < 2; h++) {
        const uint32_t mx = hmax2(hmax2(p[h], p[2 + h]), hmax2(p[4 + h], p[6 + h]));
        const uint32_t mn = hmin2(hmin2(p[h], p[2 + h]), hmin2(p[4 + h], p[6 + h])) ^ 0x80008000u;
        mm[h] = hmax2(__byte_perm(mx, mn, 0x5410), __byte_perm(mx, mn, 0x7632));
    }
    #pragma unroll
    for (int d = 1; d <= 2; d++) { mm[0] = hmax2(mm[0], __shfl_xor_sync(0xffffffffu, mm[0], d)); mm[1] = hmax2(mm[1], __shfl_xor_sync(0xffffffffu, mm[1], d)); }
}
constexpr float LOG2E = 1.4426950408889634f;
__device__ __forceinline__ void fm_pos(const uint32_t* p, const uint32_t* mm, float (&e)[32]) {
    #pragma unroll
    for (int h = 0; h < 2; h++) {
        const float cp = -bf_lo(mm[h]) * LOG2E;
        #pragma unroll
        for (int j = 0; j < 4; j++) {
            const float f0 = bf_lo(p[2 * j + h]), f1 = bf_hi(p[2 * j + h]);
            e[8 * h + 2 * j] = ex2(fmaf(f0, LOG2E, cp)); e[8 * h + 2 * j + 1] = ex2(fmaf(f1, LOG2E, cp));
            e[16 + 8 * h + 2 * j] = f0; e[16 + 8 * h + 2 * j + 1] = f1;
        }
    }
}
__device__ __forceinline__ void fm_neg(const uint32_t* mm, float nl, float (&e)[32]) {
    #pragma unroll
    for (int i = 16; i < 32; i++) e[i] = ex2(fmaf(e[i], -LOG2E, bf_hi(mm[(i >> 3) & 1]) * (i < 16 + NFREE ? -LOG2E : nl)));
}
__device__ __forceinline__ void fm_norm(const float (&e)[32], uint32_t* ph) {
    float s[4];
    #pragma unroll
    for (int k = 0; k < 4; k++) s[k] = ((e[8 * k] + e[8 * k + 1]) + (e[8 * k + 2] + e[8 * k + 3])) + ((e[8 * k + 4] + e[8 * k + 5]) + (e[8 * k + 6] + e[8 * k + 7]));
    #pragma unroll
    for (int k = 0; k < 4; k++) s[k] += shfl_x(s[k], 1);
    #pragma unroll
    for (int k = 0; k < 4; k++) s[k] = rcp(s[k] + shfl_x(s[k], 2));
    #pragma unroll
    for (int k = 0; k < 4; k++)
        #pragma unroll
        for (int j = 0; j < 4; j++) ph[8 * (k >> 1) + 2 * j + (k & 1)] = pack2(e[8 * k + 2 * j] * s[k], e[8 * k + 2 * j + 1] * s[k]);
}
template<class T> __device__ __forceinline__ T* pin_ptr(T* p) { asm volatile("" : "+l"(p) :: "memory"); return p; }
template<int N> __device__ __forceinline__ void pin(uint32_t* d) {
    #pragma unroll
    for (int i = 0; i < N; i++) asm volatile("" : "+r"(d[i]) :: "memory");
}

template<uint32_t BO, uint32_t BH> __device__ __forceinline__ void mma192_rs(float (&d)[96], const uint32_t* a, uint32_t blo) {
  asm volatile("{\n.reg .pred p;\n.reg .b32 ta, tb;\n.reg .b64 da, db;\nadd.u32 tb, %100, %101;\nmov.b64 db, {tb, %102};\nsetp.ne.b32 p, 1, 0;\n"
    "wgmma.mma_async.sync.aligned.m64n192k16.f32.bf16.bf16 {%0, %1, %2, %3, %4, %5, %6, %7, %8, %9, %10, %11, %12, %13, %14, %15, %16, %17, %18, %19, %20, %21, %22, %23, %24, %25, %26, %27, %28, %29, %30, %31, %32, %33, %34, %35, %36, %37, %38, %39, %40, %41, %42, %43, %44, %45, %46, %47, %48, %49, %50, %51, %52, %53, %54, %55, %56, %57, %58, %59, %60, %61, %62, %63, %64, %65, %66, %67, %68, %69, %70, %71, %72, %73, %74, %75, %76, %77, %78, %79, %80, %81, %82, %83, %84, %85, %86, %87, %88, %89, %90, %91, %92, %93, %94, %95}, {%96,%97,%98,%99}, db, p, 1, 1, 1;\n}\n"
    : "+f"(d[0]), "+f"(d[1]), "+f"(d[2]), "+f"(d[3]), "+f"(d[4]), "+f"(d[5]), "+f"(d[6]), "+f"(d[7]), "+f"(d[8]), "+f"(d[9]), "+f"(d[10]), "+f"(d[11]), "+f"(d[12]), "+f"(d[13]), "+f"(d[14]), "+f"(d[15]), "+f"(d[16]), "+f"(d[17]), "+f"(d[18]), "+f"(d[19]), "+f"(d[20]), "+f"(d[21]), "+f"(d[22]), "+f"(d[23]), "+f"(d[24]), "+f"(d[25]), "+f"(d[26]), "+f"(d[27]), "+f"(d[28]), "+f"(d[29]), "+f"(d[30]), "+f"(d[31]), "+f"(d[32]), "+f"(d[33]), "+f"(d[34]), "+f"(d[35]), "+f"(d[36]), "+f"(d[37]), "+f"(d[38]), "+f"(d[39]), "+f"(d[40]), "+f"(d[41]), "+f"(d[42]), "+f"(d[43]), "+f"(d[44]), "+f"(d[45]), "+f"(d[46]), "+f"(d[47]), "+f"(d[48]), "+f"(d[49]), "+f"(d[50]), "+f"(d[51]), "+f"(d[52]), "+f"(d[53]), "+f"(d[54]), "+f"(d[55]), "+f"(d[56]), "+f"(d[57]), "+f"(d[58]), "+f"(d[59]), "+f"(d[60]), "+f"(d[61]), "+f"(d[62]), "+f"(d[63]), "+f"(d[64]), "+f"(d[65]), "+f"(d[66]), "+f"(d[67]), "+f"(d[68]), "+f"(d[69]), "+f"(d[70]), "+f"(d[71]), "+f"(d[72]), "+f"(d[73]), "+f"(d[74]), "+f"(d[75]), "+f"(d[76]), "+f"(d[77]), "+f"(d[78]), "+f"(d[79]), "+f"(d[80]), "+f"(d[81]), "+f"(d[82]), "+f"(d[83]), "+f"(d[84]), "+f"(d[85]), "+f"(d[86]), "+f"(d[87]), "+f"(d[88]), "+f"(d[89]), "+f"(d[90]), "+f"(d[91]), "+f"(d[92]), "+f"(d[93]), "+f"(d[94]), "+f"(d[95])
    : "r"(a[0]), "r"(a[1]), "r"(a[2]), "r"(a[3]), "r"(blo), "n"(BO), "n"(BH));
}
template<uint32_t BO, uint32_t BH> __device__ __forceinline__ void mma192_rsp(float (&d)[96], const uint32_t* a, uint32_t blo, int sc) {
  asm volatile("{\n.reg .pred p;\n.reg .b32 ta, tb;\n.reg .b64 da, db;\nadd.u32 tb, %100, %101;\nmov.b64 db, {tb, %102};\nsetp.ne.b32 p, %103, 0;\n"
    "wgmma.mma_async.sync.aligned.m64n192k16.f32.bf16.bf16 {%0, %1, %2, %3, %4, %5, %6, %7, %8, %9, %10, %11, %12, %13, %14, %15, %16, %17, %18, %19, %20, %21, %22, %23, %24, %25, %26, %27, %28, %29, %30, %31, %32, %33, %34, %35, %36, %37, %38, %39, %40, %41, %42, %43, %44, %45, %46, %47, %48, %49, %50, %51, %52, %53, %54, %55, %56, %57, %58, %59, %60, %61, %62, %63, %64, %65, %66, %67, %68, %69, %70, %71, %72, %73, %74, %75, %76, %77, %78, %79, %80, %81, %82, %83, %84, %85, %86, %87, %88, %89, %90, %91, %92, %93, %94, %95}, {%96,%97,%98,%99}, db, p, 1, 1, 1;\n}\n"
    : "+f"(d[0]), "+f"(d[1]), "+f"(d[2]), "+f"(d[3]), "+f"(d[4]), "+f"(d[5]), "+f"(d[6]), "+f"(d[7]), "+f"(d[8]), "+f"(d[9]), "+f"(d[10]), "+f"(d[11]), "+f"(d[12]), "+f"(d[13]), "+f"(d[14]), "+f"(d[15]), "+f"(d[16]), "+f"(d[17]), "+f"(d[18]), "+f"(d[19]), "+f"(d[20]), "+f"(d[21]), "+f"(d[22]), "+f"(d[23]), "+f"(d[24]), "+f"(d[25]), "+f"(d[26]), "+f"(d[27]), "+f"(d[28]), "+f"(d[29]), "+f"(d[30]), "+f"(d[31]), "+f"(d[32]), "+f"(d[33]), "+f"(d[34]), "+f"(d[35]), "+f"(d[36]), "+f"(d[37]), "+f"(d[38]), "+f"(d[39]), "+f"(d[40]), "+f"(d[41]), "+f"(d[42]), "+f"(d[43]), "+f"(d[44]), "+f"(d[45]), "+f"(d[46]), "+f"(d[47]), "+f"(d[48]), "+f"(d[49]), "+f"(d[50]), "+f"(d[51]), "+f"(d[52]), "+f"(d[53]), "+f"(d[54]), "+f"(d[55]), "+f"(d[56]), "+f"(d[57]), "+f"(d[58]), "+f"(d[59]), "+f"(d[60]), "+f"(d[61]), "+f"(d[62]), "+f"(d[63]), "+f"(d[64]), "+f"(d[65]), "+f"(d[66]), "+f"(d[67]), "+f"(d[68]), "+f"(d[69]), "+f"(d[70]), "+f"(d[71]), "+f"(d[72]), "+f"(d[73]), "+f"(d[74]), "+f"(d[75]), "+f"(d[76]), "+f"(d[77]), "+f"(d[78]), "+f"(d[79]), "+f"(d[80]), "+f"(d[81]), "+f"(d[82]), "+f"(d[83]), "+f"(d[84]), "+f"(d[85]), "+f"(d[86]), "+f"(d[87]), "+f"(d[88]), "+f"(d[89]), "+f"(d[90]), "+f"(d[91]), "+f"(d[92]), "+f"(d[93]), "+f"(d[94]), "+f"(d[95])
    : "r"(a[0]), "r"(a[1]), "r"(a[2]), "r"(a[3]), "r"(blo), "n"(BO), "n"(BH), "r"(sc));
}
template<uint32_t BO, uint32_t BH> __device__ __forceinline__ void mma32_rs(float (&d)[16], const uint32_t* a, uint32_t blo) {
  asm volatile("{\n.reg .pred p;\n.reg .b32 ta, tb;\n.reg .b64 da, db;\nadd.u32 tb, %20, %21;\nmov.b64 db, {tb, %22};\nsetp.ne.b32 p, 1, 0;\n"
    "wgmma.mma_async.sync.aligned.m64n32k16.f32.bf16.bf16 {%0, %1, %2, %3, %4, %5, %6, %7, %8, %9, %10, %11, %12, %13, %14, %15}, {%16,%17,%18,%19}, db, p, 1, 1, 1;\n}\n"
    : "+f"(d[0]), "+f"(d[1]), "+f"(d[2]), "+f"(d[3]), "+f"(d[4]), "+f"(d[5]), "+f"(d[6]), "+f"(d[7]), "+f"(d[8]), "+f"(d[9]), "+f"(d[10]), "+f"(d[11]), "+f"(d[12]), "+f"(d[13]), "+f"(d[14]), "+f"(d[15])
    : "r"(a[0]), "r"(a[1]), "r"(a[2]), "r"(a[3]), "r"(blo), "n"(BO), "n"(BH));
}
template<uint32_t BO, uint32_t BH> __device__ __forceinline__ void mma32_rs0(float (&d)[16], const uint32_t* a, uint32_t blo) {
  asm volatile("{\n.reg .pred p;\n.reg .b32 ta, tb;\n.reg .b64 da, db;\nadd.u32 tb, %20, %21;\nmov.b64 db, {tb, %22};\nsetp.ne.b32 p, 0, 0;\n"
    "wgmma.mma_async.sync.aligned.m64n32k16.f32.bf16.bf16 {%0, %1, %2, %3, %4, %5, %6, %7, %8, %9, %10, %11, %12, %13, %14, %15}, {%16,%17,%18,%19}, db, p, 1, 1, 1;\n}\n"
    : "=f"(d[0]), "=f"(d[1]), "=f"(d[2]), "=f"(d[3]), "=f"(d[4]), "=f"(d[5]), "=f"(d[6]), "=f"(d[7]), "=f"(d[8]), "=f"(d[9]), "=f"(d[10]), "=f"(d[11]), "=f"(d[12]), "=f"(d[13]), "=f"(d[14]), "=f"(d[15])
    : "r"(a[0]), "r"(a[1]), "r"(a[2]), "r"(a[3]), "r"(blo), "n"(BO), "n"(BH));
}
template<uint32_t BO, uint32_t BH> __device__ __forceinline__ void mma40_rs(float (&d)[20], const uint32_t* a, uint32_t blo) {
  asm volatile("{\n.reg .pred p;\n.reg .b32 ta, tb;\n.reg .b64 da, db;\nadd.u32 tb, %24, %25;\nmov.b64 db, {tb, %26};\nsetp.ne.b32 p, 1, 0;\n"
    "wgmma.mma_async.sync.aligned.m64n40k16.f32.bf16.bf16 {%0, %1, %2, %3, %4, %5, %6, %7, %8, %9, %10, %11, %12, %13, %14, %15, %16, %17, %18, %19}, {%20,%21,%22,%23}, db, p, 1, 1, 1;\n}\n"
    : "+f"(d[0]), "+f"(d[1]), "+f"(d[2]), "+f"(d[3]), "+f"(d[4]), "+f"(d[5]), "+f"(d[6]), "+f"(d[7]), "+f"(d[8]), "+f"(d[9]), "+f"(d[10]), "+f"(d[11]), "+f"(d[12]), "+f"(d[13]), "+f"(d[14]), "+f"(d[15]), "+f"(d[16]), "+f"(d[17]), "+f"(d[18]), "+f"(d[19])
    : "r"(a[0]), "r"(a[1]), "r"(a[2]), "r"(a[3]), "r"(blo), "n"(BO), "n"(BH));
}
template<uint32_t BO, uint32_t BH> __device__ __forceinline__ void mma40_rs0(float (&d)[20], const uint32_t* a, uint32_t blo) {
  asm volatile("{\n.reg .pred p;\n.reg .b32 ta, tb;\n.reg .b64 da, db;\nadd.u32 tb, %24, %25;\nmov.b64 db, {tb, %26};\nsetp.ne.b32 p, 0, 0;\n"
    "wgmma.mma_async.sync.aligned.m64n40k16.f32.bf16.bf16 {%0, %1, %2, %3, %4, %5, %6, %7, %8, %9, %10, %11, %12, %13, %14, %15, %16, %17, %18, %19}, {%20,%21,%22,%23}, db, p, 1, 1, 1;\n}\n"
    : "=f"(d[0]), "=f"(d[1]), "=f"(d[2]), "=f"(d[3]), "=f"(d[4]), "=f"(d[5]), "=f"(d[6]), "=f"(d[7]), "=f"(d[8]), "=f"(d[9]), "=f"(d[10]), "=f"(d[11]), "=f"(d[12]), "=f"(d[13]), "=f"(d[14]), "=f"(d[15]), "=f"(d[16]), "=f"(d[17]), "=f"(d[18]), "=f"(d[19])
    : "r"(a[0]), "r"(a[1]), "r"(a[2]), "r"(a[3]), "r"(blo), "n"(BO), "n"(BH));
}
template<uint32_t AO, uint32_t AH, uint32_t BO, uint32_t BH> __device__ __forceinline__ void mma40_tt(float (&d)[20], uint32_t alo, uint32_t blo) {
  asm volatile("{\n.reg .pred p;\n.reg .b32 ta, tb;\n.reg .b64 da, db;\nadd.u32 ta, %20, %21;\nmov.b64 da, {ta, %22};\nadd.u32 tb, %23, %24;\nmov.b64 db, {tb, %25};\nsetp.ne.b32 p, 1, 0;\n"
    "wgmma.mma_async.sync.aligned.m64n40k16.f32.bf16.bf16 {%0, %1, %2, %3, %4, %5, %6, %7, %8, %9, %10, %11, %12, %13, %14, %15, %16, %17, %18, %19}, da, db, p, 1, 1, 1, 1;\n}\n"
    : "+f"(d[0]), "+f"(d[1]), "+f"(d[2]), "+f"(d[3]), "+f"(d[4]), "+f"(d[5]), "+f"(d[6]), "+f"(d[7]), "+f"(d[8]), "+f"(d[9]), "+f"(d[10]), "+f"(d[11]), "+f"(d[12]), "+f"(d[13]), "+f"(d[14]), "+f"(d[15]), "+f"(d[16]), "+f"(d[17]), "+f"(d[18]), "+f"(d[19])
    : "r"(alo), "n"(AO), "n"(AH), "r"(blo), "n"(BO), "n"(BH));
}
template<uint32_t AO, uint32_t AH, uint32_t BO, uint32_t BH> __device__ __forceinline__ void mma40_tt0(float (&d)[20], uint32_t alo, uint32_t blo) {
  asm volatile("{\n.reg .pred p;\n.reg .b32 ta, tb;\n.reg .b64 da, db;\nadd.u32 ta, %20, %21;\nmov.b64 da, {ta, %22};\nadd.u32 tb, %23, %24;\nmov.b64 db, {tb, %25};\nsetp.ne.b32 p, 0, 0;\n"
    "wgmma.mma_async.sync.aligned.m64n40k16.f32.bf16.bf16 {%0, %1, %2, %3, %4, %5, %6, %7, %8, %9, %10, %11, %12, %13, %14, %15, %16, %17, %18, %19}, da, db, p, 1, 1, 1, 1;\n}\n"
    : "=f"(d[0]), "=f"(d[1]), "=f"(d[2]), "=f"(d[3]), "=f"(d[4]), "=f"(d[5]), "=f"(d[6]), "=f"(d[7]), "=f"(d[8]), "=f"(d[9]), "=f"(d[10]), "=f"(d[11]), "=f"(d[12]), "=f"(d[13]), "=f"(d[14]), "=f"(d[15]), "=f"(d[16]), "=f"(d[17]), "=f"(d[18]), "=f"(d[19])
    : "r"(alo), "n"(AO), "n"(AH), "r"(blo), "n"(BO), "n"(BH));
}
template<uint32_t AO, uint32_t AH, uint32_t BO, uint32_t BH> __device__ __forceinline__ void mma8_tn(float (&d)[4], uint32_t alo, uint32_t blo) {
  asm volatile("{\n.reg .pred p;\n.reg .b32 ta, tb;\n.reg .b64 da, db;\nadd.u32 ta, %4, %5;\nmov.b64 da, {ta, %6};\nadd.u32 tb, %7, %8;\nmov.b64 db, {tb, %9};\nsetp.ne.b32 p, 1, 0;\n"
    "wgmma.mma_async.sync.aligned.m64n8k16.f32.bf16.bf16 {%0, %1, %2, %3}, da, db, p, 1, 1, 1, 0;\n}\n"
    : "+f"(d[0]), "+f"(d[1]), "+f"(d[2]), "+f"(d[3])
    : "r"(alo), "n"(AO), "n"(AH), "r"(blo), "n"(BO), "n"(BH));
}
template<uint32_t AO, uint32_t AH, uint32_t BO, uint32_t BH> __device__ __forceinline__ void mma8_tn0(float (&d)[4], uint32_t alo, uint32_t blo) {
  asm volatile("{\n.reg .pred p;\n.reg .b32 ta, tb;\n.reg .b64 da, db;\nadd.u32 ta, %4, %5;\nmov.b64 da, {ta, %6};\nadd.u32 tb, %7, %8;\nmov.b64 db, {tb, %9};\nsetp.ne.b32 p, 0, 0;\n"
    "wgmma.mma_async.sync.aligned.m64n8k16.f32.bf16.bf16 {%0, %1, %2, %3}, da, db, p, 1, 1, 1, 0;\n}\n"
    : "=f"(d[0]), "=f"(d[1]), "=f"(d[2]), "=f"(d[3])
    : "r"(alo), "n"(AO), "n"(AH), "r"(blo), "n"(BO), "n"(BH));
}
template<uint32_t AO, uint32_t AH, uint32_t BO, uint32_t BH> __device__ __forceinline__ void mma128_ss(float (&d)[64], uint32_t alo, uint32_t blo) {
  asm volatile("{\n.reg .pred p;\n.reg .b32 ta, tb;\n.reg .b64 da, db;\nadd.u32 ta, %64, %65;\nmov.b64 da, {ta, %66};\nadd.u32 tb, %67, %68;\nmov.b64 db, {tb, %69};\nsetp.ne.b32 p, 1, 0;\n"
    "wgmma.mma_async.sync.aligned.m64n128k16.f32.bf16.bf16 {%0, %1, %2, %3, %4, %5, %6, %7, %8, %9, %10, %11, %12, %13, %14, %15, %16, %17, %18, %19, %20, %21, %22, %23, %24, %25, %26, %27, %28, %29, %30, %31, %32, %33, %34, %35, %36, %37, %38, %39, %40, %41, %42, %43, %44, %45, %46, %47, %48, %49, %50, %51, %52, %53, %54, %55, %56, %57, %58, %59, %60, %61, %62, %63}, da, db, p, 1, 1, 0, 1;\n}\n"
    : "+f"(d[0]), "+f"(d[1]), "+f"(d[2]), "+f"(d[3]), "+f"(d[4]), "+f"(d[5]), "+f"(d[6]), "+f"(d[7]), "+f"(d[8]), "+f"(d[9]), "+f"(d[10]), "+f"(d[11]), "+f"(d[12]), "+f"(d[13]), "+f"(d[14]), "+f"(d[15]), "+f"(d[16]), "+f"(d[17]), "+f"(d[18]), "+f"(d[19]), "+f"(d[20]), "+f"(d[21]), "+f"(d[22]), "+f"(d[23]), "+f"(d[24]), "+f"(d[25]), "+f"(d[26]), "+f"(d[27]), "+f"(d[28]), "+f"(d[29]), "+f"(d[30]), "+f"(d[31]), "+f"(d[32]), "+f"(d[33]), "+f"(d[34]), "+f"(d[35]), "+f"(d[36]), "+f"(d[37]), "+f"(d[38]), "+f"(d[39]), "+f"(d[40]), "+f"(d[41]), "+f"(d[42]), "+f"(d[43]), "+f"(d[44]), "+f"(d[45]), "+f"(d[46]), "+f"(d[47]), "+f"(d[48]), "+f"(d[49]), "+f"(d[50]), "+f"(d[51]), "+f"(d[52]), "+f"(d[53]), "+f"(d[54]), "+f"(d[55]), "+f"(d[56]), "+f"(d[57]), "+f"(d[58]), "+f"(d[59]), "+f"(d[60]), "+f"(d[61]), "+f"(d[62]), "+f"(d[63])
    : "r"(alo), "n"(AO), "n"(AH), "r"(blo), "n"(BO), "n"(BH));
}
template<uint32_t AO, uint32_t AH, uint32_t BO, uint32_t BH> __device__ __forceinline__ void mma128_ss0(float (&d)[64], uint32_t alo, uint32_t blo) {
  asm volatile("{\n.reg .pred p;\n.reg .b32 ta, tb;\n.reg .b64 da, db;\nadd.u32 ta, %64, %65;\nmov.b64 da, {ta, %66};\nadd.u32 tb, %67, %68;\nmov.b64 db, {tb, %69};\nsetp.ne.b32 p, 0, 0;\n"
    "wgmma.mma_async.sync.aligned.m64n128k16.f32.bf16.bf16 {%0, %1, %2, %3, %4, %5, %6, %7, %8, %9, %10, %11, %12, %13, %14, %15, %16, %17, %18, %19, %20, %21, %22, %23, %24, %25, %26, %27, %28, %29, %30, %31, %32, %33, %34, %35, %36, %37, %38, %39, %40, %41, %42, %43, %44, %45, %46, %47, %48, %49, %50, %51, %52, %53, %54, %55, %56, %57, %58, %59, %60, %61, %62, %63}, da, db, p, 1, 1, 0, 1;\n}\n"
    : "=f"(d[0]), "=f"(d[1]), "=f"(d[2]), "=f"(d[3]), "=f"(d[4]), "=f"(d[5]), "=f"(d[6]), "=f"(d[7]), "=f"(d[8]), "=f"(d[9]), "=f"(d[10]), "=f"(d[11]), "=f"(d[12]), "=f"(d[13]), "=f"(d[14]), "=f"(d[15]), "=f"(d[16]), "=f"(d[17]), "=f"(d[18]), "=f"(d[19]), "=f"(d[20]), "=f"(d[21]), "=f"(d[22]), "=f"(d[23]), "=f"(d[24]), "=f"(d[25]), "=f"(d[26]), "=f"(d[27]), "=f"(d[28]), "=f"(d[29]), "=f"(d[30]), "=f"(d[31]), "=f"(d[32]), "=f"(d[33]), "=f"(d[34]), "=f"(d[35]), "=f"(d[36]), "=f"(d[37]), "=f"(d[38]), "=f"(d[39]), "=f"(d[40]), "=f"(d[41]), "=f"(d[42]), "=f"(d[43]), "=f"(d[44]), "=f"(d[45]), "=f"(d[46]), "=f"(d[47]), "=f"(d[48]), "=f"(d[49]), "=f"(d[50]), "=f"(d[51]), "=f"(d[52]), "=f"(d[53]), "=f"(d[54]), "=f"(d[55]), "=f"(d[56]), "=f"(d[57]), "=f"(d[58]), "=f"(d[59]), "=f"(d[60]), "=f"(d[61]), "=f"(d[62]), "=f"(d[63])
    : "r"(alo), "n"(AO), "n"(AH), "r"(blo), "n"(BO), "n"(BH));
}

#define XD 600
#define XSTEP 300
#define XPD 450
#define XPB 8192
#define SPG 5600
#define WL0 1800
#define WLS 350
#define NB0 2
#define WP1 2000
#define PF_START 5600
#define PFP 126
#define GPERM 0x76543210u
#define FMODE 2
#define NM0 3
#define PWAIT 600
#define AWAKE 3
#define O1H 2
#define NG1 8
#define X1E 0
#define WDW 3
#define WDGAP 300
#define YWAIT 500
#define OUTW 0
#define CWAIT 500
#define NDF 8
#define O0ALL 0
#define O1ALL 0
#define RDV 1
#define MSTEP 1200
#define MSLP 1000
#define MPOLL 3200
#define LMP 8
#define WD0 10
#define CLR0 22000
#define UPGAP 200
#define OUTGAP 150
#define MPROMO P128
#define MLOAD tma_load_ef
struct Ptrs { const bf16 *x, *wmod, *c, *wr, *wqkv; int by_sm; Scratch* s; const bf16 *wg, *wu, *wd, *wo; bf16* out; uint16_t role[132]; };

#define BAR(i) (sb + OFF_BAR + 8u * (i))

__device__ __forceinline__ uint32_t get_tag(uint32_t sb) { mbar_wait(BAR(B_TAG), 0); const uint32_t d = __shfl_sync(0xffffffffu, lds32(sb + OFF_CST + 32), 0); return d + 1 + (d & 2); }
__device__ __forceinline__ int d_kb(int n, int hg) {
    if (n < 2) return 2 * hg + n;
    const int h = n >= 9, q = n - 2 - 7 * h;
    return 2 * (q + (q >= hg)) + h;
}

__global__ void __launch_bounds__(NTHREADS, 1)
fused_kernel(const Ptrs p, const __grid_constant__ CUtensorMap tmM, const __grid_constant__ CUtensorMap tmX, const __grid_constant__ CUtensorMap tmW,
             const __grid_constant__ CUtensorMap tmWo, const __grid_constant__ CUtensorMap tmPhi, const __grid_constant__ CUtensorMap tmG,
             const __grid_constant__ CUtensorMap tmU, const __grid_constant__ CUtensorMap tmD, const __grid_constant__ CUtensorMap tmO)
{
    extern __shared__ __align__(1024) uint8_t smem_raw[];
    const uint32_t sb = smem_u32(smem_raw);
    const uint32_t cstart = __shfl_sync(0xffffffffu, clk32(), 0);
    const int tid = threadIdx.x, lane = tid & 31, warp = __shfl_sync(0xffffffffu, tid >> 5, 0);
    if (blockIdx.x < 128) {
        if (warp == 8) asm volatile("prefetch.global.L2 [%0];" :: "l"(p.wmod + (size_t)(blockIdx.x * 8 + (lane >> 2)) * 6144 + (lane & 1) * 64 + (lane & 2) * 512));
        if (warp == 13 && (lane & 1) < NM0 - 2) asm volatile("prefetch.global.L2 [%0];" :: "l"(p.wmod + (size_t)(blockIdx.x * 8 + (lane >> 2)) * 6144 + 128 + (lane & 1) * 64 + (lane & 2) * 512));
        if (warp == 12) l2_prefetch(p.wqkv + (size_t)blockIdx.x * 1536, 3072);
        if (warp == 9) { spin_until(cstart + XPD); l2_prefetch(p.x + (size_t)blockIdx.x * 16384, XPB); }
    }
    if (warp == 10) { tmap_prefetch(&tmM); tmap_prefetch(&tmX); tmap_prefetch(&tmW); }
    if (warp == 11) asm volatile("prefetch.global.L2 [%0];" :: "l"((lane < 16 ? p.c : p.wr) + (lane & 15) * 64));
    #pragma unroll
    for (int i = 0; i < 5; i++) e_init(BAR(5 * warp + i), warp < 5 ? 1 : warp < 7 ? 2 : warp < 9 ? 4 : 8);
    mbar_init_fence();
    if (warp == B_TAG / 5) { e_arrive_tx(BAR(B_TAG), 16); bulk_load(sb + OFF_CST + 32, p.s->done, 16, BAR(B_TAG)); }
    uint32_t role;
    asm("mov.u32 %0, %%smid;" : "=r"(role));
    role = p.role[p.by_sm ? role : blockIdx.x];
    const int b = role & 255;
    if (b >= 128 && warp == 0) {
        #pragma unroll
        for (int i = 0; i < 2; i++) { e_arrive_tx(BAR(i), 32768); MLOAD(sb + i * 32768u, &tmM, (b & 1) * 1024, (b & 2) * 256 + i * 256, BAR(i)); }
    }
    __syncthreads();

    if (b >= 128) {
        const int sp = b & 3;
        if (warp == 8) {
            #pragma unroll 1
            for (int j = 2, st = 2, ph = 1; j < 64; j++) {
                if (j == 2 * NM0) spin_until(cstart + SPG);
                mbar_wait(BAR(B_EA + st), ph);
                e_arrive_tx(BAR(st), 32768);
                MLOAD(sb + st * 32768u, &tmM, j < 32 ? (sp & 1) * 1024 + (j >> 1) * 64 : 2560 + sp * 512 + (j >> 2) * 64, (j < 32 ? (sp & 2) + (j & 1) : j & 3) * 256, BAR(st));
                if (++st == 6) { st = 0; ph ^= 1; }
            }
        } else if (warp < 8) {
            const int g = lane >> 2, c = lane & 3;
            {
                const bf16* cp = p.c + (tid >> 3) * 32 + (tid & 1) * 16 + (tid & 6);
                const uint32_t c0 = ldg32(cp), c1 = ldg32(cp + 8);
                stg_zero(p.s->llm1 + (tid >> 4) * 64 + sp * 16 + (tid & 15));
                if (tid < 128) stg_zero(p.s->llmod2 + sp * 128 + tid);
                sts64(sb + 200704u + tid * 8, silu2(c0), silu2(c1));
                bar_sync(1, 256);
                TR(57);
            }
            const uint32_t tag = get_tag(sb);
            const uint32_t wa = sb + (warp * 32 + (lane & 7) + (lane >> 4) * 8) * 128u + ((((lane >> 3) & 1) ^ (lane & 7)) << 4);
            float m[4][4];
            #pragma unroll
            for (int i = 0; i < 4; i++) m[i][0] = m[i][1] = m[i][2] = m[i][3] = 0.f;
            #pragma unroll 1
            for (int r = 0, st = 0, ph = 0; r < 32; r++) {
                const int n = r < 16 ? r : (r >> 1) + 8;
                const bf16* wr = p.wr + (sp & 1) * 512 + (n & 7) * 64 + (g & 3) * 16 + 2 * c;
                const uint32_t wr0 = ldg32(wr), wr1 = ldg32(wr + 8);
                const uint32_t sa = sb + 200704u + ((r < 16 ? sp >> 1 : r & 1) * 16 + warp) * 64 + c * 16;
                const uint4 sv0 = lds128(sa), sv1 = lds128(sa + 512);
                uint32_t f[16][4];
                #pragma unroll
                for (int q = 0; q < 2; q++) {
                    mbar_wait(BAR(st + q), ph);
                    if (r == 0 && warp == 0) TR(60 + q);
                    #pragma unroll
                    for (int i = 0; i < 8; i++) ldsm4t(f[8 * q + i], (wa + (st + q) * 32768u + (i >> 2) * 2048u) ^ ((i & 3) << 5));
                }
                #pragma unroll
                for (int i = 0; i < 16; i++) {
                    const uint4& sv = i < 8 ? sv0 : sv1;
                    mma16816(m[i & 3], f[i][0], f[i][1], f[i][2], f[i][3], (i & 4) ? sv.z : sv.x, (i & 4) ? sv.w : sv.y);
                    if ((i & 7) == 7) e_arrive(BAR(B_EA + st + (i >> 3)));
                }
                st += 2; if (st == 6) { st = 0; ph ^= 1; }
                if (r >= 16 && !(r & 1)) continue;
                const uint32_t red = sb + 196608u + (n & 1) * 2048u;
                const uint32_t a = red + warp * 256u + (c * 16 + (g >> 1) * 4 + (g & 1)) * 4u;
                stsf(a, sel4(c, m[0][0], m[1][0], m[2][0], m[3][0])); stsf(a + 8, sel4(c, m[0][2], m[1][2], m[2][2], m[3][2]));
                #pragma unroll
                for (int i = 0; i < 4; i++) m[i][0] = m[i][1] = m[i][2] = m[i][3] = 0.f;
                bar_sync(1, 256);
                if (warp == (n & 7)) {
                    const uint32_t ra = red + (lane >> 4) * 1024u + (lane & 15) * 16u;
                    const uint4 r0 = lds128(ra), r1 = lds128(ra + 256), r2 = lds128(ra + 512), r3 = lds128(ra + 768);
                    #define F4(f) ((u2f(r0.f) + u2f(r1.f)) + (u2f(r2.f) + u2f(r3.f)))
                    float x = F4(x), y = F4(y), z = F4(z), w = F4(w);
                    #undef F4
                    x += shfl_x(x, 16); y += shfl_x(y, 16); z += shfl_x(z, 16); w += shfl_x(w, 16);
                    if (n < 16) {
                        if (lane < 16) st_ll4(p.s->llm1 + n * 64 + sp * 16 + lane, x, y, z, w, tag);
                    } else {
                        uint32_t lo = pack2(x, y), hi2 = pack2(z, w);
                        float d = fmaf(bf_lo(lo), bf_lo(wr0), bf_hi(lo) * bf_hi(wr0)) + fmaf(bf_lo(hi2), bf_lo(wr1), bf_hi(hi2) * bf_hi(wr1));
                        if (sp >= 2) {
                            lo = hadd2(lo, ONE2); hi2 = hadd2(hi2, ONE2);
                            const uint32_t r0 = hmul2(lo, wr0), r1 = hmul2(hi2, wr1);
                            d = (bf_lo(r0) + bf_hi(r0)) + (bf_lo(r1) + bf_hi(r1));
                        }
                        #pragma unroll 1
                        for (int k = 1; k < 16; k <<= 1) d += shfl_x(d, k);
                        if (lane < 16) st_ll(p.s->llmod2 + sp * 128 + (n & 7) * 16 + lane, lo, hi2, f2u(d), tag);
                    }
                    TR(n);
                }
            }
        }
    } else if (warp >= 12) {
        reg_dec<24>();
        const int rb = b >> 3, hg = b & 7, fs = role >> 8;
        const bool ffn = fs < 112;
        if (warp == 12) {
            #pragma unroll 1
            for (int j = 0, s = 0, ph = 1; j < 16; j++) {
                if (j < 2) mbar_wait(j ? BAR(B_STS) : BAR(B_STP), 0);
                mbar_wait(BAR(B_EA + s), ph);
                e_arrive_tx(BAR(B_FA + s), 16384); tma_load(sb + OFF_A + s * 16384u, &tmX, j * 64, rb * 128, BAR(B_FA + s));
                if (j == 0) TS(2);
                if (j == 1) GT(0);
                if (j == 6) GT(1);
                if (j == 11) GT(2);
                if (++s == 3) { s = 0; ph ^= 1; }
            }
            tmap_prefetch(&tmO);
            const uint32_t tag = get_tag(sb);
            e_arrive(BAR(B_FD)); e_arrive(BAR(B_FD + 1));
            const uint4* osrc = pin_ptr(p.s->os + (size_t)rb * 16 * 1024);
            #pragma unroll 1
            for (int q = 0; q < 3; q++) {
                mbar_wait(q < 2 ? BAR(B_KST + 1 + 2 * q) : BAR(B_OWN), 0);
                poll_flags(q < 2 ? p.s->flk + (q + 1) * 256 + (hg * 16 + (lane & 15)) * 2 : p.s->flo + (O0ALL ? (rb & 12) * 16 + lane * 2 : rb * 16 + (lane & 7) * 2) * 2, tag);
                if (q == 2) break;
                e_arrive_tx(BAR(B_KVL + q), 16896); bulk_load(sb + (q ? OFF_PHI : OFF_KL), p.s->kvacc + hg * 2112 + q * 1056, 16896, BAR(B_KVL + q));
                TS(12 + q);
                if (!q) GT(4);
            }
            TS(3); GT(5);
            #pragma unroll
            for (int n = 2; n < 6; n++) {
                if (n >= 4) mbar_wait(BAR(B_ED + (n & 3)), 0); else mbar_wait(BAR(B_GE + (4 * n <= NG1 ? 1 : 2)), 0);
                e_arrive_tx(BAR(B_FD + (n & 3)), 16384);
                bulk_load(sb + (n == 5 ? OFF_X1 : OFF_R0 + (n & 3) * 16384u), osrc + (n - 2 >= hg ? n - 1 : n - 2) * 2048, 16384, BAR(B_FD + (n & 3)));
                TR(32 + n);
            }
            #pragma unroll 1
            for (int n = 6; n < 16; n++) {
                const uint32_t s = n & 3, fb = BAR(B_FD + s);
                const uint4* src = osrc + d_kb(n, hg) * 1024;
                if (n == 9) mbar_wait(BAR(B_O1), 0);
                mbar_wait(BAR(B_ED + s), ((n >> 2) - 1) & 1);
                e_arrive_tx(fb, 16384);
                bulk_load(sb + OFF_R0 + s * 16384u, src, 16384, fb);
                TR(32 + n);
            }
            e_arrive_tx(BAR(B_WPHI), 32768);
            if (X1E) tma_load(sb + OFF_X1, &tmX, hg * 128 + 64, rb * 128, BAR(B_WPHI));
            mbar_wait(BAR(B_ED), 1);
            tma_load(sb + OFF_R0, &tmX, hg * 128, rb * 128, BAR(B_WPHI));
            if (!X1E) tma_load(sb + OFF_X1, &tmX, hg * 128 + 64, rb * 128, BAR(B_WPHI));
            GT(6);
            mbar_wait(BAR(B_CAND), 0);
            GT(7);
            const uint2 lc = lds64(sb + OFF_CST + 16);
            const uint32_t w0 = __shfl_sync(0xffffffffu, lc.x >> 4, 0), w1 = __shfl_sync(0xffffffffu, lc.y >> 4, 0);
            mbar_wait(BAR(B_SWP), 0);
            fence_async_smem();
            if (OUTW) mbar_wait(BAR(B_SEL), 0);
            #pragma unroll 1
            for (uint32_t w = 0; w < 8; w++)
                if (w != w0 && w != w1) { tma_store4(&tmO, rb * 128 + w * 16, hg * 2, sb + OFF_OUT + w * 4096u); spin_until(clk32() + OUTGAP); }
            mbar_wait(BAR(B_SEL), 0);
            const uint2 sel = lds64(sb + OFF_CST + 24);
            #pragma unroll 1
            for (uint32_t i = 0; i < (w0 == w1 ? 8u : 16u); i++) {
                const uint32_t w = i < 8 ? w0 : w1, r = (i & 7) * 2 + (lane >> 4), row = rb * 128 + w * 16 + r;
                const uint4 o = lds128(sb + OFF_OUT + w * 4096u + ((lane >> 3) & 1) * 2048u + r * 128u + (((lane ^ r) & 7) << 4));
                if (row != (~sel.x & 2047u) && row != (~sel.y & 2047u)) stg128(p.out + (size_t)row * 1024 + hg * 128 + (lane & 15) * 8, o);
            }
            bulk_wait_read();
        } else if (warp == 14) {
            const uint32_t fb = ffn ? 65536 : 0;
            e_arrive_tx(BAR(B_GF), fb); e_arrive_tx(BAR(B_UD), fb); e_arrive_tx(BAR(B_UF), fb); e_arrive_tx(BAR(B_WD), fb);
            uint32_t due = cstart + WP1;
            #pragma unroll 1
            for (int i = -2; i < 26; i++) {
                if (i >= 0) {
                    const bf16* a = i < 8 ? p.wg + (size_t)(i * 128 + b) * 3584 : i < 16 ? p.wu + (size_t)((i - 8) * 128 + b) * 3584
                                  : i < 18 ? p.wo + (size_t)(b * 2 + i - 16) * 4096 : p.wd + (size_t)(b * 8 + i - 18) * 3584;
                    sleep_until(due);
                    l2_prefetch(a, (i >> 1) == 8 ? 8192 : 7168);
                    due += 7 * PFP;
                }
                if (i == 1) { tmap_prefetch(&tmPhi); tmap_prefetch(&tmG); tmap_prefetch(&tmWo); tmap_prefetch(&tmU); tmap_prefetch(&tmD); mbar_wait(BAR(B_STS), 0); }
                if (ffn && (uint32_t)(i - 3) < 8u) tma_load_ef(sb + OFF_R0 + (i - 3) * 8192u, &tmG, fs * 32, (i - 3) * 128, BAR(B_GF));
                if (ffn && (uint32_t)(i - 11) < 8u) tma_load(sb + OFF_WPHI, &tmU, fs * 32, (i - 11) * 128, BAR(B_UD));
                if (i == 19) { mbar_wait(BAR(B_UD), 0); e_arrive_tx(BAR(B_WPHI), 8192); tma_load(sb + OFF_WPHI, &tmPhi, 0, hg * 128, BAR(B_WPHI)); }
                if (i == LMP + 2 * (b & 3) + (b >> 6)) tma_prefetch(&tmM, 2048 + (b >> 6) * 2048 + (b >> 2) * 64, (b & 3) * 256);
                if (i < 13) {
                    sleep_until(due);
                    l2_prefetch(p.wqkv + (size_t)((i + 3) * 128 + b) * 1536, 3072);
                    due += i == -2 ? PF_START - WP1 : 3 * PFP;
                }
            }
            if (lane < 4) stg_zero(p.s->flo + b * 4 + lane);
            const uint32_t tag = get_tag(sb);
            #pragma unroll 1
            for (int q = 0; q < 2; q++) {
                mbar_wait(BAR(B_OWN + q), 0);
                if (q) { if (O1H >= 4) mbar_wait(BAR(B_FD + 2), 0); mbar_wait(BAR(B_FD + (O1H & 3)), O1H >> 2); }
                bulk_store(p.s->os + ((size_t)b * 2 + q) * 1024, sb + OFF_R0 + q * 16384u, 16384);
                bulk_wait();
                __syncwarp();
                st_flag(p.s->flo + (b * 2 + q) * 2, tag, lane);
                TS(7 + q);
            }
            e_arrive(BAR(B_OST));
        } else {
            uint4* fk = p.s->flk + (hg * 16 + rb) * 2;
            if (warp == 13) {
                #pragma unroll 1
                for (int i = 0; i < 32; i++) {
                    const uint32_t s = i & 3;
                    if (i < NB0) spin_until(cstart + WL0 + WLS * i); else if (i == NB0) mbar_wait(BAR(B_STS), 0);
                    mbar_wait(BAR(B_EB + s), ((i >> 2) - 1) & 1);
                    e_arrive_tx(BAR(B_FB + s), 24576); tma_load4(sb + OFF_B + s * 24576u, &tmW, i * 32, hg * 2, BAR(B_FB + s));
                    TR(64 + i);
                }
                mbar_wait(BAR(B_EB), 1); mbar_wait(BAR(B_EB + 1), 1);
                e_arrive_tx(BAR(B_LMF), 32768); tma_load_ef(sb + OFF_B, &tmM, 2048 + (b >> 6) * 2048 + (b >> 2) * 64, (b & 3) * 256, BAR(B_LMF));
                mbar_wait(BAR(B_LMD), 0);
                #pragma unroll 1
                for (int n = 0; n < 4; n++) {
                    e_arrive_tx(BAR(B_FD + n), 16384); tma_load4(sb + OFF_DB + n * 16384u, &tmWo, d_kb(n, hg) * 64, hg * 2, BAR(B_FD + n));
                }
            } else {
                sleep_until(cstart + CLR0);
                const uint32_t tag = get_tag(sb);
                #pragma unroll 1
                for (int i = lane; i < 132; i += 32) stg_zero(p.s->kvacc + hg * 2112 + rb * 132 + i);
                if (lane < 4) stg_zero(fk + 256 + (lane >> 1) * 256 + (lane & 1));
                fence_gpu();
                __syncwarp();
                st_flag(fk, tag, lane);
                sleep_until(clk32() + 2000);
                poll_flags(p.s->flk + (hg * 16 + (lane & 15)) * 2, tag);
                mbar_wait(BAR(B_QE), 0);
                #pragma unroll 1
                for (int i = 0; i < 4; i++) {
                    stg_zero(p.s->llln2 + b * 128 + i * 32 + lane);
                    stg_zero(p.s->llrowh + (i >> 1) * 8192 + (rb * 2 + (i & 1)) * 256 + hg * 32 + lane);
                    #pragma unroll
                    for (int k = 0; k < 4; k++) stg_zero(p.s->lly + (fs & 127) * 512 + i * 128 + k * 32 + lane);
                }
                if (lane < 2 && hg == (rb & 7)) stg_zero(p.s->llcand + rb * 2 + lane);
                __syncwarp();
                e_arrive(BAR(B_KZ));
            }
            const int q = warp == 13;
            const uint32_t tag = get_tag(sb);
            mbar_wait(BAR(B_KZ), 0);
            #pragma unroll 1
            for (int h = 2 * q; h < 2 * q + 2; h++) {
                mbar_wait(BAR(B_KST + h), 0);
                uint4* acc = p.s->kvacc + (hg * 4 + h) * 528;
                bulk_reduce(acc, sb + OFF_V + h * 8192u, 8192); bulk_reduce(acc + 512, sb + OFF_ZS + h * 256u, 256);
            }
            bulk_wait();
            if (q) e_arrive(BAR(B_KZ));
            TR(158 + q);
            fence_gpu();
            __syncwarp();
            st_flag(fk + 256 + q * 256, tag, lane);
            TS(10 + q);
            if (q) {
                #pragma unroll 1
                for (int n = 4; n < 16; n++) {
                    const uint32_t s = n & 3;
                    mbar_wait(BAR(B_ED + s), ((n >> 2) - 1) & 1);
                    e_arrive_tx(BAR(B_FD + s), 16384);
                    tma_load4(sb + OFF_DB + s * 16384u, &tmWo, d_kb(n, hg) * 64, hg * 2, BAR(B_FD + s));
                    TR(96 + n);
                    if (ffn && (uint32_t)(n - WD0) < 4u) {
                        #pragma unroll
                        for (int k = 0; k < 2; k++) tma_load_ef(sb + OFF_F2 + (n - WD0) * 8192u + k * 4096u, &tmD, (n - WD0) * 256 + k * 128, fs * 32, BAR(B_WD));
                    }
                }
                if (ffn) {
                    mbar_wait(BAR(B_ED + WDW), 1);
                    #pragma unroll 1
                    for (int z = 0; z < 8; z++) { tma_load_ef(sb + OFF_DB + z * 4096u, &tmD, z * 128 + 64, fs * 32, BAR(B_WD)); sleep_until(clk32() + WDGAP); }
                }
            } else {
                if (ffn) {
                    mbar_wait(BAR(B_KZ), 1);
                    #pragma unroll 1
                    for (int i = 7; i < 15; i++) {
                        if (i == 12) mbar_wait(BAR(B_KVT + 1), 0);
                        tma_load_ef(sb + OFF_F2 + (i & 7) * 8192u, &tmU, fs * 32, (i & 7) * 128, BAR(B_UF));
                        sleep_until(clk32() + UPGAP);
                    }
                }
                mbar_wait(BAR(B_OST), 0);
                poll_flags(p.s->flo + (O1ALL ? (rb & 12) * 16 + lane * 2 + 1 : rb * 16 + (lane & 7) * 2 + 1) * 2, tag);
                e_arrive(BAR(B_O1));
                TS(4);
            }
        }
    } else if (warp >= 8) {
        reg_dec<24>();
        const int rb = b >> 3, hg = b & 7, w4 = warp & 3, g = lane >> 2, c = lane & 3, t = tid & 127;
        const uint32_t sv = silu2(ldg32(p.c + (b & 3) * 256 + 2 * t)), tag = get_tag(sb);
        if (w4 < 3) {
            spin_until(cstart + MPOLL + MSTEP * w4);
            #pragma unroll 1
            for (int j = w4, ph = 1; j < 16; j += 3, ph ^= 1) {
                uint4 w[2];
                poll_words<2, 0, 3>(w, p.s->llm1 + j * 64 + lane, 32, tag);
                uint32_t lo = pack2(u2f(w[0].x) + u2f(w[1].x), u2f(w[0].y) + u2f(w[1].y)), hi = pack2(u2f(w[0].z) + u2f(w[1].z), u2f(w[0].w) + u2f(w[1].w));
                if (lane >= 16) { lo = hadd2(lo, ONE2); hi = hadd2(hi, ONE2); }
                sts64(sb + OFF_TAB + j * 256 + (lane & 15) * 16 + (lane < 16 ? 8 : 0), lo, hi);
                __syncwarp();
                if (j == 0) TS(5);
                TR(16 + j);
                mbar_wait(BAR(B_EA + w4), ph);
                e_arrive(BAR(B_FA + w4));
                __nanosleep(MSLP);
            }
        }
        mbar_wait(BAR(B_QE), 0);
        if (warp == 8) GT(3);
        sts32(sb + OFF_KL + w4 * 1024u + lane * 4, sv);
        fence_async_smem();
        bar_sync(2, 128);
        reg_inc<56>();
        {
            float m0[4], m1[4];
            const uint32_t da = desc_lo(sb + OFF_B, 16), db = desc_lo(sb + OFF_KL, 16);
            mbar_wait(BAR(B_LMF), 0);
            wg_fence();
            #define LMS(f, i) f<(i) * 256, H128, ((i) >> 1) * 64 + ((i) & 1) * 4, H128>(m0, da, db); f<(i) * 256 + 128, H128, ((i) >> 1) * 64 + ((i) & 1) * 4 + 2, H128>(m1, da, db)
            LMS(mma8_tn0, 0); LMS(mma8_tn, 1); LMS(mma8_tn, 2); LMS(mma8_tn, 3); LMS(mma8_tn, 4); LMS(mma8_tn, 5); LMS(mma8_tn, 6); LMS(mma8_tn, 7);
            #undef LMS
            wg_commit();
            wg_wait<0>();
            acc_fence(m0); acc_fence(m1);
            e_arrive(BAR(B_LMD));
            const float v0 = m0[0] + m1[0], v1 = m0[2] + m1[2], u0 = shfl_x(v0, 4), u1 = shfl_x(v1, 4);
            if (!(lane & 7)) st_ll4(p.s->llg + (b >> 6) * 1024 + (b & 3) * 256 + ((b >> 2) & 15) * 16 + w4 * 4 + (lane >> 3), v0, u0, v1, u1, tag);
            if (warp == 8) TR(150);
        }
        #pragma unroll 1
        for (int h = 0; h < 4; h++) {
            float okv[20];
            const uint32_t vb = OFF_V + h * 8192u, dp = desc_lo(sb + OFF_PHI + (h & 1) * 16384u, 16), dv = desc_lo(sb + vb, OFF_ONES - vb);
            mbar_wait(BAR(B_PF + h), 0);
            fence_async_smem();
            wg_fence();
            #define KVS(i) mma40_tt<(i) * 128, H128, (i) * (64u - (64u << 16)), H64>(okv, dp, dv)
            mma40_tt0<0, H128, 0, H64>(okv, dp, dv); KVS(1); KVS(2); KVS(3); KVS(4); KVS(5); KVS(6); KVS(7);
            #undef KVS
            wg_commit();
            wg_wait<0>();
            acc_fence(okv);
            if (h < 2) e_arrive(BAR(B_PE + h));
            bar_sync(2, 128);
            #pragma unroll
            for (int k = 0; k < 4; k++) sts128(sb + vb + (k * 128 + t) * 16u, make_uint4(f2u(okv[4 * k]), f2u(okv[4 * k + 1]), f2u(okv[4 * k + 2]), f2u(okv[4 * k + 3])));
            if (c == 0) sts64(sb + OFF_ZS + h * 256u + (w4 * 8 + g) * 8u, f2u(okv[16]), f2u(okv[18]));
            fence_async_smem();
            __syncwarp();
            e_arrive(BAR(B_KST + h));
            if (warp == 8) TR(151 + h);
        }
        #pragma unroll 1
        for (int q = 0; q < 2; q++) {
            const uint32_t f = w4 * 16 + g, kl = sb + (q ? OFF_PHI : OFF_KL), ta = sb + (q ? OFF_KL : OFF_KVT) + f * 64u + ((g >> 1) << 4) + 4 * c;
            const uint32_t za = sb + OFF_Z + (f + 8 * (c & 1)) * 64u + (((2 * q) ^ (g >> 1)) << 4) + (c >> 1) * 8;
            mbar_wait(q ? BAR(B_KVT) : BAR(B_STP), q ^ 1);
            mbar_wait(BAR(B_KVL + q), 0);
            uint4 v[8]; float z[2];
            #pragma unroll
            for (int k = 0; k < 8; k++) v[k] = lds128(kl + (k >> 2) * 8448u + (k & 3) * 2048u + t * 16u);
            #pragma unroll
            for (int hh = 0; hh < 2; hh++) z[hh] = ldsf(kl + hh * 8448u + 8192u + (w4 * 8 + g) * 8u + (c & 1) * 4);
            #pragma unroll
            for (int k = 0; k < 8; k++) {
                sts32((ta ^ ((k & 3) << 4)) + (k >> 2) * 4096u, pack2(u2f(v[k].x), u2f(v[k].y))); sts32((ta ^ ((k & 3) << 4)) + (k >> 2) * 4096u + 512, pack2(u2f(v[k].z), u2f(v[k].w)));
            }
            #pragma unroll
            for (int hh = 0; hh < 2; hh++) { const uint32_t zz = pack2(z[hh], z[hh]); sts64(za ^ (hh << 4), zz, zz); }
            fence_async_smem();
            __syncwarp();
            e_arrive(BAR(B_KVT + q));
            if (warp == 8) TR(155 + q);
        }
        reg_dec<24>();
        mbar_wait(BAR(B_O1), 0);
        if (w4 == 0 || w4 == 3) {
            float s[4] = {0.f, 0.f, 0.f, 0.f};
            #pragma unroll 1
            for (int k = 0; k < 2; k++) {
                uint4 w[2];
                poll_words<2, 0, 3>(w, p.s->llg + (w4 & 1) * 1024 + k * 512 + hg * 32 + lane, 256, tag);
                s[0] += u2f(w[0].x) + u2f(w[1].x); s[1] += u2f(w[0].y) + u2f(w[1].y); s[2] += u2f(w[0].z) + u2f(w[1].z); s[3] += u2f(w[0].w) + u2f(w[1].w);
            }
            const uint32_t lo = pack2(s[0], s[1]), hi = pack2(s[2], s[3]);
            sts64(w4 ? sb + OFF_T3 + lane * 8 : sb + OFF_T1 + lane * 16, lo, hi);
            if (!w4) sts64(sb + OFF_T1 + 512 + lane * 16, lo, hi);
        } else {
            const bf16* wr = p.wr + hg * 128 + g * 16 + 2 * c;
            const uint32_t wr0 = ldg32(wr), wr1 = ldg32(wr + 8);
            uint4 w[2];
            poll_words<2, 1>(w, p.s->llmod2 + (w4 - 1) * 256 + hg * 32 + lane, (lane & 15) * 16 - hg * 32 - lane, tag);
            sts64(sb + OFF_T2 + lane * 16 + (w4 & 1) * 8, w[0].x, w[0].y);
            if (w4 == 2) sts64(sb + OFF_T1 + 512 + lane * 16 + 8, hmul2(w[0].x, wr0), hmul2(w[0].y, wr1));
            float d = u2f(w[1].z);
            #pragma unroll 1
            for (int k = 1; k < 16; k <<= 1) d += shfl_x(d, k);
            stsf(sb + OFF_CST + 8 + (w4 & 1) * 4, d);
        }
        __syncwarp();
        e_arrive(BAR(B_PAR));
        if (warp == 9) TS(6);
        if (w4 < 2) {
            mbar_wait(BAR(B_PAR), 0);
            const uint4 ta = lds128(sb + OFF_T2 + lane * 16);
            const uint2 gb = lds64(sb + OFF_T3 + lane * 8);
            uint4* d = pin_ptr(p.s->llrowh + (rb * 2 + w4) * 256 + hg * 32 + lane);
            mbar_wait(BAR(B_KEYS), 0);
            const uint4 kk = lds128(sb + OFF_KEY + lane * 16);
            uint32_t k[4] = {kk.x, kk.y, kk.z, kk.w}, b0, b1;
            top2<4>(k, b0, b1);
            const uint32_t cd = ~(w4 ? b1 : b0) & 127u;
            const uint32_t xa = sb + OFF_R0 + (g >> 2) * (OFF_X1 - OFF_R0) + cd * 128u + ((((g & 3) * 2) ^ (cd & 7)) << 4) + c * 4;
            const uint32_t x0 = lds32(xa), x1 = lds32(xa ^ 16);
            const uint4 st = lds128(sb + OFF_ST2 + cd * 16);
            st_ll(d, lnmod(x0, st.x, st.y, st.z, ta.x, ta.z), lnmod(x1, st.x, st.y, st.z, ta.y, ta.w), gb.x, tag);
            st_ll(d + 8192, x0, x1, gb.y, tag);
            sts32(sb + OFF_CST + 16 + w4 * 4, cd);
            __syncwarp();
            e_arrive(BAR(B_CAND));
            if (warp == 8) TS(9);
        } else if (w4 == 2) {
            uint4* cp = pin_ptr(p.s->llcand + lane);
            mbar_wait(BAR(B_KEYS), 0);
            if (hg == (rb & 7)) {
                const uint4 kk = lds128(sb + OFF_KEY + lane * 16);
                uint32_t k[4] = {kk.x, kk.y, kk.z, kk.w}, b0, b1;
                top2<4>(k, b0, b1);
                if ((lane >> 1) == rb) st_ll(cp, (lane & 1) ? b1 : b0, tag, tag, tag);
            } else spin_until(clk32() + CWAIT);
            uint2 v = make_uint2(0, 0);
            #pragma unroll 1
            for (int it = 0; it < POLL_MAX; it++) {
                if (v.y != tag) asm volatile("ld.relaxed.gpu.global.v2.b32 {%0,%1}, [%2];" : "=r"(v.x), "=r"(v.y) : "l"(cp) : "memory");
                if (__all_sync(0xffffffffu, v.y == tag)) break;
            }
            uint32_t k[1] = {v.x}, b0, b1;
            top2<1>(k, b0, b1);
            sts64(sb + OFF_CST + 24, b0, b1);
            __syncwarp();
            e_arrive(BAR(B_SEL));
        }
    } else {
        reg_inc<232>();
        float a0[96], a1[96];
        {
            const int g = lane >> 2, c = lane & 3;
            uint4* stp = p.s->llstat + b * 16 + warp * 2 + (lane >> 4);
            if (lane == 0 || lane == 18) stg_zero(stp);
            spin_until(cstart + XD + XSTEP * warp);
            e_arrive_tx(BAR(B_XP + warp), 4096);
            bulk_load(sb + OFF_R0 + warp * 4096u, p.x + (size_t)(b * 16 + 2 * warp) * 1024, 4096, BAR(B_XP + warp));
            const uint32_t tag = get_tag(sb);
            if (tid < 64) sts128(sb + OFF_ONES + tid * 16, make_uint4(ONE2, ONE2, ONE2, ONE2));
            if (tid == 64) { sts64(sb + OFF_CST, role, tag); stsf(sb + OFF_CST + 48, -LOG2E); }
            if (AWAKE & 1) mbar_wait_awake(BAR(B_XP + warp), 0); else mbar_wait(BAR(B_XP + warp), 0);
            e_arrive(BAR(B_STP));
            if (warp == 7) TS(14);
            float s[2][4], q0[2][4], q1[2][4];
            #pragma unroll
            for (int i = 0; i < 4; i++) s[0][i] = s[1][i] = q0[0][i] = q0[1][i] = q1[0][i] = q1[1][i] = 0.f;
            uint32_t xa[8][4], xb[8][4];
            const uint32_t la = sb + OFF_R0 + warp * 4096u + (lane & 7) * 16u;
            #pragma unroll
            for (int i = 0; i < 8; i++) {
                ldsm4(xa[i], la + ((lane >> 3) & 1) * 2048u + (lane >> 4) * 128u + i * 256u);
                ldsm4(xb[i], la + ((lane >> 3) & 1) * 128u + (lane >> 4) * 2048u + i * 256u);
            }
            #pragma unroll
            for (int i = 0; i < 8; i++) {
                mma16816(q0[i & 1], xa[i][0], xa[i][1], xa[i][2], xa[i][3], xb[i][0], xb[i][1]);
                mma16816(q1[i & 1], xa[i][0], xa[i][1], xa[i][2], xa[i][3], xb[i][2], xb[i][3]);
                mma16816(s[i & 1], xa[i][0], xa[i][1], xa[i][2], xa[i][3], ONE2, ONE2);
            }
            const float s0 = s[0][0] + s[1][0], s1 = s[0][2] + s[1][2];
            const float sq0 = (g & 1) ? q0[0][1] + q0[1][1] : q0[0][0] + q0[1][0], sq1 = (g & 1) ? q1[0][3] + q1[1][3] : q1[0][2] + q1[1][2];
            const bool up = lane >= 16;
            float sm = (up ? s1 : s0) + shfl_x(up ? s0 : s1, 18), sq = (up ? sq1 : sq0) + shfl_x(up ? sq0 : sq1, 18);
            sm += shfl_x(sm, 9); sq += shfl_x(sq, 9);
            sm += shfl_x(sm, 4); sq += shfl_x(sq, 4);
            uint32_t m2, rh, rl; float rinv;
            ln_final(sm, sq, m2, rinv);
            split_rcp(rinv, rh, rl);
            if (lane == 0 || lane == 18) st_ll(stp, m2, rh, rl, tag);
            if (warp == 7) TS(15);
            uint4 st[2];
            if (PWAIT) { mbar_wait(BAR(B_STP), 0); if (warp < 7) spin_until(clk32() + PWAIT); }
            #pragma unroll 1
            for (int it = 0; it < POLL_MAX; it++) {
                st[0] = ld_ll(p.s->llstat + (b >> 3) * 128 + warp * 16 + g); st[1] = ld_ll(p.s->llstat + (b >> 3) * 128 + warp * 16 + g + 8);
                const uint32_t o = RDV ? ld_rlx(&p.s->llstat[((b >> 5) * 4 + c) * 128 + warp * 16 + 15].w) : tag;
                if (__all_sync(0xffffffffu, !tag_bad(tag_bad(o ^ tag, st[0].w, tag), st[1].w, tag))) break;
                if (AWAKE & 1) it += awake_zero();
            }
            e_arrive(BAR(B_STS));
            if (warp == 0) TS(16);
            const uint32_t lrow = warp * 16 + (lane & 15);
            uint32_t aad = sb + OFF_A + lrow * 128u + (((lane >> 4) ^ (lrow & 7)) << 4);
            uint32_t tad = sb + OFF_TAB + c * 16, ab = BAR(B_FA), pa = 0;
            uint32_t f0[4], f1[4];
            #define PREP(f, q) do { \
                const uint4 t = lds128(tad + (q) * 64); \
                ldsm4(f, aad ^ ((q) << 5)); \
                f[0] = lnmod(f[0], st[0].x, st[0].y, st[0].z, t.x, t.z); f[1] = lnmod(f[1], st[1].x, st[1].y, st[1].z, t.x, t.z); \
                f[2] = lnmod(f[2], st[0].x, st[0].y, st[0].z, t.y, t.w); f[3] = lnmod(f[3], st[1].x, st[1].y, st[1].z, t.y, t.w); } while (0)
            #define MMA(f, off) do { wg_fence(); mma192_rs<(off), H128>(a0, f, blo); mma192_rs<(off) + 768, H128>(a1, f, blo); wg_commit(); wg_wait<1>(); } while (0)
            mbar_wait(ab, 0);
            PREP(f0, 0);
            if (RDV) mbar_wait(BAR(B_STS), 0);
            #pragma unroll 1
            for (int j = 0; j < 16; j++) {
                const uint32_t bb = BAR(B_FB) + (j & 1) * 16, blo = desc_lo(sb + OFF_B, 4096) + (j & 1) * 3072, pb = (j >> 1) & 1;
                mbar_wait(bb, pb);
                wg_fence(); mma192_rsp<0, H128>(a0, f0, blo, j); mma192_rsp<768, H128>(a1, f0, blo, j); wg_commit(); wg_wait<1>();
                if (j) e_arrive((bb ^ 16) + 8 * (B_EB - B_FB) + 8);
                PREP(f1, 1);
                MMA(f1, 128);
                PREP(f0, 2);
                mbar_wait(bb + 8, pb);
                MMA(f0, 1536);
                e_arrive(bb + 8 * (B_EB - B_FB));
                PREP(f1, 3);
                MMA(f1, 1536 + 128);
                e_arrive(ab + 8 * (B_EA - B_FA));
                ab += 8; aad += 16384; tad += 256;
                if (ab == BAR(B_FA + 3)) { ab -= 24; aad -= 49152; pa ^= 1; }
                if (j < 15) mbar_wait(ab, pa);
                PREP(f0, 0);
            }
            #undef PREP
            #undef MMA
        }
        int tid_o; asm volatile("mov.u32 %0, %%tid.x;" : "=r"(tid_o) :: "memory");
        const int tid = tid_o, lane = tid & 31, warp = __shfl_sync(0xffffffffu, tid >> 5, 0), wgi = warp >> 2, g = lane >> 2, c = lane & 3;
        const uint32_t srow = warp * 16 + (lane & 15);
        #define T128(t) (sb + (((t) >> 5) * 16 + ((t) & 15)) * 128u + (((((t) >> 4) & 1) ^ ((t) & 7)) << 4))
        const uint32_t pa = T128(tid);
        mbar_wait(BAR(B_WPHI), 0);
        mbar_wait(BAR(B_EA), 1);
        wg_wait<0>();
        acc_fence(a0); acc_fence(a1);
        e_arrive(BAR(B_QE));
        if (warp == 0) TS(18);
        uint32_t ph0[16], ph1[16], kq[32];
        {
        uint32_t pk[16], mm[4], mn[2];
        float ea[32], eb[32];
        {
            float p0[16], p1[16];
            const uint32_t dw = desc_lo(sb + OFF_WPHI, 16);
            #define PMMA(f, o) do { wg_fence(); mma32_rs0<(o), H64>(p0, f, dw); mma32_rs0<(o) + 128, H64>(p1, f + 8, dw); \
                mma32_rs<(o) + 64, H64>(p0, f + 4, dw); mma32_rs<(o) + 192, H64>(p1, f + 12, dw); wg_commit(); } while (0)
            #define V_OUT(lo) _Pragma("unroll") for (int i = lo; i < lo + 4; i++) { const int o = 32 + 8 * i; \
                stsm4(sb + OFF_V + (i >> 1) * 8192u + srow * 64u + (((2 * (i & 1) + (lane >> 4)) ^ ((srow >> 1) & 3)) << 4), \
                      pack2(a1[o], a1[o + 1]), pack2(a1[o + 2], a1[o + 3]), pack2(a1[o + 4], a1[o + 5]), pack2(a1[o + 6], a1[o + 7])); }
            V_OUT(0);
            #pragma unroll
            for (int i = 0; i < 16; i++) ph0[i] = pack2(a0[64 + 2 * i], a0[65 + 2 * i]);
            PMMA(ph0, 0);
            V_OUT(4);
            #undef V_OUT
            wg_wait<0>();
            acc_fence(p0); acc_fence(p1);
            fm_max(p0, pk, mm); fm_max(p1, pk + 8, mm + 2);
            #pragma unroll
            for (int i = 0; i < 16; i++) ph1[i] = pack2(a1[2 * i], a1[2 * i + 1]);
            PMMA(ph1, 256);
            if (warp == 0) TS(19);
            fm_pos(pk, mm, ea);
            #pragma unroll
            for (int i = 0; i < 32; i++) kq[i] = pack2(a0[2 * i], a0[2 * i + 1]);
            acc_fence(ea); pin<32>(kq);
            wg_wait<0>();
            acc_fence(p0); acc_fence(p1);
            #define PHI_OUT(ph, i) do { if (u < 2) { \
                    mbar_wait(u ? BAR(B_PE + (i)) : (i) ? BAR(B_LMD) : BAR(B_QE), 0);          \
                    _Pragma("unroll") for (int q = 0; q < 4; q++) stsm4((pa ^ (q << 5)) + OFF_PHI + (i) * 16384u, ph[4 * q], ph[4 * q + 1], ph[4 * q + 2], ph[4 * q + 3]); \
                    __syncwarp(); \
                    e_arrive(BAR(B_PF + (i)) + u * 16); } } while (0)
            reg_dec<216>();
            #pragma unroll 1
            for (int u = 0; u < 4; u++) {
                fm_neg(mm, ldsf(sb + OFF_CST + 48), ea); fm_pos(pk + 8, mm + 2, eb);
                fm_norm(ea, ph0); fm_max(p0, pk, mm); fm_max(p1, pk + 8, mn);
                PHI_OUT(ph0, 0);
                if (warp == 0) TR(130 + (u & 1) * 6);
                if (u == 0) PMMA(kq, 0); else PMMA(kq + 16, 256);
                fm_neg(mm + 2, ldsf(sb + OFF_CST + 48), eb); fm_pos(pk, mm, ea);
                fm_norm(eb, ph1);
                mm[2] = mn[0]; mm[3] = mn[1];
                PHI_OUT(ph1, 1);
                wg_wait<0>();
                acc_fence(p0); acc_fence(p1);
                if (u == 2) {
                    e_arrive(BAR(B_STP));
                    mbar_wait(BAR(B_GF), 0);
                    #pragma unroll
                    for (int i = 0; i < 16; i++) { kq[i] = ph0[i]; kq[16 + i] = ph1[i]; }
                }
                if (warp == 0) TR(133 + (u & 1) * 6);
                if (warp == 0) TS(21 + u);
            }
            #undef PHI_OUT
            #undef PMMA
        }
        }
        uint32_t gf[16][4], uf[16][4];
        const uint32_t fo = sb + (warp >> 1) * 2048u + ((lane & 7) + (lane >> 4) * 8) * 64u + (((2 * (warp & 1) + ((lane >> 3) & 1)) ^ ((lane >> 1) & 3)) << 4);
        #define F_LOAD(f, off, i) ldsm4t(f[i], fo + (off) + ((i) >> 1) * 8192u + ((i) & 1) * 1024u)
        #define G_LOAD(lo, n, k) do { _Pragma("unroll") for (int i = lo; i < lo + n; i++) F_LOAD(gf, OFF_R0, i); e_arrive(BAR(B_GE + k)); } while (0)
        #define O_BLOCK(pp, ph0, ph1) do { \
            if ((AWAKE & 2) && !(pp)) mbar_wait_awake(BAR(B_KVT + (pp)), 0); else mbar_wait(BAR(B_KVT + (pp)), 0); \
            if (warp == 0) TS(25 + 3 * (pp)); \
            const uint32_t oa = T128(tid + (lds32(sb + OFF_CST) >> 16)); \
            float o0[20], o1[20]; \
            const uint32_t dk = (pp) ? desc_lo(sb + OFF_KL, OFF_Z + 32 - OFF_KL) : desc_lo(sb + OFF_KVT, OFF_Z - OFF_KVT); \
            constexpr uint32_t K1 = 256u - (255u << 16);          \
            wg_fence(); \
            mma40_rs0<0, H64>(o0, ph0, dk); mma40_rs0<K1, H64>(o1, ph1, dk); \
            mma40_rs<64, H64>(o0, ph0 + 4, dk); mma40_rs<K1 + 64, H64>(o1, ph1 + 4, dk); \
            mma40_rs<128, H64>(o0, ph0 + 8, dk); mma40_rs<K1 + 128, H64>(o1, ph1 + 8, dk); \
            mma40_rs<192, H64>(o0, ph0 + 12, dk); mma40_rs<K1 + 192, H64>(o1, ph1 + 12, dk); \
            wg_commit(); \
            wg_wait<0>(); \
            acc_fence(o0); acc_fence(o1); \
            if (pp) e_arrive(BAR(B_ED)); \
            if (warp == 0) TS(26 + 3 * (pp)); \
            mbar_wait(BAR(B_GE + (pp)), 0); \
            _Pragma("unroll") for (int hh = 0; hh < 2; hh++) { \
                const float (&o)[20] = hh ? o1 : o0; \
                uint32_t h0, l0, h1, l1; \
                split_rcp(rcp(rbf(rbf(o[16]) + 1e-6f)), h0, l0); split_rcp(rcp(rbf(rbf(o[18]) + 1e-6f)), h1, l1); \
                _Pragma("unroll") for (int q = 0; q < 2; q++) \
                    stsm4((oa ^ ((2 * hh + q) << 5)) + OFF_R0 + (pp) * 16384u, hdiv2(pack2(o[8 * q], o[8 * q + 1]), h0, l0), hdiv2(pack2(o[8 * q + 2], o[8 * q + 3]), h1, l1), \
                          hdiv2(pack2(o[8 * q + 4], o[8 * q + 5]), h0, l0), hdiv2(pack2(o[8 * q + 6], o[8 * q + 7]), h1, l1)); \
            } \
            fence_async_smem(); \
            __syncwarp(); \
            e_arrive(BAR(B_OWN + (pp))); \
            if (warp == 0) TS(27 + 3 * (pp)); \
        } while (0)
        float acc[64];
        const uint32_t da = desc_lo(sb + OFF_R0 + wgi * 8192u, 16), db = desc_lo(sb + OFF_DB, 8192);
        #define D_MMA(first, a, s) do { \
            wg_fence(); \
            first<(a), H128, (s) * 1024, H128>(acc, da, db); mma128_ss<(a) + 2, H128, (s) * 1024 + 128, H128>(acc, da, db); \
            mma128_ss<(a) + 4, H128, (s) * 1024 + 256, H128>(acc, da, db); mma128_ss<(a) + 6, H128, (s) * 1024 + 384, H128>(acc, da, db); \
            wg_commit(); } while (0)
        G_LOAD(0, 4, 0);
        O_BLOCK(0, kq, (kq + 16));
        G_LOAD(4, NG1, 1);
        mbar_wait(BAR(B_OWN), 0);
        mbar_wait(BAR(B_FD), 0);
        D_MMA(mma128_ss0, 0, 0);
        O_BLOCK(1, ph0, ph1);
        G_LOAD(4 + NG1, 12 - NG1, 2);
        reg_inc<232>();
        mbar_wait(BAR(B_OWN + 1), 0);
        #undef O_BLOCK
        #define D_STEP(n) do { \
            mbar_wait(BAR(B_FD + ((n) & 3)), ((n) >> 2) & 1); \
            if (warp == 0) TR(112 + (n)); \
            D_MMA(mma128_ss, (n) == 5 ? OFF_X1 / 16 : ((n) & 3) * 1024, (n) & 3); \
            if ((n) == 3) mbar_wait(BAR(B_UF), 0); \
            if ((n) >= 3 && (n) < 7) { F_LOAD(uf, OFF_F2, 2 * (((n) + 5) & 7)); F_LOAD(uf, OFF_F2, 2 * (((n) + 5) & 7) + 1); } \
            wg_wait<1>(); \
            if ((n) > 2) e_arrive(BAR(B_ED + (((n) + 3) & 3))); } while (0)
        D_STEP(1);
        wg_wait<0>();
        e_arrive(BAR(B_ED + 1));
        D_STEP(2);
        if (warp == 0) TS(31);
        D_STEP(3); D_STEP(4); D_STEP(5); D_STEP(6); D_STEP(7); D_STEP(8); D_STEP(9); D_STEP(10); D_STEP(11); D_STEP(12); D_STEP(13); D_STEP(14); D_STEP(15);
        #undef D_STEP
        #undef D_MMA
        #define XADDR(i) ((xa ^ (((i) & 3) << 5)) + ((i) < 4 ? OFF_R0 : OFF_X1))
        mbar_wait(BAR(B_PAR), 0);
        const uint4 cst = lds128(sb + OFF_CST);
        const int b = cst.x & 255;
        const uint32_t tag = cst.y, xa = T128(tid + (cst.x >> 16));
        uint4 w[4];
        const uint32_t rl = warp * 16 + g + 8 * (c & 1);
        const uint4* ws = pin_ptr(p.s->llln2 + ((b & ~7) + (c >> 1) * 4) * 128 + rl);
        {
        {
            uint32_t x2[8][4];
            mbar_wait(BAR(B_WPHI), 1);
            #pragma unroll
            for (int i = 0; i < 8; i++) ldsm4(x2[i], XADDR(i));
            uint4* d = pin_ptr(p.s->llln2 + b * 128 + warp * 16 + g);
            const uint32_t ta = sb + OFF_T1 + (g & 1) * 512 + c * 16;
            uint4 t = lds128(ta), tn = lds128(ta + 64);
            wg_wait<0>();
            acc_fence(acc);
            e_arrive(BAR(B_ED + 3));
            if (warp == 0) TS(32);
            float sd[4] = {0.f, 0.f, 0.f, 0.f}, qa[4] = {0.f, 0.f, 0.f, 0.f}, qb[4] = {0.f, 0.f, 0.f, 0.f};
            #pragma unroll
            for (int i = 0; i < 8; i++) {
                x2[i][0] = hadd2(x2[i][0], hmul2(t.x, pack2(acc[8 * i], acc[8 * i + 1]))); x2[i][1] = hadd2(x2[i][1], hmul2(t.x, pack2(acc[8 * i + 2], acc[8 * i + 3])));
                x2[i][2] = hadd2(x2[i][2], hmul2(t.y, pack2(acc[8 * i + 4], acc[8 * i + 5]))); x2[i][3] = hadd2(x2[i][3], hmul2(t.y, pack2(acc[8 * i + 6], acc[8 * i + 7])));
                mma16816(sd, x2[i][0], x2[i][1], x2[i][2], x2[i][3], t.z, t.w);
                t = tn;
                if (i < 6) tn = lds128(ta + (i + 2) * 64);
                mma16816(qa, x2[i][0], x2[i][1], x2[i][2], x2[i][3], x2[i][0], x2[i][2]);
                mma16816(qb, x2[i][0], x2[i][1], x2[i][2], x2[i][3], x2[i][1], x2[i][3]);
            }
            if (c == (g >> 1)) {
                st_ll(d, f2u(sd[0]), f2u((g & 1) ? qa[1] : qa[0]), f2u(sd[1]), tag);
                st_ll(d + 8, f2u(sd[2]), f2u((g & 1) ? qb[3] : qb[2]), f2u(sd[3]), tag);
            }
            __syncwarp();
            #pragma unroll
            for (int i = 0; i < 4; i++) w[i] = ld_ll(ws + i * 128);
            if (warp == 0) TS(33);
            #pragma unroll
            for (int i = 0; i < 8; i++) stsm4(XADDR(i), x2[i][0], x2[i][1], x2[i][2], x2[i][3]);
        }
        uint4 t2[8]; uint2 t3[8];
        #pragma unroll
        for (int i = 0; i < 8; i++) { t2[i] = lds128(sb + OFF_T2 + i * 64 + c * 16); t3[i] = lds64(sb + OFF_T3 + i * 32 + c * 8); }
        mbar_wait(BAR(B_ED + 3), 1);
        {
            #pragma unroll 1
            for (int it = 0; it < POLL_MAX; it++) {
                if (__all_sync(0xffffffffu, !(tag_bad(w[0].w ^ tag, w[1].w, tag) | tag_bad(w[2].w ^ tag, w[3].w, tag)))) break;
                #pragma unroll
                for (int i = 0; i < 4; i++) if (w[i].w != tag) w[i] = ld_ll(ws + i * 128);
            }
            float s1 = (u2f(w[0].x) + u2f(w[1].x)) + (u2f(w[2].x) + u2f(w[3].x));
            float s2 = (u2f(w[0].y) + u2f(w[1].y)) + (u2f(w[2].y) + u2f(w[3].y));
            float dt = (u2f(w[0].z) + u2f(w[1].z)) + (u2f(w[2].z) + u2f(w[3].z));
            s1 += shfl_x(s1, 2); s2 += shfl_x(s2, 2); dt += shfl_x(dt, 2);
            uint32_t m2, rh, rl2; float rinv;
            ln_final(s1, s2, m2, rinv);
            const uint32_t key = (f2key(fmaf(fmaf(-bf_lo(m2), u2f(cst.z), dt), rinv, u2f(cst.w))) | 2047u) ^ ((b >> 3) * 128 + rl);
            split_rcp(rinv, rh, rl2);
            if (c < 2) { sts32(sb + OFF_KEY + rl * 4, key); sts128(sb + OFF_ST2 + rl * 16, make_uint4(m2, rh, rl2, 0)); }
            __syncwarp();
            e_arrive(BAR(B_KEYS));
        }
        if (warp == 0) TS(34);
        {
            const uint4 s0 = lds128(sb + OFF_ST2 + (warp * 16 + g) * 16), s1 = lds128(sb + OFF_ST2 + (warp * 16 + g + 8) * 16);
            uint32_t x2[8][4];
            #pragma unroll
            for (int i = 0; i < 8; i++) ldsm4(x2[i], XADDR(i));
            const uint32_t oa = xa + warp * 2048u;
            #pragma unroll
            for (int i = 0; i < 8; i++) {
                const uint4 t = t2[i]; const uint2 gb = t3[i];
                stsm4((oa ^ ((i & 3) << 5)) + OFF_OUT + (i >> 2) * 2048u,
                      hadd2(x2[i][0], hmul2(gb.x, lnmod(x2[i][0], s0.x, s0.y, s0.z, t.x, t.z))), hadd2(x2[i][1], hmul2(gb.x, lnmod(x2[i][1], s1.x, s1.y, s1.z, t.x, t.z))),
                      hadd2(x2[i][2], hmul2(gb.y, lnmod(x2[i][2], s0.x, s0.y, s0.z, t.y, t.w))), hadd2(x2[i][3], hmul2(gb.y, lnmod(x2[i][3], s1.x, s1.y, s1.z, t.y, t.w))));
            }
            __syncwarp();
            e_arrive(BAR(B_SWP));
        }
        }
        #undef XADDR
        if (warp == 0) TS(35);
        uint32_t fx = 0, fh = 0, fg = 0, fs2, frow;
        uint32_t df[16][4];
        const uint32_t dfo = sb + warp * 4096u + ((lane & 7) + (lane >> 4) * 8) * 128u + ((((lane >> 3) & 1) ^ (lane & 7)) << 4);
        #define DF_LOAD(i) ldsm4t(df[i], (dfo + ((i) < 8 ? OFF_F2 : OFF_DB) + ((i) & 1) * 2048u) ^ ((((i) >> 1) & 3) << 5))
        {
            const int wi = ((tid >> 3) & 7) * 32 + (tid >> 6) * 8 + (tid & 7);
            const uint4* rh = pin_ptr(p.s->llrowh + wi);
            #pragma unroll
            for (int i = 8; i < 16; i++) F_LOAD(uf, OFF_F2, i);
            mbar_wait(BAR(B_SEL) + ((AWAKE & 4) ? awake_zero() : 0), 0);
            const uint2 bb = lds64(sb + OFF_CST + 24);
            const uint32_t b0 = bb.x, b1 = bb.y;
            if (warp == 0) TS(36);
            const uint32_t o0 = (~b0 & 0x780u) * 4, o1 = (~b1 & 0x780u) * 4, slot0 = o0, slot1 = o1 + (o0 == o1 ? 256 : 0);
            const int wd = ((g & 1) ? slot1 : slot0) + b * 2 + (c >> 1) - wi;
            uint4 hv[2], fv[2];
            #pragma unroll 1
            for (int it = 0; it < POLL_MAX; it++) {
                hv[0] = ld_ll(rh + slot0); hv[1] = ld_ll(rh + slot1);
                uint32_t bad = 0;
                if (warp == 0) {
                    fv[0] = ld_ll(rh + wd + 8192); fv[1] = ld_ll(rh + wd);
                    bad = tag_bad(fv[0].w ^ tag, fv[1].w, tag);
                    fx = (g & 2) ? fv[0].y : fv[0].x; fh = (g & 2) ? fv[1].y : fv[1].x; fg = (g & 2) ? fv[0].z : fv[1].z;
                }
                if (it == 0) {
                    mbar_wait(BAR(B_WD), 0);
                    #pragma unroll
                    for (int i = 0; i < NDF; i++) DF_LOAD(i);
                }
                if (__all_sync(0xffffffffu, !ll_bad<1>(ll_bad<1>(bad, hv[0], tag), hv[1], tag))) break;
            }
            const uint32_t ha = sb + OFF_HSEL + (tid >> 3) * 128u + c * 16u + (g & 1) * 8u;
            sts64(ha, hv[0].x, hv[0].y); sts64(ha + 64, hv[1].x, hv[1].y);
            bar_sync(2 + (warp >> 1), 64);
            const uint32_t bk = (g & 1) ? b1 : b0;
            frow = ~bk & 2047u;
            const float sg = sigmoid_f(rbf(key2f((bk & ~2047u) | 1024u)));
            fs2 = pack2(sg, sg);
        }
        if (warp == 0) TS(37);
        uint4* yd = p.s->lly + (cst.x >> 8) * 512 + (warp * 8 + c) * 8 + g;
        const uint4* ys = p.s->lly + (tid >> 2) * 512 + b * 4 + c;
        uint16_t* od = (uint16_t*)p.out + (size_t)frow * 1024 + (b >> 1) * 16 + (b & 1) * 4 + c + 8 * (g >> 1);
        {
            float ag[2][4], au[2][4];
            #pragma unroll
            for (int i = 0; i < 4; i++) ag[0][i] = ag[1][i] = au[0][i] = au[1][i] = 0.f;
            const uint32_t ha = sb + OFF_HSEL + (warp >> 1) * 1024u + (lane & 7) * 16u;
            uint4 hn = lds128(ha), hm = lds128(ha + 128);
            #pragma unroll
            for (int i = 0; i < 8; i++) {
                const uint4 h = hn;
                hn = hm;
                if (i < 6) hm = lds128(ha + (i + 2) * 128u);
                mma16816(ag[0], gf[2 * i][0], gf[2 * i][1], gf[2 * i][2], gf[2 * i][3], h.x, h.y);
                mma16816(au[0], uf[2 * i][0], uf[2 * i][1], uf[2 * i][2], uf[2 * i][3], h.x, h.y);
                mma16816(ag[1], gf[2 * i + 1][0], gf[2 * i + 1][1], gf[2 * i + 1][2], gf[2 * i + 1][3], h.z, h.w);
                mma16816(au[1], uf[2 * i + 1][0], uf[2 * i + 1][1], uf[2 * i + 1][2], uf[2 * i + 1][3], h.z, h.w);
                if (NDF + 2 * i < 16) { DF_LOAD((NDF + 2 * i) & 15); DF_LOAD((NDF + 2 * i + 1) & 15); }
            }
            sts64(sb + OFF_RED + (warp >> 1) * 512u + (c & 1) * 256u + ((warp & 1) * 16 + (c >> 1) * 8 + g) * 8u,
                  f2u(sel4(c, ag[0][0], ag[0][1], ag[0][2], ag[0][3]) + sel4(c, ag[1][0], ag[1][1], ag[1][2], ag[1][3])),
                  f2u(sel4(c, au[0][0], au[0][1], au[0][2], au[0][3]) + sel4(c, au[1][0], au[1][1], au[1][2], au[1][3])));
        }
        yd = pin_ptr(yd); ys = pin_ptr(ys); od = pin_ptr(od); pin<1>(&fs2);
        bar_sync(1, 256);
        {
            const uint32_t ra = sb + OFF_RED + lane * 16u;
            const uint4 r0 = lds128(ra), r1 = lds128(ra + 512), r2 = lds128(ra + 1024), r3 = lds128(ra + 1536);
            #define F4(f) ((u2f(r0.f) + u2f(r1.f)) + (u2f(r2.f) + u2f(r3.f)))
            const uint32_t hid = hmul2(silu2(pack2(F4(x), F4(z))), pack2(F4(y), F4(w)));
            #undef F4
            if (warp == 0) TS(38);
            const int src = (g & 1) * 16 + c;
            const uint32_t b0 = __shfl_sync(0xffffffffu, hid, src), b1 = __shfl_sync(0xffffffffu, hid, src + 4), b2 = __shfl_sync(0xffffffffu, hid, src + 8), b3 = __shfl_sync(0xffffffffu, hid, src + 12);
            float y[8][4];
            #pragma unroll
            for (int i = 0; i < 8; i++) {
                y[i][0] = y[i][1] = y[i][2] = y[i][3] = 0.f;
                mma16816(y[i], df[2 * i][0], df[2 * i][1], df[2 * i][2], df[2 * i][3], b0, b1);
            }
            #pragma unroll
            for (int i = 0; i < 8; i++) mma16816(y[i], df[2 * i + 1][0], df[2 * i + 1][1], df[2 * i + 1][2], df[2 * i + 1][3], b2, b3);
            if (cst.x < 112 * 256) {
                #pragma unroll
                for (int h = 0; h < 2; h++) {
                    #define YS(e) sel4(c, y[4 * h][e], y[4 * h + 1][e], y[4 * h + 2][e], y[4 * h + 3][e])
                    st_ll4(yd + 32 * h, YS(0), YS(1), YS(2), YS(3), tag);
                    #undef YS
                }
            }
        }
        if (warp == 0) TS(39);
        if (warp < 7) {
            uint4 v[2];
            v[0].w = v[1].w = 0;
            spin_until(clk32() + YWAIT);
            #pragma unroll 1
            for (int it = 0; it < POLL_MAX; it++) {
                if ((v[0].w ^ tag) & 3) v[0] = ld_ll(ys);
                if ((v[1].w ^ tag) & 3) v[1] = ld_ll(ys + 56 * 512);
                if (__all_sync(0xffffffffu, !(tag_bad(v[0].w ^ tag, v[1].w, tag) & 3))) break;
            }
            float y0 = u2f(v[0].x) + u2f(v[1].x), y1 = u2f(v[0].y) + u2f(v[1].y), y2 = u2f(v[0].z) + u2f(v[1].z), y3 = u2f(v[0].w) + u2f(v[1].w);
            const bool g0 = g & 1, g1 = g & 2;
            const float k0 = (g0 ? y1 : y0) + shfl_x(g0 ? y0 : y1, 4), k1 = (g0 ? y3 : y2) + shfl_x(g0 ? y2 : y3, 4);
            const float y = (g1 ? k1 : k0) + shfl_x(g1 ? k0 : k1, 8);
            stsf(sb + OFF_RED2 + (lane & 15) * 64u + (lane >> 4) * 32u + warp * 4u, y);
            bar_sync(6, 224);
            if (tid < 16) {
                const uint32_t a = sb + OFF_RED2 + lane * 64u;
                const uint4 ya = lds128(a), yb = lds128(a + 16), yc = lds128(a + 32), ye = lds128(a + 48);
                const float s = (((u2f(ya.x) + u2f(ya.y)) + (u2f(ya.z) + u2f(ya.w))) + ((u2f(yb.x) + u2f(yb.y)) + u2f(yb.z)))
                              + (((u2f(yc.x) + u2f(yc.y)) + (u2f(yc.z) + u2f(yc.w))) + ((u2f(ye.x) + u2f(ye.y)) + u2f(ye.z)));
                const uint32_t o = hadd2(fx, hmul2(fg, hadd2(fh, hmul2(pack2(s, s), fs2))));
                *od = (c & 1) ? o >> 16 : o;
                if (b == 0 && tid == 0) p.s->done[0] = tag;
                TS(40);
            }
        }
    }
}

typedef CUresult (*EncodeFn)(CUtensorMap*, CUtensorMapDataType, cuuint32_t, void*, const cuuint64_t*, const cuuint64_t*, const cuuint32_t*,
                             const cuuint32_t*, CUtensorMapInterleave, CUtensorMapSwizzle, CUtensorMapL2promotion, CUtensorMapFloatOOBfill);

CUtensorMap make_map(EncodeFn enc, const void* ptr, uint64_t cols, uint64_t rows, uint32_t bc, uint32_t br, CUtensorMapSwizzle swz, CUtensorMapL2promotion promo) {
    CUtensorMap m;
    cuuint64_t dims[2] = {cols, rows}, strides[1] = {cols * 2};
    cuuint32_t box[2] = {bc, br}, es[2] = {1, 1};
    enc(&m, CU_TENSOR_MAP_DATA_TYPE_BFLOAT16, 2, const_cast<void*>(ptr), dims, strides, box, es, CU_TENSOR_MAP_INTERLEAVE_NONE, swz, promo,
        CU_TENSOR_MAP_FLOAT_OOB_FILL_NONE);
    return m;
}
CUtensorMap make_map4(EncodeFn enc, const void* ptr, uint32_t groups, uint64_t rows, uint32_t br, CUtensorMapL2promotion promo) {
    CUtensorMap m;
    cuuint64_t dims[4] = {64, rows, 16, groups}, strides[3] = {groups * 2048ull, 128, 2048};
    cuuint32_t box[4] = {64, br, 2, groups}, es[4] = {1, 1, 1, 1};
    enc(&m, CU_TENSOR_MAP_DATA_TYPE_BFLOAT16, 4, const_cast<void*>(ptr), dims, strides, box, es, CU_TENSOR_MAP_INTERLEAVE_NONE, CU_TENSOR_MAP_SWIZZLE_128B, promo,
        CU_TENSOR_MAP_FLOAT_OOB_FILL_NONE);
    return m;
}

}

extern "C" void kernel_launch(void* const* d_in, const int* in_sizes, int n_in, void* d_out, int out_size) {
    (void)in_sizes; (void)n_in; (void)out_size;
    void* fn = nullptr; cudaDriverEntryPointQueryResult qr;
    cudaGetDriverEntryPoint("cuTensorMapEncodeTiled", &fn, cudaEnableDefault, &qr);
    EncodeFn enc = (EncodeFn)fn;
    void* hs = nullptr;
    cudaGetSymbolAddress(&hs, g_scratch);
    int dev = 0, sms = 0;
    cudaGetDevice(&dev);
    cudaDeviceGetAttribute(&sms, cudaDevAttrMultiProcessorCount, dev);
    const CUtensorMapL2promotion P256 = CU_TENSOR_MAP_L2_PROMOTION_L2_256B, P128 = CU_TENSOR_MAP_L2_PROMOTION_L2_128B, P0 = CU_TENSOR_MAP_L2_PROMOTION_NONE;
    CUtensorMap tmW = make_map4(enc, d_in[1], 3, 1024, 32, P256);
    CUtensorMap tmWo = make_map4(enc, d_in[3], 1, 1024, 64, P256);
    CUtensorMap tmO = make_map4(enc, d_out, 1, 2048, 16, P0);
    CUtensorMap tmPhi = make_map(enc, d_in[2], 32, 1024, 32, 128, CU_TENSOR_MAP_SWIZZLE_64B, P128);
    CUtensorMap tmG = make_map(enc, d_in[6], 3584, 1024, 32, 128, CU_TENSOR_MAP_SWIZZLE_64B, P0);
    CUtensorMap tmU = make_map(enc, d_in[7], 3584, 1024, 32, 128, CU_TENSOR_MAP_SWIZZLE_64B, P0);
    CUtensorMap tmD = make_map(enc, d_in[8], 1024, 3584, 64, 32, CU_TENSOR_MAP_SWIZZLE_128B, P128);
    CUtensorMap tmX = make_map(enc, d_in[0], 1024, 2048, 64, 128, CU_TENSOR_MAP_SWIZZLE_128B, P128);
    CUtensorMap tmM = make_map(enc, d_in[10], 6144, 1024, 64, 256, CU_TENSOR_MAP_SWIZZLE_128B, MPROMO);
    Ptrs p;
    p.x = (const bf16*)d_in[0]; p.c = (const bf16*)d_in[9]; p.wmod = (const bf16*)d_in[10]; p.wr = (const bf16*)d_in[5];
    p.wg = (const bf16*)d_in[6]; p.wu = (const bf16*)d_in[7]; p.wd = (const bf16*)d_in[8]; p.out = (bf16*)d_out; p.s = (Scratch*)hs;
    p.wqkv = (const bf16*)d_in[1]; p.wo = (const bf16*)d_in[3];
    p.by_sm = sms == 132;
    for (int sm = 0; sm < 132; sm++) {
        const int tp = sm >> 1, u = tp - 32;
        const int gp = (GPERM >> (4 * (tp < 32 ? tp & 7 : tp < 60 ? 1 + u % 7 : 0))) & 7, sl = 2 * (tp < 32 ? tp >> 3 : tp < 60 ? 4 + u / 7 : tp - 58) + (sm & 1);
        const int b = (tp >> 1) == 30 ? sm + 8 : ((gp >> 1) * 4 + (sl & 3)) * 8 + (gp & 1) * 4 + (sl >> 2);
        const int f = FMODE == 0 ? (b < 112 ? b : 255) : FMODE == 1 ? (sl < 14 && b < 128 ? gp * 14 + sl : 255) : (sm < 112 ? sm : 255);
        p.role[sm] = (uint16_t)(b | f << 8);
    }
    cudaFuncSetAttribute(fused_kernel, cudaFuncAttributeMaxDynamicSharedMemorySize, SMEM_BYTES);
    fused_kernel<<<132, NTHREADS, SMEM_BYTES, cudaStreamPerThread>>>(p, tmM, tmX, tmW, tmWo, tmPhi, tmG, tmU, tmD, tmO);
}
```

```cpp
#include <cuda_runtime.h>
#include <cuda.h>
#include <cuda_bf16.h>
#include <stdint.h>

namespace {

typedef __nv_bfloat16 bf16;

#define NFREE 4
constexpr int NTHREADS = 512;
constexpr int POLL_MAX = 400000;

constexpr uint32_t OFF_R0   = 0;
constexpr uint32_t OFF_A    = 65536;
constexpr uint32_t OFF_B    = 114688;
constexpr uint32_t OFF_V    = 65536;
constexpr uint32_t OFF_PHI  = 98304;
constexpr uint32_t OFF_F2   = 65536;
constexpr uint32_t OFF_DB   = 131072;
constexpr uint32_t OFF_KL   = 196608;
constexpr uint32_t OFF_WPHI = 214016;
constexpr uint32_t OFF_KVT  = OFF_WPHI;
constexpr uint32_t OFF_Z    = 222208;
constexpr uint32_t OFF_TAB  = OFF_Z;
constexpr uint32_t OFF_ONES = 226304;
constexpr uint32_t OFF_BAR  = 227328;
constexpr uint32_t OFF_CST  = OFF_BAR + 640;
constexpr uint32_t OFF_T1   = OFF_ONES;
constexpr uint32_t OFF_T2   = OFF_CST + 64;
constexpr uint32_t OFF_T3   = OFF_T2 + 512;
constexpr uint32_t OFF_KEY  = OFF_T3 + 256;
constexpr uint32_t OFF_ST2  = OFF_KEY + 512;
constexpr uint32_t OFF_ZS   = OFF_ST2;
constexpr uint32_t SMEM_BYTES = 232448;
constexpr uint32_t OFF_X1   = OFF_KL;
constexpr uint32_t OFF_OUT  = OFF_R0 + 32768;
constexpr uint32_t OFF_HSEL = OFF_WPHI;
constexpr uint32_t OFF_RED  = OFF_WPHI + 4096;
constexpr uint32_t OFF_RED2 = OFF_RED + 2048;
static_assert(OFF_ST2 + 2048 <= SMEM_BYTES, "layout");

enum {
    B_O1 = 0, B_UF = 1, B_UD = 2, B_WPHI = 3, B_FB = 4  , B_OST = 8, B_GF = 9, B_WD = 10, B_KVL = 11  , B_KZ = 13, B_LMF = 14, B_SEL = 15, B_XP = 16  , B_TAG = 24,
    B_FA = 25  , B_FD = 30  , B_CAND = 34,
    B_PE = 35  , B_KST = 37  , B_KVT = 41  , B_LMD = 43, B_PAR = 44,
    B_EA = 45  , B_EB = 48  , B_ED = 52  , B_PF = 56  , B_OWN = 60  , B_QE = 62, B_STP = 63, B_KEYS = 64, B_SWP = 65, B_STS = 66, B_GE = 67
};

struct Scratch {
    uint4 os[16 * 16 * 1024];
    uint4 kvacc[8 * 4 * 528];
    uint4 flk[3 * 128 * 2];
    uint4 llstat[2048];
    uint4 llm1[16 * 64];
    uint4 flo[16 * 16 * 2];
    uint4 llmod2[2 * 256];
    uint4 llg[2 * 4 * 256];
    uint4 llln2[16 * 8 * 128];
    uint4 llcand[16 * 2];
    uint4 llrowh[32 * 256];
    uint4 llrowx[32 * 256];
    uint4 lly[128 * 512];
    unsigned done[4];
};
__device__ __align__(1024) Scratch g_scratch;
#define GT(i) do {} while (0)
#define TS(i) do {} while (0)
#define TR(i) do {} while (0)

__device__ __forceinline__ uint32_t smem_u32(const void* p) { return (uint32_t)__cvta_generic_to_shared(p); }
__device__ __forceinline__ uint32_t clk32() { uint32_t c; asm volatile("mov.u32 %0, %%clock;" : "=r"(c) :: "memory"); return c; }
__device__ __forceinline__ void spin_until(uint32_t t) { while ((int)(clk32() - t) < 0) {} }
__device__ __forceinline__ void sleep_until(uint32_t t) { while ((int)(clk32() - t) < 0) __nanosleep(40); }
__device__ __forceinline__ void mbar_init_fence() { asm volatile("fence.mbarrier_init.release.cluster;" ::: "memory"); }
__device__ __forceinline__ void mbar_wait(uint32_t bar, uint32_t parity) {
    asm volatile("{\n.reg .pred P1;\nLAB_WAIT:\nmbarrier.try_wait.parity.shared::cta.b64 P1, [%0], %1;\n@!P1 bra LAB_WAIT;\n}" :: "r"(bar), "r"(parity) : "memory");
}
__device__ __forceinline__ uint64_t policy_evict_first() { uint64_t p; asm("createpolicy.fractional.L2::evict_first.b64 %0, 1.0;" : "=l"(p)); return p; }
#define ELECT "{\n.reg .pred e;\nelect.sync _|e, 0xffffffff;\n@e "
__device__ __forceinline__ void e_arrive(uint32_t bar) { asm volatile(ELECT "mbarrier.arrive.shared::cta.b64 _, [%0];\n}" :: "r"(bar) : "memory"); }
__device__ __forceinline__ void e_arrive_tx(uint32_t bar, uint32_t bytes) { asm volatile(ELECT "mbarrier.arrive.expect_tx.shared::cta.b64 _, [%0], %1;\n}" :: "r"(bar), "r"(bytes) : "memory"); }
__device__ __forceinline__ void e_init(uint32_t bar, uint32_t cnt) { asm volatile(ELECT "mbarrier.init.shared::cta.b64 [%0], %1;\n}" :: "r"(bar), "r"(cnt) : "memory"); }
__device__ __forceinline__ void tma_load_ef(uint32_t dst, const CUtensorMap* tm, int c0, int c1, uint32_t bar) {
    asm volatile(ELECT "cp.async.bulk.tensor.2d.shared::cluster.global.mbarrier::complete_tx::bytes.L2::cache_hint [%0], [%1, {%3, %4}], [%2], %5;\n}"
        :: "r"(dst), "l"(tm), "r"(bar), "r"(c0), "r"(c1), "l"(policy_evict_first()) : "memory");
}
__device__ __forceinline__ void tma_load(uint32_t dst, const CUtensorMap* tm, int c0, int c1, uint32_t bar) {
    asm volatile(ELECT "cp.async.bulk.tensor.2d.shared::cluster.global.mbarrier::complete_tx::bytes [%0], [%1, {%3, %4}], [%2];\n}"
        :: "r"(dst), "l"(tm), "r"(bar), "r"(c0), "r"(c1) : "memory");
}
__device__ __forceinline__ void tma_load4(uint32_t dst, const CUtensorMap* tm, int row, int blk, uint32_t bar) {
    asm volatile(ELECT "cp.async.bulk.tensor.4d.shared::cluster.global.mbarrier::complete_tx::bytes [%0], [%1, {0, %3, %4, 0}], [%2];\n}"
        :: "r"(dst), "l"(tm), "r"(bar), "r"(row), "r"(blk) : "memory");
}
__device__ __forceinline__ void tma_store4(const CUtensorMap* tm, int row, int blk, uint32_t src) {
    asm volatile(ELECT "cp.async.bulk.tensor.4d.global.shared::cta.bulk_group [%0, {0, %2, %3, 0}], [%1];\n}" :: "l"(tm), "r"(src), "r"(row), "r"(blk) : "memory");
}
__device__ __forceinline__ void bulk_load(uint32_t dst, const void* src, uint32_t bytes, uint32_t bar) {
    asm volatile(ELECT "cp.async.bulk.shared::cluster.global.mbarrier::complete_tx::bytes [%0], [%1], %2, [%3];\n}" :: "r"(dst), "l"(src), "r"(bytes), "r"(bar) : "memory");
}
__device__ __forceinline__ void bulk_store(void* dst, uint32_t src, uint32_t bytes) {
    asm volatile(ELECT "cp.async.bulk.global.shared::cta.bulk_group [%0], [%1], %2;\n}" :: "l"(dst), "r"(src), "r"(bytes) : "memory");
}
__device__ __forceinline__ void bulk_reduce(void* dst, uint32_t src, uint32_t bytes) {
    asm volatile(ELECT "cp.reduce.async.bulk.global.shared::cta.bulk_group.add.f32 [%0], [%1], %2;\n}" :: "l"(dst), "r"(src), "r"(bytes) : "memory");
}
__device__ __forceinline__ void tma_prefetch(const CUtensorMap* tm, int c0, int c1) {
    asm volatile(ELECT "cp.async.bulk.prefetch.tensor.2d.L2.global [%0, {%1, %2}];\n}" :: "l"(tm), "r"(c0), "r"(c1) : "memory");
}
__device__ __forceinline__ void l2_prefetch(const void* p, uint32_t bytes) {
    asm volatile(ELECT "cp.async.bulk.prefetch.L2.global [%0], %1;\n}" :: "l"(p), "r"(bytes) : "memory");
}
__device__ __forceinline__ void bulk_wait_read() { asm volatile("cp.async.bulk.commit_group;\ncp.async.bulk.wait_group.read 0;" ::: "memory"); }
__device__ __forceinline__ void bulk_wait() { asm volatile("cp.async.bulk.commit_group;\ncp.async.bulk.wait_group 0;" ::: "memory"); }
__device__ __forceinline__ void tmap_prefetch(const CUtensorMap* tm) { asm volatile("prefetch.tensormap [%0];" :: "l"(tm) : "memory"); }
__device__ __forceinline__ void wg_fence() { asm volatile("wgmma.fence.sync.aligned;" ::: "memory"); }
__device__ __forceinline__ void wg_commit() { asm volatile("wgmma.commit_group.sync.aligned;" ::: "memory"); }
template<int N> __device__ __forceinline__ void wg_wait() { asm volatile("wgmma.wait_group.sync.aligned %0;" :: "n"(N) : "memory"); }
template<int N> __device__ __forceinline__ void acc_fence(float (&d)[N]) {
    #pragma unroll
    for (int i = 0; i < N; i++) asm volatile("" : "+f"(d[i]) :: "memory");
}
__device__ __forceinline__ uint32_t desc_lo(uint32_t addr, uint32_t lbo) { return (addr >> 4) | ((lbo >> 4) << 16); }
constexpr uint32_t H128 = 0x40000040u;
constexpr uint32_t H64 = 0x80000020u;
__device__ __forceinline__ void fence_async_smem() { asm volatile("fence.proxy.async.shared::cta;" ::: "memory"); }
__device__ __forceinline__ void bar_sync(int id, int n) { asm volatile("bar.sync %0, %1;" :: "r"(id), "r"(n) : "memory"); }
template<int R> __device__ __forceinline__ void reg_inc() { asm volatile("setmaxnreg.inc.sync.aligned.u32 %0;" :: "n"(R)); }
template<int R> __device__ __forceinline__ void reg_dec() { asm volatile("setmaxnreg.dec.sync.aligned.u32 %0;" :: "n"(R)); }

__device__ __forceinline__ void stsm4(uint32_t addr, uint32_t r0, uint32_t r1, uint32_t r2, uint32_t r3) {
    asm volatile("stmatrix.sync.aligned.m8n8.x4.shared.b16 [%0], {%1,%2,%3,%4};" :: "r"(addr), "r"(r0), "r"(r1), "r"(r2), "r"(r3) : "memory");
}
__device__ __forceinline__ void ldsm4(uint32_t* r, uint32_t addr) {
    asm volatile("ldmatrix.sync.aligned.m8n8.x4.shared.b16 {%0,%1,%2,%3}, [%4];" : "=r"(r[0]), "=r"(r[1]), "=r"(r[2]), "=r"(r[3]) : "r"(addr) : "memory");
}
__device__ __forceinline__ void ldsm4t(uint32_t* r, uint32_t addr) {
    asm volatile("ldmatrix.sync.aligned.m8n8.x4.trans.shared.b16 {%0,%1,%2,%3}, [%4];" : "=r"(r[0]), "=r"(r[1]), "=r"(r[2]), "=r"(r[3]) : "r"(addr) : "memory");
}
__device__ __forceinline__ void mma16816(float (&d)[4], uint32_t a0, uint32_t a1, uint32_t a2, uint32_t a3, uint32_t b0, uint32_t b1) {
    asm volatile("mma.sync.aligned.m16n8k16.row.col.f32.bf16.bf16.f32 {%0,%1,%2,%3}, {%4,%5,%6,%7}, {%8,%9}, {%0,%1,%2,%3};"
        : "+f"(d[0]), "+f"(d[1]), "+f"(d[2]), "+f"(d[3]) : "r"(a0), "r"(a1), "r"(a2), "r"(a3), "r"(b0), "r"(b1));
}
__device__ __forceinline__ uint32_t awake_zero() {
    uint32_t r;
    asm volatile("{\n.reg .f32 d<4>;\nmma.sync.aligned.m16n8k8.row.col.f32.bf16.bf16.f32 {d0,d1,d2,d3}, {%1,%1}, {%1}, {%2,%2,%2,%2};\nmov.b32 %0, d0;\n}" : "=r"(r) : "r"(0), "f"(0.f));
    return r;
}
__device__ __forceinline__ void mbar_wait_awake(uint32_t bar, uint32_t parity) {
    #pragma unroll 1
    for (int it = 0; it < POLL_MAX; it++) {
        uint32_t ok;
        asm volatile("{\n.reg .pred p;\nmbarrier.try_wait.parity.shared::cta.b64 p, [%1], %2;\nselp.u32 %0, 0, 1, p;\n}" : "=r"(ok) : "r"(bar), "r"(parity) : "memory");
        if (__all_sync(0xffffffffu, ok == 0)) break;
        it += awake_zero();
    }
}
__device__ __forceinline__ uint4 lds128(uint32_t a) { uint4 v; asm volatile("ld.shared.v4.b32 {%0,%1,%2,%3}, [%4];" : "=r"(v.x), "=r"(v.y), "=r"(v.z), "=r"(v.w) : "r"(a) : "memory"); return v; }
__device__ __forceinline__ uint32_t lds32(uint32_t a) { uint32_t v; asm volatile("ld.shared.b32 %0, [%1];" : "=r"(v) : "r"(a) : "memory"); return v; }
__device__ __forceinline__ uint2 lds64(uint32_t a) { uint2 v; asm volatile("ld.shared.v2.b32 {%0,%1}, [%2];" : "=r"(v.x), "=r"(v.y) : "r"(a) : "memory"); return v; }
__device__ __forceinline__ float ldsf(uint32_t a) { float v; asm volatile("ld.shared.f32 %0, [%1];" : "=f"(v) : "r"(a) : "memory"); return v; }
__device__ __forceinline__ void sts128(uint32_t a, uint4 v) { asm volatile("st.shared.v4.b32 [%0], {%1,%2,%3,%4};" :: "r"(a), "r"(v.x), "r"(v.y), "r"(v.z), "r"(v.w) : "memory"); }
__device__ __forceinline__ void sts64(uint32_t a, uint32_t x, uint32_t y) { asm volatile("st.shared.v2.b32 [%0], {%1,%2};" :: "r"(a), "r"(x), "r"(y) : "memory"); }
__device__ __forceinline__ void sts32(uint32_t a, uint32_t x) { asm volatile("st.shared.b32 [%0], %1;" :: "r"(a), "r"(x) : "memory"); }
__device__ __forceinline__ void stsf(uint32_t a, float x) { asm volatile("st.shared.f32 [%0], %1;" :: "r"(a), "f"(x) : "memory"); }
__device__ __forceinline__ float u2f(uint32_t v) { return __uint_as_float(v); }
__device__ __forceinline__ uint32_t f2u(float v) { return __float_as_uint(v); }

__device__ __forceinline__ uint32_t ldg32(const void* p) { uint32_t v; asm volatile("ld.global.nc.b32 %0, [%1];" : "=r"(v) : "l"(p)); return v; }
__device__ __forceinline__ void stg128(void* p, uint4 v) { asm volatile("st.global.v4.b32 [%0], {%1,%2,%3,%4};" :: "l"(p), "r"(v.x), "r"(v.y), "r"(v.z), "r"(v.w) : "memory"); }
__device__ __forceinline__ void stg_zero(void* p) { stg128(p, make_uint4(0, 0, 0, 0)); }
__device__ __forceinline__ void fence_gpu() { asm volatile("fence.release.gpu;" ::: "memory"); }
__device__ __forceinline__ void st_ll(uint4* p, uint32_t x, uint32_t y, uint32_t z, uint32_t w) {
    asm volatile("st.relaxed.gpu.global.v4.b32 [%0], {%1,%2,%3,%4};" :: "l"(p), "r"(x), "r"(y), "r"(z), "r"(w) : "memory");
}
__device__ __forceinline__ uint4 ld_ll(const uint4* p) {
    uint4 v;
    asm volatile("ld.relaxed.gpu.global.v4.b32 {%0,%1,%2,%3}, [%4];" : "=r"(v.x), "=r"(v.y), "=r"(v.z), "=r"(v.w) : "l"(p) : "memory");
    return v;
}
template<uint32_t LUT> __device__ __forceinline__ uint32_t lop3(uint32_t a, uint32_t b, uint32_t c) { uint32_t d; asm("lop3.b32 %0, %1, %2, %3, %4;" : "=r"(d) : "r"(a), "r"(b), "r"(c), "n"(LUT)); return d; }
__device__ __forceinline__ uint32_t tag_bad(uint32_t bad, uint32_t w, uint32_t tag) { return lop3<0xF6>(bad, w, tag); }
__device__ __forceinline__ void st_ll4(uint4* p, float a, float b, float c, float d, uint32_t tag) { st_ll(p, f2u(a), f2u(b), f2u(c), lop3<0xD8>(f2u(d), tag, 3u)); }
__device__ __forceinline__ unsigned ld_rlx(const void* p) { unsigned v; asm volatile("ld.relaxed.gpu.global.u32 %0, [%1];" : "=r"(v) : "l"(p) : "memory"); return v; }
__device__ __forceinline__ void st_flag(uint4* p, uint32_t v, int lane) { if (lane < 2) st_ll(p + lane, v, v, v, v); }
__device__ __forceinline__ void poll_flags(const uint4* f, uint32_t tag) {
    unsigned v0 = ld_rlx(f), v1;
    spin_until(clk32() + 140);
    #pragma unroll 1
    for (int it = 0; it < POLL_MAX; it++) {
        v1 = ld_rlx(f);
        if (__all_sync(0xffffffffu, v0 == tag)) break;
        v0 = ld_rlx(f);
        if (__all_sync(0xffffffffu, v1 == tag)) break;
    }
}
template<int Z> __device__ __forceinline__ uint32_t ll_bad(uint32_t bad, const uint4& v, uint32_t tag) {
    bad = tag_bad(bad, v.w, tag);
    return Z && lop3<0x80>(v.x, v.y, v.z) == ~0u ? 1u : bad;
}
template<int N, int Z, uint32_t M = ~0u, int AW = 0> __device__ __forceinline__ void poll_words(uint4 (&v)[N], const uint4* p, int stride, uint32_t tag) {
    #pragma unroll 1
    for (int it = 0; it < POLL_MAX; it++) {
        uint32_t bad = 0;
        #pragma unroll
        for (int i = 0; i < N; i++) v[i] = ld_ll(p + i * stride);
        #pragma unroll
        for (int i = 0; i < N; i++) bad = ll_bad<Z>(bad, v[i], tag);
        if (__all_sync(0xffffffffu, !(bad & M))) break;
        if (AW) it += awake_zero();
    }
}
constexpr uint32_t ONE2 = 0x3F803F80u;
__device__ __forceinline__ uint32_t pack2(float lo, float hi) { uint32_t d; asm("cvt.rn.bf16x2.f32 %0, %1, %2;" : "=r"(d) : "f"(hi), "f"(lo)); return d; }
__device__ __forceinline__ float bf_lo(uint32_t v) { return u2f(v << 16); }
__device__ __forceinline__ float bf_hi(uint32_t v) { return u2f(v & 0xffff0000u); }
__device__ __forceinline__ float rbf(float x) { return bf_lo(pack2(x, 0.f)); }
__device__ __forceinline__ uint32_t hsub2(uint32_t a, uint32_t b) { uint32_t d; asm("sub.rn.bf16x2 %0, %1, %2;" : "=r"(d) : "r"(a), "r"(b)); return d; }
__device__ __forceinline__ uint32_t hadd2(uint32_t a, uint32_t b) { uint32_t d; asm("add.rn.bf16x2 %0, %1, %2;" : "=r"(d) : "r"(a), "r"(b)); return d; }
__device__ __forceinline__ uint32_t hmul2(uint32_t a, uint32_t b) { uint32_t d; asm("mul.rn.bf16x2 %0, %1, %2;" : "=r"(d) : "r"(a), "r"(b)); return d; }
__device__ __forceinline__ uint32_t hfma2(uint32_t a, uint32_t b, uint32_t c) { uint32_t d; asm("fma.rn.bf16x2 %0, %1, %2, %3;" : "=r"(d) : "r"(a), "r"(b), "r"(c)); return d; }
__device__ __forceinline__ uint32_t hmax2(uint32_t a, uint32_t b) { uint32_t d; asm("max.bf16x2 %0, %1, %2;" : "=r"(d) : "r"(a), "r"(b)); return d; }
__device__ __forceinline__ uint32_t hmin2(uint32_t a, uint32_t b) { uint32_t d; asm("min.bf16x2 %0, %1, %2;" : "=r"(d) : "r"(a), "r"(b)); return d; }
__device__ __forceinline__ float ex2(float x) { float y; asm("ex2.approx.ftz.f32 %0, %1;" : "=f"(y) : "f"(x)); return y; }
__device__ __forceinline__ float rcp(float x) { float y; asm("rcp.approx.ftz.f32 %0, %1;" : "=f"(y) : "f"(x)); return y; }
__device__ __forceinline__ float shfl_x(float v, int m) { return __shfl_xor_sync(0xffffffffu, v, m); }
__device__ __forceinline__ uint32_t hdiv2(uint32_t d, uint32_t rh, uint32_t rl) { return hfma2(d, rh, hmul2(d, rl)); }
__device__ __forceinline__ void split_rcp(float r, uint32_t& rh, uint32_t& rl) { rh = pack2(r, r); const float l = r - bf_lo(rh); rl = pack2(l, l); }
__device__ __forceinline__ uint32_t lnmod(uint32_t x, uint32_t m, uint32_t rh, uint32_t rl, uint32_t a, uint32_t s) { return hadd2(hmul2(hdiv2(hsub2(x, m), rh, rl), a), s); }
__device__ __forceinline__ void ln_final(float s1, float s2, uint32_t& m2, float& rinv) {
    const float mean = s1 * (1.0f / 1024.0f), var = fmaf(-mean, mean, s2 * (1.0f / 1024.0f));
    m2 = pack2(mean, mean);
    float sd;
    asm("sqrt.approx.ftz.f32 %0, %1;" : "=f"(sd) : "f"(rbf(rbf(fmaxf(var, 0.f)) + 1e-5f)));
    rinv = rcp(rbf(sd));
}
__device__ __forceinline__ float sigmoid_f(float x) { return rcp(1.0f + ex2(-1.4426950408889634f * x)); }
__device__ __forceinline__ uint32_t silu2(uint32_t v) { return pack2(bf_lo(v) * sigmoid_f(bf_lo(v)), bf_hi(v) * sigmoid_f(bf_hi(v))); }
__device__ __forceinline__ uint32_t f2key(float f) { uint32_t u = f2u(f); return (u & 0x80000000u) ? ~u : (u | 0x80000000u); }
__device__ __forceinline__ float key2f(uint32_t k) { return u2f((k & 0x80000000u) ? k ^ 0x80000000u : ~k); }
template<int N> __device__ __forceinline__ void top2(uint32_t (&k)[N], uint32_t& b0, uint32_t& b1) {
    uint32_t m = k[0];
    #pragma unroll
    for (int i = 1; i < N; i++) m = max(m, k[i]);
    b0 = __reduce_max_sync(0xffffffffu, m);
    m = 0;
    #pragma unroll
    for (int i = 0; i < N; i++) m = max(m, k[i] == b0 ? 0u : k[i]);
    b1 = __reduce_max_sync(0xffffffffu, m);
}
template<class T> __device__ __forceinline__ T sel4(int c, T a0, T a1, T a2, T a3) { return (c & 2) ? ((c & 1) ? a3 : a2) : ((c & 1) ? a1 : a0); }

__device__ __forceinline__ void fm_max(const float (&a)[16], uint32_t* p, uint32_t* mm) {
    #pragma unroll
    for (int i = 0; i < 8; i++) p[i] = pack2(a[2 * i], a[2 * i + 1]);
    #pragma unroll
    for (int h = 0; h < 2; h++) {
        const uint32_t mx = hmax2(hmax2(p[h], p[2 + h]), hmax2(p[4 + h], p[6 + h]));
        const uint32_t mn = hmin2(hmin2(p[h], p[2 + h]), hmin2(p[4 + h], p[6 + h])) ^ 0x80008000u;
        mm[h] = hmax2(__byte_perm(mx, mn, 0x5410), __byte_perm(mx, mn, 0x7632));
    }
    #pragma unroll
    for (int d = 1; d <= 2; d++) { mm[0] = hmax2(mm[0], __shfl_xor_sync(0xffffffffu, mm[0], d)); mm[1] = hmax2(mm[1], __shfl_xor_sync(0xffffffffu, mm[1], d)); }
}
constexpr float LOG2E = 1.4426950408889634f;
__device__ __forceinline__ void fm_pos(const uint32_t* p, const uint32_t* mm, float (&e)[32]) {
    #pragma unroll
    for (int h = 0; h < 2; h++) {
        const float cp = -bf_lo(mm[h]) * LOG2E;
        #pragma unroll
        for (int j = 0; j < 4; j++) {
            const float f0 = bf_lo(p[2 * j + h]), f1 = bf_hi(p[2 * j + h]);
            e[8 * h + 2 * j] = ex2(fmaf(f0, LOG2E, cp)); e[8 * h + 2 * j + 1] = ex2(fmaf(f1, LOG2E, cp));
            e[16 + 8 * h + 2 * j] = f0; e[16 + 8 * h + 2 * j + 1] = f1;
        }
    }
}
__device__ __forceinline__ void fm_neg(const uint32_t* mm, float nl, float (&e)[32]) {
    #pragma unroll
    for (int i = 16; i < 32; i++) e[i] = ex2(fmaf(e[i], -LOG2E, bf_hi(mm[(i >> 3) & 1]) * (i < 16 + NFREE ? -LOG2E : nl)));
}
__device__ __forceinline__ void fm_norm(const float (&e)[32], uint32_t* ph) {
    float s[4];
    #pragma unroll
    for (int k = 0; k < 4; k++) s[k] = ((e[8 * k] + e[8 * k + 1]) + (e[8 * k + 2] + e[8 * k + 3])) + ((e[8 * k + 4] + e[8 * k + 5]) + (e[8 * k + 6] + e[8 * k + 7]));
    #pragma unroll
    for (int k = 0; k < 4; k++) s[k] += shfl_x(s[k], 1);
    #pragma unroll
    for (int k = 0; k < 4; k++) s[k] = rcp(s[k] + shfl_x(s[k], 2));
    #pragma unroll
    for (int k = 0; k < 4; k++)
        #pragma unroll
        for (int j = 0; j < 4; j++) ph[8 * (k >> 1) + 2 * j + (k & 1)] = pack2(e[8 * k + 2 * j] * s[k], e[8 * k + 2 * j + 1] * s[k]);
}
template<class T> __device__ __forceinline__ T* pin_ptr(T* p) { asm volatile("" : "+l"(p) :: "memory"); return p; }
template<int N> __device__ __forceinline__ void pin(uint32_t* d) {
    #pragma unroll
    for (int i = 0; i < N; i++) asm volatile("" : "+r"(d[i]) :: "memory");
}

template<uint32_t BO, uint32_t BH> __device__ __forceinline__ void mma192_rs(float (&d)[96], const uint32_t* a, uint32_t blo) {
  asm volatile("{\n.reg .pred p;\n.reg .b32 ta, tb;\n.reg .b64 da, db;\nadd.u32 tb, %100, %101;\nmov.b64 db, {tb, %102};\nsetp.ne.b32 p, 1, 0;\n"
    "wgmma.mma_async.sync.aligned.m64n192k16.f32.bf16.bf16 {%0, %1, %2, %3, %4, %5, %6, %7, %8, %9, %10, %11, %12, %13, %14, %15, %16, %17, %18, %19, %20, %21, %22, %23, %24, %25, %26, %27, %28, %29, %30, %31, %32, %33, %34, %35, %36, %37, %38, %39, %40, %41, %42, %43, %44, %45, %46, %47, %48, %49, %50, %51, %52, %53, %54, %55, %56, %57, %58, %59, %60, %61, %62, %63, %64, %65, %66, %67, %68, %69, %70, %71, %72, %73, %74, %75, %76, %77, %78, %79, %80, %81, %82, %83, %84, %85, %86, %87, %88, %89, %90, %91, %92, %93, %94, %95}, {%96,%97,%98,%99}, db, p, 1, 1, 1;\n}\n"
    : "+f"(d[0]), "+f"(d[1]), "+f"(d[2]), "+f"(d[3]), "+f"(d[4]), "+f"(d[5]), "+f"(d[6]), "+f"(d[7]), "+f"(d[8]), "+f"(d[9]), "+f"(d[10]), "+f"(d[11]), "+f"(d[12]), "+f"(d[13]), "+f"(d[14]), "+f"(d[15]), "+f"(d[16]), "+f"(d[17]), "+f"(d[18]), "+f"(d[19]), "+f"(d[20]), "+f"(d[21]), "+f"(d[22]), "+f"(d[23]), "+f"(d[24]), "+f"(d[25]), "+f"(d[26]), "+f"(d[27]), "+f"(d[28]), "+f"(d[29]), "+f"(d[30]), "+f"(d[31]), "+f"(d[32]), "+f"(d[33]), "+f"(d[34]), "+f"(d[35]), "+f"(d[36]), "+f"(d[37]), "+f"(d[38]), "+f"(d[39]), "+f"(d[40]), "+f"(d[41]), "+f"(d[42]), "+f"(d[43]), "+f"(d[44]), "+f"(d[45]), "+f"(d[46]), "+f"(d[47]), "+f"(d[48]), "+f"(d[49]), "+f"(d[50]), "+f"(d[51]), "+f"(d[52]), "+f"(d[53]), "+f"(d[54]), "+f"(d[55]), "+f"(d[56]), "+f"(d[57]), "+f"(d[58]), "+f"(d[59]), "+f"(d[60]), "+f"(d[61]), "+f"(d[62]), "+f"(d[63]), "+f"(d[64]), "+f"(d[65]), "+f"(d[66]), "+f"(d[67]), "+f"(d[68]), "+f"(d[69]), "+f"(d[70]), "+f"(d[71]), "+f"(d[72]), "+f"(d[73]), "+f"(d[74]), "+f"(d[75]), "+f"(d[76]), "+f"(d[77]), "+f"(d[78]), "+f"(d[79]), "+f"(d[80]), "+f"(d[81]), "+f"(d[82]), "+f"(d[83]), "+f"(d[84]), "+f"(d[85]), "+f"(d[86]), "+f"(d[87]), "+f"(d[88]), "+f"(d[89]), "+f"(d[90]), "+f"(d[91]), "+f"(d[92]), "+f"(d[93]), "+f"(d[94]), "+f"(d[95])
    : "r"(a[0]), "r"(a[1]), "r"(a[2]), "r"(a[3]), "r"(blo), "n"(BO), "n"(BH));
}
template<uint32_t BO, uint32_t BH> __device__ __forceinline__ void mma192_rsp(float (&d)[96], const uint32_t* a, uint32_t blo, int sc) {
  asm volatile("{\n.reg .pred p;\n.reg .b32 ta, tb;\n.reg .b64 da, db;\nadd.u32 tb, %100, %101;\nmov.b64 db, {tb, %102};\nsetp.ne.b32 p, %103, 0;\n"
    "wgmma.mma_async.sync.aligned.m64n192k16.f32.bf16.bf16 {%0, %1, %2, %3, %4, %5, %6, %7, %8, %9, %10, %11, %12, %13, %14, %15, %16, %17, %18, %19, %20, %21, %22, %23, %24, %25, %26, %27, %28, %29, %30, %31, %32, %33, %34, %35, %36, %37, %38, %39, %40, %41, %42, %43, %44, %45, %46, %47, %48, %49, %50, %51, %52, %53, %54, %55, %56, %57, %58, %59, %60, %61, %62, %63, %64, %65, %66, %67, %68, %69, %70, %71, %72, %73, %74, %75, %76, %77, %78, %79, %80, %81, %82, %83, %84, %85, %86, %87, %88, %89, %90, %91, %92, %93, %94, %95}, {%96,%97,%98,%99}, db, p, 1, 1, 1;\n}\n"
    : "+f"(d[0]), "+f"(d[1]), "+f"(d[2]), "+f"(d[3]), "+f"(d[4]), "+f"(d[5]), "+f"(d[6]), "+f"(d[7]), "+f"(d[8]), "+f"(d[9]), "+f"(d[10]), "+f"(d[11]), "+f"(d[12]), "+f"(d[13]), "+f"(d[14]), "+f"(d[15]), "+f"(d[16]), "+f"(d[17]), "+f"(d[18]), "+f"(d[19]), "+f"(d[20]), "+f"(d[21]), "+f"(d[22]), "+f"(d[23]), "+f"(d[24]), "+f"(d[25]), "+f"(d[26]), "+f"(d[27]), "+f"(d[28]), "+f"(d[29]), "+f"(d[30]), "+f"(d[31]), "+f"(d[32]), "+f"(d[33]), "+f"(d[34]), "+f"(d[35]), "+f"(d[36]), "+f"(d[37]), "+f"(d[38]), "+f"(d[39]), "+f"(d[40]), "+f"(d[41]), "+f"(d[42]), "+f"(d[43]), "+f"(d[44]), "+f"(d[45]), "+f"(d[46]), "+f"(d[47]), "+f"(d[48]), "+f"(d[49]), "+f"(d[50]), "+f"(d[51]), "+f"(d[52]), "+f"(d[53]), "+f"(d[54]), "+f"(d[55]), "+f"(d[56]), "+f"(d[57]), "+f"(d[58]), "+f"(d[59]), "+f"(d[60]), "+f"(d[61]), "+f"(d[62]), "+f"(d[63]), "+f"(d[64]), "+f"(d[65]), "+f"(d[66]), "+f"(d[67]), "+f"(d[68]), "+f"(d[69]), "+f"(d[70]), "+f"(d[71]), "+f"(d[72]), "+f"(d[73]), "+f"(d[74]), "+f"(d[75]), "+f"(d[76]), "+f"(d[77]), "+f"(d[78]), "+f"(d[79]), "+f"(d[80]), "+f"(d[81]), "+f"(d[82]), "+f"(d[83]), "+f"(d[84]), "+f"(d[85]), "+f"(d[86]), "+f"(d[87]), "+f"(d[88]), "+f"(d[89]), "+f"(d[90]), "+f"(d[91]), "+f"(d[92]), "+f"(d[93]), "+f"(d[94]), "+f"(d[95])
    : "r"(a[0]), "r"(a[1]), "r"(a[2]), "r"(a[3]), "r"(blo), "n"(BO), "n"(BH), "r"(sc));
}
template<uint32_t BO, uint32_t BH> __device__ __forceinline__ void mma32_rs(float (&d)[16], const uint32_t* a, uint32_t blo) {
  asm volatile("{\n.reg .pred p;\n.reg .b32 ta, tb;\n.reg .b64 da, db;\nadd.u32 tb, %20, %21;\nmov.b64 db, {tb, %22};\nsetp.ne.b32 p, 1, 0;\n"
    "wgmma.mma_async.sync.aligned.m64n32k16.f32.bf16.bf16 {%0, %1, %2, %3, %4, %5, %6, %7, %8, %9, %10, %11, %12, %13, %14, %15}, {%16,%17,%18,%19}, db, p, 1, 1, 1;\n}\n"
    : "+f"(d[0]), "+f"(d[1]), "+f"(d[2]), "+f"(d[3]), "+f"(d[4]), "+f"(d[5]), "+f"(d[6]), "+f"(d[7]), "+f"(d[8]), "+f"(d[9]), "+f"(d[10]), "+f"(d[11]), "+f"(d[12]), "+f"(d[13]), "+f"(d[14]), "+f"(d[15])
    : "r"(a[0]), "r"(a[1]), "r"(a[2]), "r"(a[3]), "r"(blo), "n"(BO), "n"(BH));
}
template<uint32_t BO, uint32_t BH> __device__ __forceinline__ void mma32_rs0(float (&d)[16], const uint32_t* a, uint32_t blo) {
  asm volatile("{\n.reg .pred p;\n.reg .b32 ta, tb;\n.reg .b64 da, db;\nadd.u32 tb, %20, %21;\nmov.b64 db, {tb, %22};\nsetp.ne.b32 p, 0, 0;\n"
    "wgmma.mma_async.sync.aligned.m64n32k16.f32.bf16.bf16 {%0, %1, %2, %3, %4, %5, %6, %7, %8, %9, %10, %11, %12, %13, %14, %15}, {%16,%17,%18,%19}, db, p, 1, 1, 1;\n}\n"
    : "=f"(d[0]), "=f"(d[1]), "=f"(d[2]), "=f"(d[3]), "=f"(d[4]), "=f"(d[5]), "=f"(d[6]), "=f"(d[7]), "=f"(d[8]), "=f"(d[9]), "=f"(d[10]), "=f"(d[11]), "=f"(d[12]), "=f"(d[13]), "=f"(d[14]), "=f"(d[15])
    : "r"(a[0]), "r"(a[1]), "r"(a[2]), "r"(a[3]), "r"(blo), "n"(BO), "n"(BH));
}
template<uint32_t BO, uint32_t BH> __device__ __forceinline__ void mma40_rs(float (&d)[20], const uint32_t* a, uint32_t blo) {
  asm volatile("{\n.reg .pred p;\n.reg .b32 ta, tb;\n.reg .b64 da, db;\nadd.u32 tb, %24, %25;\nmov.b64 db, {tb, %26};\nsetp.ne.b32 p, 1, 0;\n"
    "wgmma.mma_async.sync.aligned.m64n40k16.f32.bf16.bf16 {%0, %1, %2, %3, %4, %5, %6, %7, %8, %9, %10, %11, %12, %13, %14, %15, %16, %17, %18, %19}, {%20,%21,%22,%23}, db, p, 1, 1, 1;\n}\n"
    : "+f"(d[0]), "+f"(d[1]), "+f"(d[2]), "+f"(d[3]), "+f"(d[4]), "+f"(d[5]), "+f"(d[6]), "+f"(d[7]), "+f"(d[8]), "+f"(d[9]), "+f"(d[10]), "+f"(d[11]), "+f"(d[12]), "+f"(d[13]), "+f"(d[14]), "+f"(d[15]), "+f"(d[16]), "+f"(d[17]), "+f"(d[18]), "+f"(d[19])
    : "r"(a[0]), "r"(a[1]), "r"(a[2]), "r"(a[3]), "r"(blo), "n"(BO), "n"(BH));
}
template<uint32_t BO, uint32_t BH> __device__ __forceinline__ void mma40_rs0(float (&d)[20], const uint32_t* a, uint32_t blo) {
  asm volatile("{\n.reg .pred p;\n.reg .b32 ta, tb;\n.reg .b64 da, db;\nadd.u32 tb, %24, %25;\nmov.b64 db, {tb, %26};\nsetp.ne.b32 p, 0, 0;\n"
    "wgmma.mma_async.sync.aligned.m64n40k16.f32.bf16.bf16 {%0, %1, %2, %3, %4, %5, %6, %7, %8, %9, %10, %11, %12, %13, %14, %15, %16, %17, %18, %19}, {%20,%21,%22,%23}, db, p, 1, 1, 1;\n}\n"
    : "=f"(d[0]), "=f"(d[1]), "=f"(d[2]), "=f"(d[3]), "=f"(d[4]), "=f"(d[5]), "=f"(d[6]), "=f"(d[7]), "=f"(d[8]), "=f"(d[9]), "=f"(d[10]), "=f"(d[11]), "=f"(d[12]), "=f"(d[13]), "=f"(d[14]), "=f"(d[15]), "=f"(d[16]), "=f"(d[17]), "=f"(d[18]), "=f"(d[19])
    : "r"(a[0]), "r"(a[1]), "r"(a[2]), "r"(a[3]), "r"(blo), "n"(BO), "n"(BH));
}
template<uint32_t AO, uint32_t AH, uint32_t BO, uint32_t BH> __device__ __forceinline__ void mma40_tt(float (&d)[20], uint32_t alo, uint32_t blo) {
  asm volatile("{\n.reg .pred p;\n.reg .b32 ta, tb;\n.reg .b64 da, db;\nadd.u32 ta, %20, %21;\nmov.b64 da, {ta, %22};\nadd.u32 tb, %23, %24;\nmov.b64 db, {tb, %25};\nsetp.ne.b32 p, 1, 0;\n"
    "wgmma.mma_async.sync.aligned.m64n40k16.f32.bf16.bf16 {%0, %1, %2, %3, %4, %5, %6, %7, %8, %9, %10, %11, %12, %13, %14, %15, %16, %17, %18, %19}, da, db, p, 1, 1, 1, 1;\n}\n"
    : "+f"(d[0]), "+f"(d[1]), "+f"(d[2]), "+f"(d[3]), "+f"(d[4]), "+f"(d[5]), "+f"(d[6]), "+f"(d[7]), "+f"(d[8]), "+f"(d[9]), "+f"(d[10]), "+f"(d[11]), "+f"(d[12]), "+f"(d[13]), "+f"(d[14]), "+f"(d[15]), "+f"(d[16]), "+f"(d[17]), "+f"(d[18]), "+f"(d[19])
    : "r"(alo), "n"(AO), "n"(AH), "r"(blo), "n"(BO), "n"(BH));
}
template<uint32_t AO, uint32_t AH, uint32_t BO, uint32_t BH> __device__ __forceinline__ void mma40_tt0(float (&d)[20], uint32_t alo, uint32_t blo) {
  asm volatile("{\n.reg .pred p;\n.reg .b32 ta, tb;\n.reg .b64 da, db;\nadd.u32 ta, %20, %21;\nmov.b64 da, {ta, %22};\nadd.u32 tb, %23, %24;\nmov.b64 db, {tb, %25};\nsetp.ne.b32 p, 0, 0;\n"
    "wgmma.mma_async.sync.aligned.m64n40k16.f32.bf16.bf16 {%0, %1, %2, %3, %4, %5, %6, %7, %8, %9, %10, %11, %12, %13, %14, %15, %16, %17, %18, %19}, da, db, p, 1, 1, 1, 1;\n}\n"
    : "=f"(d[0]), "=f"(d[1]), "=f"(d[2]), "=f"(d[3]), "=f"(d[4]), "=f"(d[5]), "=f"(d[6]), "=f"(d[7]), "=f"(d[8]), "=f"(d[9]), "=f"(d[10]), "=f"(d[11]), "=f"(d[12]), "=f"(d[13]), "=f"(d[14]), "=f"(d[15]), "=f"(d[16]), "=f"(d[17]), "=f"(d[18]), "=f"(d[19])
    : "r"(alo), "n"(AO), "n"(AH), "r"(blo), "n"(BO), "n"(BH));
}
template<uint32_t AO, uint32_t AH, uint32_t BO, uint32_t BH> __device__ __forceinline__ void mma8_tn(float (&d)[4], uint32_t alo, uint32_t blo) {
  asm volatile("{\n.reg .pred p;\n.reg .b32 ta, tb;\n.reg .b64 da, db;\nadd.u32 ta, %4, %5;\nmov.b64 da, {ta, %6};\nadd.u32 tb, %7, %8;\nmov.b64 db, {tb, %9};\nsetp.ne.b32 p, 1, 0;\n"
    "wgmma.mma_async.sync.aligned.m64n8k16.f32.bf16.bf16 {%0, %1, %2, %3}, da, db, p, 1, 1, 1, 0;\n}\n"
    : "+f"(d[0]), "+f"(d[1]), "+f"(d[2]), "+f"(d[3])
    : "r"(alo), "n"(AO), "n"(AH), "r"(blo), "n"(BO), "n"(BH));
}
template<uint32_t AO, uint32_t AH, uint32_t BO, uint32_t BH> __device__ __forceinline__ void mma8_tn0(float (&d)[4], uint32_t alo, uint32_t blo) {
  asm volatile("{\n.reg .pred p;\n.reg .b32 ta, tb;\n.reg .b64 da, db;\nadd.u32 ta, %4, %5;\nmov.b64 da, {ta, %6};\nadd.u32 tb, %7, %8;\nmov.b64 db, {tb, %9};\nsetp.ne.b32 p, 0, 0;\n"
    "wgmma.mma_async.sync.aligned.m64n8k16.f32.bf16.bf16 {%0, %1, %2, %3}, da, db, p, 1, 1, 1, 0;\n}\n"
    : "=f"(d[0]), "=f"(d[1]), "=f"(d[2]), "=f"(d[3])
    : "r"(alo), "n"(AO), "n"(AH), "r"(blo), "n"(BO), "n"(BH));
}
template<uint32_t AO, uint32_t AH, uint32_t BO, uint32_t BH> __device__ __forceinline__ void mma128_ss(float (&d)[64], uint32_t alo, uint32_t blo) {
  asm volatile("{\n.reg .pred p;\n.reg .b32 ta, tb;\n.reg .b64 da, db;\nadd.u32 ta, %64, %65;\nmov.b64 da, {ta, %66};\nadd.u32 tb, %67, %68;\nmov.b64 db, {tb, %69};\nsetp.ne.b32 p, 1, 0;\n"
    "wgmma.mma_async.sync.aligned.m64n128k16.f32.bf16.bf16 {%0, %1, %2, %3, %4, %5, %6, %7, %8, %9, %10, %11, %12, %13, %14, %15, %16, %17, %18, %19, %20, %21, %22, %23, %24, %25, %26, %27, %28, %29, %30, %31, %32, %33, %34, %35, %36, %37, %38, %39, %40, %41, %42, %43, %44, %45, %46, %47, %48, %49, %50, %51, %52, %53, %54, %55, %56, %57, %58, %59, %60, %61, %62, %63}, da, db, p, 1, 1, 0, 1;\n}\n"
    : "+f"(d[0]), "+f"(d[1]), "+f"(d[2]), "+f"(d[3]), "+f"(d[4]), "+f"(d[5]), "+f"(d[6]), "+f"(d[7]), "+f"(d[8]), "+f"(d[9]), "+f"(d[10]), "+f"(d[11]), "+f"(d[12]), "+f"(d[13]), "+f"(d[14]), "+f"(d[15]), "+f"(d[16]), "+f"(d[17]), "+f"(d[18]), "+f"(d[19]), "+f"(d[20]), "+f"(d[21]), "+f"(d[22]), "+f"(d[23]), "+f"(d[24]), "+f"(d[25]), "+f"(d[26]), "+f"(d[27]), "+f"(d[28]), "+f"(d[29]), "+f"(d[30]), "+f"(d[31]), "+f"(d[32]), "+f"(d[33]), "+f"(d[34]), "+f"(d[35]), "+f"(d[36]), "+f"(d[37]), "+f"(d[38]), "+f"(d[39]), "+f"(d[40]), "+f"(d[41]), "+f"(d[42]), "+f"(d[43]), "+f"(d[44]), "+f"(d[45]), "+f"(d[46]), "+f"(d[47]), "+f"(d[48]), "+f"(d[49]), "+f"(d[50]), "+f"(d[51]), "+f"(d[52]), "+f"(d[53]), "+f"(d[54]), "+f"(d[55]), "+f"(d[56]), "+f"(d[57]), "+f"(d[58]), "+f"(d[59]), "+f"(d[60]), "+f"(d[61]), "+f"(d[62]), "+f"(d[63])
    : "r"(alo), "n"(AO), "n"(AH), "r"(blo), "n"(BO), "n"(BH));
}
template<uint32_t AO, uint32_t AH, uint32_t BO, uint32_t BH> __device__ __forceinline__ void mma128_ss0(float (&d)[64], uint32_t alo, uint32_t blo) {
  asm volatile("{\n.reg .pred p;\n.reg .b32 ta, tb;\n.reg .b64 da, db;\nadd.u32 ta, %64, %65;\nmov.b64 da, {ta, %66};\nadd.u32 tb, %67, %68;\nmov.b64 db, {tb, %69};\nsetp.ne.b32 p, 0, 0;\n"
    "wgmma.mma_async.sync.aligned.m64n128k16.f32.bf16.bf16 {%0, %1, %2, %3, %4, %5, %6, %7, %8, %9, %10, %11, %12, %13, %14, %15, %16, %17, %18, %19, %20, %21, %22, %23, %24, %25, %26, %27, %28, %29, %30, %31, %32, %33, %34, %35, %36, %37, %38, %39, %40, %41, %42, %43, %44, %45, %46, %47, %48, %49, %50, %51, %52, %53, %54, %55, %56, %57, %58, %59, %60, %61, %62, %63}, da, db, p, 1, 1, 0, 1;\n}\n"
    : "=f"(d[0]), "=f"(d[1]), "=f"(d[2]), "=f"(d[3]), "=f"(d[4]), "=f"(d[5]), "=f"(d[6]), "=f"(d[7]), "=f"(d[8]), "=f"(d[9]), "=f"(d[10]), "=f"(d[11]), "=f"(d[12]), "=f"(d[13]), "=f"(d[14]), "=f"(d[15]), "=f"(d[16]), "=f"(d[17]), "=f"(d[18]), "=f"(d[19]), "=f"(d[20]), "=f"(d[21]), "=f"(d[22]), "=f"(d[23]), "=f"(d[24]), "=f"(d[25]), "=f"(d[26]), "=f"(d[27]), "=f"(d[28]), "=f"(d[29]), "=f"(d[30]), "=f"(d[31]), "=f"(d[32]), "=f"(d[33]), "=f"(d[34]), "=f"(d[35]), "=f"(d[36]), "=f"(d[37]), "=f"(d[38]), "=f"(d[39]), "=f"(d[40]), "=f"(d[41]), "=f"(d[42]), "=f"(d[43]), "=f"(d[44]), "=f"(d[45]), "=f"(d[46]), "=f"(d[47]), "=f"(d[48]), "=f"(d[49]), "=f"(d[50]), "=f"(d[51]), "=f"(d[52]), "=f"(d[53]), "=f"(d[54]), "=f"(d[55]), "=f"(d[56]), "=f"(d[57]), "=f"(d[58]), "=f"(d[59]), "=f"(d[60]), "=f"(d[61]), "=f"(d[62]), "=f"(d[63])
    : "r"(alo), "n"(AO), "n"(AH), "r"(blo), "n"(BO), "n"(BH));
}

#define XD 600
#define XSTEP 300
#define XPD 450
#define XPB 8192
#define SPG 5600
#define WL0 1800
#define WLS 350
#define NB0 2
#define WP1 2000
#define PF_START 5600
#define PFP 126
#define GPERM 0x76543210u
#define FMODE 2
#define NM0 3
#define PWAIT 600
#define AWAKE 3
#define O1H 2
#define NG1 8
#define OFEN 1
#define X1E 0
#define WDW 3
#define WDGAP 300
#define YWAIT 500
#define OUTW 0
#define CWAIT 500
#define NDF 8
#define O0ALL 0
#define O1ALL 0
#define RDV 1
#define MSTEP 1200
#define MSLP 1000
#define MPOLL 3200
#define LMP 8
#define WD0 10
#define CLR0 22000
#define UPGAP 200
#define OUTGAP 150
#define MPROMO P128
#define MLOAD tma_load_ef
struct Ptrs { const bf16 *x, *wmod, *c, *wr, *wqkv; int by_sm; Scratch* s; const bf16 *wg, *wu, *wd, *wo; bf16* out; uint16_t role[132]; };

#define BAR(i) (sb + OFF_BAR + 8u * (i))

__device__ __forceinline__ uint32_t get_tag(uint32_t sb) { mbar_wait(BAR(B_TAG), 0); const uint32_t d = __shfl_sync(0xffffffffu, lds32(sb + OFF_CST + 32), 0); return d + 1 + (d & 2); }
__device__ __forceinline__ int d_kb(int n, int hg) {
    if (n < 2) return 2 * hg + n;
    const int h = n >= 9, q = n - 2 - 7 * h;
    return 2 * (q + (q >= hg)) + h;
}

__global__ void __launch_bounds__(NTHREADS, 1)
fused_kernel(const Ptrs p, const __grid_constant__ CUtensorMap tmM, const __grid_constant__ CUtensorMap tmX, const __grid_constant__ CUtensorMap tmW,
             const __grid_constant__ CUtensorMap tmWo, const __grid_constant__ CUtensorMap tmPhi, const __grid_constant__ CUtensorMap tmG,
             const __grid_constant__ CUtensorMap tmU, const __grid_constant__ CUtensorMap tmD, const __grid_constant__ CUtensorMap tmO)
{
    extern __shared__ __align__(1024) uint8_t smem_raw[];
    const uint32_t sb = smem_u32(smem_raw);
    const uint32_t cstart = __shfl_sync(0xffffffffu, clk32(), 0);
    const int tid = threadIdx.x, lane = tid & 31, warp = __shfl_sync(0xffffffffu, tid >> 5, 0);
    if (blockIdx.x < 128) {
        if (warp == 8) asm volatile("prefetch.global.L2 [%0];" :: "l"(p.wmod + (size_t)(blockIdx.x * 8 + (lane >> 2)) * 6144 + (lane & 1) * 64 + (lane & 2) * 512));
        if (warp == 13 && (lane & 1) < NM0 - 2) asm volatile("prefetch.global.L2 [%0];" :: "l"(p.wmod + (size_t)(blockIdx.x * 8 + (lane >> 2)) * 6144 + 128 + (lane & 1) * 64 + (lane & 2) * 512));
        if (warp == 12) l2_prefetch(p.wqkv + (size_t)blockIdx.x * 1536, 3072);
        if (warp == 9) { spin_until(cstart + XPD); l2_prefetch(p.x + (size_t)blockIdx.x * 16384, XPB); }
    }
    if (warp == 10) { tmap_prefetch(&tmM); tmap_prefetch(&tmX); tmap_prefetch(&tmW); }
    if (warp == 11) asm volatile("prefetch.global.L2 [%0];" :: "l"((lane < 16 ? p.c : p.wr) + (lane & 15) * 64));
    #pragma unroll
    for (int i = 0; i < 5; i++) e_init(BAR(5 * warp + i), warp < 5 ? 1 : warp < 7 ? 2 : warp < 9 ? 4 : 8);
    mbar_init_fence();
    if (warp == B_TAG / 5) { e_arrive_tx(BAR(B_TAG), 16); bulk_load(sb + OFF_CST + 32, p.s->done, 16, BAR(B_TAG)); }
    uint32_t role;
    asm("mov.u32 %0, %%smid;" : "=r"(role));
    role = p.role[p.by_sm ? role : blockIdx.x];
    const int b = role & 255;
    if (b >= 128 && warp == 0) {
        #pragma unroll
        for (int i = 0; i < 2; i++) { e_arrive_tx(BAR(i), 32768); MLOAD(sb + i * 32768u, &tmM, (b & 1) * 1024, (b & 2) * 256 + i * 256, BAR(i)); }
    }
    __syncthreads();

    if (b >= 128) {
        const int sp = b & 3;
        if (warp == 8) {
            #pragma unroll 1
            for (int j = 2, st = 2, ph = 1; j < 64; j++) {
                if (j == 2 * NM0) spin_until(cstart + SPG);
                mbar_wait(BAR(B_EA + st), ph);
                e_arrive_tx(BAR(st), 32768);
                MLOAD(sb + st * 32768u, &tmM, j < 32 ? (sp & 1) * 1024 + (j >> 1) * 64 : 2560 + sp * 512 + (j >> 2) * 64, (j < 32 ? (sp & 2) + (j & 1) : j & 3) * 256, BAR(st));
                if (++st == 6) { st = 0; ph ^= 1; }
            }
        } else if (warp < 8) {
            const int g = lane >> 2, c = lane & 3;
            {
                const bf16* cp = p.c + (tid >> 3) * 32 + (tid & 1) * 16 + (tid & 6);
                const uint32_t c0 = ldg32(cp), c1 = ldg32(cp + 8);
                stg_zero(p.s->llm1 + (tid >> 4) * 64 + sp * 16 + (tid & 15));
                if (tid < 128) stg_zero(p.s->llmod2 + sp * 128 + tid);
                sts64(sb + 200704u + tid * 8, silu2(c0), silu2(c1));
                bar_sync(1, 256);
                TR(57);
            }
            const uint32_t tag = get_tag(sb);
            const uint32_t wa = sb + (warp * 32 + (lane & 7) + (lane >> 4) * 8) * 128u + ((((lane >> 3) & 1) ^ (lane & 7)) << 4);
            float m[4][4];
            #pragma unroll
            for (int i = 0; i < 4; i++) m[i][0] = m[i][1] = m[i][2] = m[i][3] = 0.f;
            #pragma unroll 1
            for (int r = 0, st = 0, ph = 0; r < 32; r++) {
                const int n = r < 16 ? r : (r >> 1) + 8;
                const bf16* wr = p.wr + (sp & 1) * 512 + (n & 7) * 64 + (g & 3) * 16 + 2 * c;
                const uint32_t wr0 = ldg32(wr), wr1 = ldg32(wr + 8);
                const uint32_t sa = sb + 200704u + ((r < 16 ? sp >> 1 : r & 1) * 16 + warp) * 64 + c * 16;
                const uint4 sv0 = lds128(sa), sv1 = lds128(sa + 512);
                uint32_t f[16][4];
                #pragma unroll
                for (int q = 0; q < 2; q++) {
                    mbar_wait(BAR(st + q), ph);
                    if (r == 0 && warp == 0) TR(60 + q);
                    #pragma unroll
                    for (int i = 0; i < 8; i++) ldsm4t(f[8 * q + i], (wa + (st + q) * 32768u + (i >> 2) * 2048u) ^ ((i & 3) << 5));
                }
                #pragma unroll
                for (int i = 0; i < 16; i++) {
                    const uint4& sv = i < 8 ? sv0 : sv1;
                    mma16816(m[i & 3], f[i][0], f[i][1], f[i][2], f[i][3], (i & 4) ? sv.z : sv.x, (i & 4) ? sv.w : sv.y);
                    if ((i & 7) == 7) e_arrive(BAR(B_EA + st + (i >> 3)));
                }
                st += 2; if (st == 6) { st = 0; ph ^= 1; }
                if (r >= 16 && !(r & 1)) continue;
                const uint32_t red = sb + 196608u + (n & 1) * 2048u;
                const uint32_t a = red + warp * 256u + (c * 16 + (g >> 1) * 4 + (g & 1)) * 4u;
                stsf(a, sel4(c, m[0][0], m[1][0], m[2][0], m[3][0])); stsf(a + 8, sel4(c, m[0][2], m[1][2], m[2][2], m[3][2]));
                #pragma unroll
                for (int i = 0; i < 4; i++) m[i][0] = m[i][1] = m[i][2] = m[i][3] = 0.f;
                bar_sync(1, 256);
                if (warp == (n & 7)) {
                    const uint32_t ra = red + (lane >> 4) * 1024u + (lane & 15) * 16u;
                    const uint4 r0 = lds128(ra), r1 = lds128(ra + 256), r2 = lds128(ra + 512), r3 = lds128(ra + 768);
                    #define F4(f) ((u2f(r0.f) + u2f(r1.f)) + (u2f(r2.f) + u2f(r3.f)))
                    float x = F4(x), y = F4(y), z = F4(z), w = F4(w);
                    #undef F4
                    x += shfl_x(x, 16); y += shfl_x(y, 16); z += shfl_x(z, 16); w += shfl_x(w, 16);
                    if (n < 16) {
                        if (lane < 16) st_ll4(p.s->llm1 + n * 64 + sp * 16 + lane, x, y, z, w, tag);
                    } else {
                        uint32_t lo = pack2(x, y), hi2 = pack2(z, w);
                        float d = fmaf(bf_lo(lo), bf_lo(wr0), bf_hi(lo) * bf_hi(wr0)) + fmaf(bf_lo(hi2), bf_lo(wr1), bf_hi(hi2) * bf_hi(wr1));
                        if (sp >= 2) {
                            lo = hadd2(lo, ONE2); hi2 = hadd2(hi2, ONE2);
                            const uint32_t r0 = hmul2(lo, wr0), r1 = hmul2(hi2, wr1);
                            d = (bf_lo(r0) + bf_hi(r0)) + (bf_lo(r1) + bf_hi(r1));
                        }
                        #pragma unroll 1
                        for (int k = 1; k < 16; k <<= 1) d += shfl_x(d, k);
                        if (lane < 16) st_ll(p.s->llmod2 + sp * 128 + (n & 7) * 16 + lane, lo, hi2, f2u(d), tag);
                    }
                    TR(n);
                }
            }
        }
    } else if (warp >= 12) {
        reg_dec<24>();
        const int rb = b >> 3, hg = b & 7, fs = role >> 8;
        const bool ffn = fs < 112;
        if (warp == 12) {
            #pragma unroll 1
            for (int j = 0, s = 0, ph = 1; j < 16; j++) {
                if (j < 2) mbar_wait(j ? BAR(B_STS) : BAR(B_STP), 0);
                mbar_wait(BAR(B_EA + s), ph);
                e_arrive_tx(BAR(B_FA + s), 16384); tma_load(sb + OFF_A + s * 16384u, &tmX, j * 64, rb * 128, BAR(B_FA + s));
                if (j == 0) TS(2);
                if (j == 1) GT(0);
                if (j == 6) GT(1);
                if (j == 11) GT(2);
                if (++s == 3) { s = 0; ph ^= 1; }
            }
            tmap_prefetch(&tmO);
            const uint32_t tag = get_tag(sb);
            e_arrive(BAR(B_FD)); e_arrive(BAR(B_FD + 1));
            const uint4* osrc = pin_ptr(p.s->os + (size_t)rb * 16 * 1024);
            #pragma unroll 1
            for (int q = 0; q < 3; q++) {
                mbar_wait(q < 2 ? BAR(B_KST + 1 + 2 * q) : BAR(B_OWN), 0);
                poll_flags(q < 2 ? p.s->flk + (q + 1) * 256 + (hg * 16 + (lane & 15)) * 2 : p.s->flo + (O0ALL ? (rb & 12) * 16 + lane * 2 : rb * 16 + (lane & 7) * 2) * 2, tag);
                if (q == 2) break;
                e_arrive_tx(BAR(B_KVL + q), 16896); bulk_load(sb + (q ? OFF_PHI : OFF_KL), p.s->kvacc + hg * 2112 + q * 1056, 16896, BAR(B_KVL + q));
                TS(12 + q);
                if (!q) GT(4);
            }
            if (O1H == 1) e_arrive(BAR(B_UD));
            TS(3); GT(5);
            #pragma unroll
            for (int n = 2; n < 6; n++) {
                if (n >= 4) mbar_wait(BAR(B_ED + (n & 3)), 0); else mbar_wait(BAR(B_GE + (4 * n <= NG1 ? 1 : 2)), 0);
                e_arrive_tx(BAR(B_FD + (n & 3)), 16384);
                bulk_load(sb + (n == 5 ? OFF_X1 : OFF_R0 + (n & 3) * 16384u), osrc + (n - 2 >= hg ? n - 1 : n - 2) * 2048, 16384, BAR(B_FD + (n & 3)));
                TR(32 + n);
            }
            #pragma unroll 1
            for (int n = 6; n < 16; n++) {
                const uint32_t s = n & 3, fb = BAR(B_FD + s);
                const uint4* src = osrc + d_kb(n, hg) * 1024;
                if (n == 9) mbar_wait(BAR(B_O1), 0);
                mbar_wait(BAR(B_ED + s), ((n >> 2) - 1) & 1);
                e_arrive_tx(fb, 16384);
                bulk_load(sb + OFF_R0 + s * 16384u, src, 16384, fb);
                TR(32 + n);
            }
            e_arrive_tx(BAR(B_WPHI), 32768);
            if (X1E) tma_load(sb + OFF_X1, &tmX, hg * 128 + 64, rb * 128, BAR(B_WPHI));
            mbar_wait(BAR(B_ED), 1);
            tma_load(sb + OFF_R0, &tmX, hg * 128, rb * 128, BAR(B_WPHI));
            if (!X1E) tma_load(sb + OFF_X1, &tmX, hg * 128 + 64, rb * 128, BAR(B_WPHI));
            GT(6);
            mbar_wait(BAR(B_CAND), 0);
            GT(7);
            const uint2 lc = lds64(sb + OFF_CST + 16);
            const uint32_t w0 = __shfl_sync(0xffffffffu, lc.x >> 4, 0), w1 = __shfl_sync(0xffffffffu, lc.y >> 4, 0);
            mbar_wait(BAR(B_SWP), 0);
            fence_async_smem();
            if (OUTW) mbar_wait(BAR(B_SEL), 0);
            #pragma unroll 1
            for (uint32_t w = 0; w < 8; w++)
                if (w != w0 && w != w1) { tma_store4(&tmO, rb * 128 + w * 16, hg * 2, sb + OFF_OUT + w * 4096u); spin_until(clk32() + OUTGAP); }
            mbar_wait(BAR(B_SEL), 0);
            const uint2 sel = lds64(sb + OFF_CST + 24);
            #pragma unroll 1
            for (uint32_t i = 0; i < (w0 == w1 ? 8u : 16u); i++) {
                const uint32_t w = i < 8 ? w0 : w1, r = (i & 7) * 2 + (lane >> 4), row = rb * 128 + w * 16 + r;
                const uint4 o = lds128(sb + OFF_OUT + w * 4096u + ((lane >> 3) & 1) * 2048u + r * 128u + (((lane ^ r) & 7) << 4));
                if (row != (~sel.x & 2047u) && row != (~sel.y & 2047u)) stg128(p.out + (size_t)row * 1024 + hg * 128 + (lane & 15) * 8, o);
            }
            bulk_wait_read();
        } else if (warp == 14) {
            const uint32_t fb = ffn ? 65536 : 0;
            e_arrive_tx(BAR(B_GF), fb); e_arrive_tx(BAR(B_UD), fb); e_arrive_tx(BAR(B_UF), fb); e_arrive_tx(BAR(B_WD), fb);
            uint32_t due = cstart + WP1;
            #pragma unroll 1
            for (int i = -2; i < 26; i++) {
                if (i >= 0) {
                    const bf16* a = i < 8 ? p.wg + (size_t)(i * 128 + b) * 3584 : i < 16 ? p.wu + (size_t)((i - 8) * 128 + b) * 3584
                                  : i < 18 ? p.wo + (size_t)(b * 2 + i - 16) * 4096 : p.wd + (size_t)(b * 8 + i - 18) * 3584;
                    sleep_until(due);
                    l2_prefetch(a, (i >> 1) == 8 ? 8192 : 7168);
                    due += 7 * PFP;
                }
                if (i == 1) { tmap_prefetch(&tmPhi); tmap_prefetch(&tmG); tmap_prefetch(&tmWo); tmap_prefetch(&tmU); tmap_prefetch(&tmD); mbar_wait(BAR(B_STS), 0); }
                if (ffn && (uint32_t)(i - 3) < 8u) tma_load_ef(sb + OFF_R0 + (i - 3) * 8192u, &tmG, fs * 32, (i - 3) * 128, BAR(B_GF));
                if (ffn && (uint32_t)(i - 11) < 8u) tma_load(sb + OFF_WPHI, &tmU, fs * 32, (i - 11) * 128, BAR(B_UD));
                if (i == 19) { mbar_wait(BAR(B_UD), 0); e_arrive_tx(BAR(B_WPHI), 8192); tma_load(sb + OFF_WPHI, &tmPhi, 0, hg * 128, BAR(B_WPHI)); }
                if (i == LMP + 2 * (b & 3) + (b >> 6)) tma_prefetch(&tmM, 2048 + (b >> 6) * 2048 + (b >> 2) * 64, (b & 3) * 256);
                if (i < 13) {
                    sleep_until(due);
                    l2_prefetch(p.wqkv + (size_t)((i + 3) * 128 + b) * 1536, 3072);
                    due += i == -2 ? PF_START - WP1 : 3 * PFP;
                }
            }
            if (lane < 4) stg_zero(p.s->flo + b * 4 + lane);
            const uint32_t tag = get_tag(sb);
            #pragma unroll 1
            for (int q = 0; q < 2; q++) {
                mbar_wait(BAR(B_OWN + q), 0);
                if (q && O1H == 1) mbar_wait(BAR(B_UD), 1); else if (q && O1H) mbar_wait(BAR(B_FD + O1H), 0);
                bulk_store(p.s->os + ((size_t)b * 2 + q) * 1024, sb + OFF_R0 + q * 16384u, 16384);
                bulk_wait();
                if (OFEN) fence_gpu();
                __syncwarp();
                st_flag(p.s->flo + (b * 2 + q) * 2, tag, lane);
                TS(7 + q);
            }
            e_arrive(BAR(B_OST));
        } else {
            uint4* fk = p.s->flk + (hg * 16 + rb) * 2;
            if (warp == 13) {
                #pragma unroll 1
                for (int i = 0; i < 32; i++) {
                    const uint32_t s = i & 3;
                    if (i < NB0) spin_until(cstart + WL0 + WLS * i); else if (i == NB0) mbar_wait(BAR(B_STS), 0);
                    mbar_wait(BAR(B_EB + s), ((i >> 2) - 1) & 1);
                    e_arrive_tx(BAR(B_FB + s), 24576); tma_load4(sb + OFF_B + s * 24576u, &tmW, i * 32, hg * 2, BAR(B_FB + s));
                    TR(64 + i);
                }
                mbar_wait(BAR(B_EB), 1); mbar_wait(BAR(B_EB + 1), 1);
                e_arrive_tx(BAR(B_LMF), 32768); tma_load_ef(sb + OFF_B, &tmM, 2048 + (b >> 6) * 2048 + (b >> 2) * 64, (b & 3) * 256, BAR(B_LMF));
                mbar_wait(BAR(B_LMD), 0);
                #pragma unroll 1
                for (int n = 0; n < 4; n++) {
                    e_arrive_tx(BAR(B_FD + n), 16384); tma_load4(sb + OFF_DB + n * 16384u, &tmWo, d_kb(n, hg) * 64, hg * 2, BAR(B_FD + n));
                }
            } else {
                sleep_until(cstart + CLR0);
                const uint32_t tag = get_tag(sb);
                #pragma unroll 1
                for (int i = lane; i < 132; i += 32) stg_zero(p.s->kvacc + hg * 2112 + rb * 132 + i);
                if (lane < 4) stg_zero(fk + 256 + (lane >> 1) * 256 + (lane & 1));
                fence_gpu();
                __syncwarp();
                st_flag(fk, tag, lane);
                sleep_until(clk32() + 2000);
                poll_flags(p.s->flk + (hg * 16 + (lane & 15)) * 2, tag);
                mbar_wait(BAR(B_QE), 0);
                #pragma unroll 1
                for (int i = 0; i < 4; i++) {
                    stg_zero(p.s->llln2 + b * 128 + i * 32 + lane);
                    stg_zero(p.s->llrowh + (i >> 1) * 8192 + (rb * 2 + (i & 1)) * 256 + hg * 32 + lane);
                    #pragma unroll
                    for (int k = 0; k < 4; k++) stg_zero(p.s->lly + (fs & 127) * 512 + i * 128 + k * 32 + lane);
                }
                if (lane < 2 && hg == (rb & 7)) stg_zero(p.s->llcand + rb * 2 + lane);
                __syncwarp();
                e_arrive(BAR(B_KZ));
            }
            const int q = warp == 13;
            const uint32_t tag = get_tag(sb);
            mbar_wait(BAR(B_KZ), 0);
            #pragma unroll 1
            for (int h = 2 * q; h < 2 * q + 2; h++) {
                mbar_wait(BAR(B_KST + h), 0);
                uint4* acc = p.s->kvacc + (hg * 4 + h) * 528;
                bulk_reduce(acc, sb + OFF_V + h * 8192u, 8192); bulk_reduce(acc + 512, sb + OFF_ZS + h * 256u, 256);
            }
            bulk_wait();
            if (q) e_arrive(BAR(B_KZ));
            TR(158 + q);
            fence_gpu();
            __syncwarp();
            st_flag(fk + 256 + q * 256, tag, lane);
            TS(10 + q);
            if (q) {
                #pragma unroll 1
                for (int n = 4; n < 16; n++) {
                    const uint32_t s = n & 3;
                    mbar_wait(BAR(B_ED + s), ((n >> 2) - 1) & 1);
                    e_arrive_tx(BAR(B_FD + s), 16384);
                    tma_load4(sb + OFF_DB + s * 16384u, &tmWo, d_kb(n, hg) * 64, hg * 2, BAR(B_FD + s));
                    TR(96 + n);
                    if (ffn && (uint32_t)(n - WD0) < 4u) {
                        #pragma unroll
                        for (int k = 0; k < 2; k++) tma_load_ef(sb + OFF_F2 + (n - WD0) * 8192u + k * 4096u, &tmD, (n - WD0) * 256 + k * 128, fs * 32, BAR(B_WD));
                    }
                }
                if (ffn) {
                    mbar_wait(BAR(B_ED + WDW), 1);
                    #pragma unroll 1
                    for (int z = 0; z < 8; z++) { tma_load_ef(sb + OFF_DB + z * 4096u, &tmD, z * 128 + 64, fs * 32, BAR(B_WD)); sleep_until(clk32() + WDGAP); }
                }
            } else {
                if (ffn) {
                    mbar_wait(BAR(B_KZ), 1);
                    #pragma unroll 1
                    for (int i = 7; i < 15; i++) {
                        if (i == 12) mbar_wait(BAR(B_KVT + 1), 0);
                        tma_load_ef(sb + OFF_F2 + (i & 7) * 8192u, &tmU, fs * 32, (i & 7) * 128, BAR(B_UF));
                        sleep_until(clk32() + UPGAP);
                    }
                }
                mbar_wait(BAR(B_OST), 0);
                poll_flags(p.s->flo + (O1ALL ? (rb & 12) * 16 + lane * 2 + 1 : rb * 16 + (lane & 7) * 2 + 1) * 2, tag);
                e_arrive(BAR(B_O1));
                TS(4);
            }
        }
    } else if (warp >= 8) {
        reg_dec<24>();
        const int rb = b >> 3, hg = b & 7, w4 = warp & 3, g = lane >> 2, c = lane & 3, t = tid & 127;
        const uint32_t sv = silu2(ldg32(p.c + (b & 3) * 256 + 2 * t)), tag = get_tag(sb);
        if (w4 < 3) {
            spin_until(cstart + MPOLL + MSTEP * w4);
            #pragma unroll 1
            for (int j = w4, ph = 1; j < 16; j += 3, ph ^= 1) {
                uint4 w[2];
                poll_words<2, 0, 3>(w, p.s->llm1 + j * 64 + lane, 32, tag);
                uint32_t lo = pack2(u2f(w[0].x) + u2f(w[1].x), u2f(w[0].y) + u2f(w[1].y)), hi = pack2(u2f(w[0].z) + u2f(w[1].z), u2f(w[0].w) + u2f(w[1].w));
                if (lane >= 16) { lo = hadd2(lo, ONE2); hi = hadd2(hi, ONE2); }
                sts64(sb + OFF_TAB + j * 256 + (lane & 15) * 16 + (lane < 16 ? 8 : 0), lo, hi);
                __syncwarp();
                if (j == 0) TS(5);
                TR(16 + j);
                mbar_wait(BAR(B_EA + w4), ph);
                e_arrive(BAR(B_FA + w4));
                __nanosleep(MSLP);
            }
        }
        mbar_wait(BAR(B_QE), 0);
        if (warp == 8) GT(3);
        sts32(sb + OFF_KL + w4 * 1024u + lane * 4, sv);
        fence_async_smem();
        bar_sync(2, 128);
        reg_inc<56>();
        {
            float m0[4], m1[4];
            const uint32_t da = desc_lo(sb + OFF_B, 16), db = desc_lo(sb + OFF_KL, 16);
            mbar_wait(BAR(B_LMF), 0);
            wg_fence();
            #define LMS(f, i) f<(i) * 256, H128, ((i) >> 1) * 64 + ((i) & 1) * 4, H128>(m0, da, db); f<(i) * 256 + 128, H128, ((i) >> 1) * 64 + ((i) & 1) * 4 + 2, H128>(m1, da, db)
            LMS(mma8_tn0, 0); LMS(mma8_tn, 1); LMS(mma8_tn, 2); LMS(mma8_tn, 3); LMS(mma8_tn, 4); LMS(mma8_tn, 5); LMS(mma8_tn, 6); LMS(mma8_tn, 7);
            #undef LMS
            wg_commit();
            wg_wait<0>();
            acc_fence(m0); acc_fence(m1);
            e_arrive(BAR(B_LMD));
            const float v0 = m0[0] + m1[0], v1 = m0[2] + m1[2], u0 = shfl_x(v0, 4), u1 = shfl_x(v1, 4);
            if (!(lane & 7)) st_ll4(p.s->llg + (b >> 6) * 1024 + (b & 3) * 256 + ((b >> 2) & 15) * 16 + w4 * 4 + (lane >> 3), v0, u0, v1, u1, tag);
            if (warp == 8) TR(150);
        }
        #pragma unroll 1
        for (int h = 0; h < 4; h++) {
            float okv[20];
            const uint32_t vb = OFF_V + h * 8192u, dp = desc_lo(sb + OFF_PHI + (h & 1) * 16384u, 16), dv = desc_lo(sb + vb, OFF_ONES - vb);
            mbar_wait(BAR(B_PF + h), 0);
            fence_async_smem();
            wg_fence();
            #define KVS(i) mma40_tt<(i) * 128, H128, (i) * (64u - (64u << 16)), H64>(okv, dp, dv)
            mma40_tt0<0, H128, 0, H64>(okv, dp, dv); KVS(1); KVS(2); KVS(3); KVS(4); KVS(5); KVS(6); KVS(7);
            #undef KVS
            wg_commit();
            wg_wait<0>();
            acc_fence(okv);
            if (h < 2) e_arrive(BAR(B_PE + h));
            bar_sync(2, 128);
            #pragma unroll
            for (int k = 0; k < 4; k++) sts128(sb + vb + (k * 128 + t) * 16u, make_uint4(f2u(okv[4 * k]), f2u(okv[4 * k + 1]), f2u(okv[4 * k + 2]), f2u(okv[4 * k + 3])));
            if (c == 0) sts64(sb + OFF_ZS + h * 256u + (w4 * 8 + g) * 8u, f2u(okv[16]), f2u(okv[18]));
            fence_async_smem();
            __syncwarp();
            e_arrive(BAR(B_KST + h));
            if (warp == 8) TR(151 + h);
        }
        #pragma unroll 1
        for (int q = 0; q < 2; q++) {
            const uint32_t f = w4 * 16 + g, kl = sb + (q ? OFF_PHI : OFF_KL), ta = sb + (q ? OFF_KL : OFF_KVT) + f * 64u + ((g >> 1) << 4) + 4 * c;
            const uint32_t za = sb + OFF_Z + (f + 8 * (c & 1)) * 64u + (((2 * q) ^ (g >> 1)) << 4) + (c >> 1) * 8;
            mbar_wait(q ? BAR(B_KVT) : BAR(B_STP), q ^ 1);
            mbar_wait(BAR(B_KVL + q), 0);
            uint4 v[8]; float z[2];
            #pragma unroll
            for (int k = 0; k < 8; k++) v[k] = lds128(kl + (k >> 2) * 8448u + (k & 3) * 2048u + t * 16u);
            #pragma unroll
            for (int hh = 0; hh < 2; hh++) z[hh] = ldsf(kl + hh * 8448u + 8192u + (w4 * 8 + g) * 8u + (c & 1) * 4);
            #pragma unroll
            for (int k = 0; k < 8; k++) {
                sts32((ta ^ ((k & 3) << 4)) + (k >> 2) * 4096u, pack2(u2f(v[k].x), u2f(v[k].y))); sts32((ta ^ ((k & 3) << 4)) + (k >> 2) * 4096u + 512, pack2(u2f(v[k].z), u2f(v[k].w)));
            }
            #pragma unroll
            for (int hh = 0; hh < 2; hh++) { const uint32_t zz = pack2(z[hh], z[hh]); sts64(za ^ (hh << 4), zz, zz); }
            fence_async_smem();
            __syncwarp();
            e_arrive(BAR(B_KVT + q));
            if (warp == 8) TR(155 + q);
        }
        reg_dec<24>();
        mbar_wait(BAR(B_O1), 0);
        if (w4 == 0 || w4 == 3) {
            float s[4] = {0.f, 0.f, 0.f, 0.f};
            #pragma unroll 1
            for (int k = 0; k < 2; k++) {
                uint4 w[2];
                poll_words<2, 0, 3>(w, p.s->llg + (w4 & 1) * 1024 + k * 512 + hg * 32 + lane, 256, tag);
                s[0] += u2f(w[0].x) + u2f(w[1].x); s[1] += u2f(w[0].y) + u2f(w[1].y); s[2] += u2f(w[0].z) + u2f(w[1].z); s[3] += u2f(w[0].w) + u2f(w[1].w);
            }
            const uint32_t lo = pack2(s[0], s[1]), hi = pack2(s[2], s[3]);
            sts64(w4 ? sb + OFF_T3 + lane * 8 : sb + OFF_T1 + lane * 16, lo, hi);
            if (!w4) sts64(sb + OFF_T1 + 512 + lane * 16, lo, hi);
        } else {
            const bf16* wr = p.wr + hg * 128 + g * 16 + 2 * c;
            const uint32_t wr0 = ldg32(wr), wr1 = ldg32(wr + 8);
            uint4 w[2];
            poll_words<2, 1>(w, p.s->llmod2 + (w4 - 1) * 256 + hg * 32 + lane, (lane & 15) * 16 - hg * 32 - lane, tag);
            sts64(sb + OFF_T2 + lane * 16 + (w4 & 1) * 8, w[0].x, w[0].y);
            if (w4 == 2) sts64(sb + OFF_T1 + 512 + lane * 16 + 8, hmul2(w[0].x, wr0), hmul2(w[0].y, wr1));
            float d = u2f(w[1].z);
            #pragma unroll 1
            for (int k = 1; k < 16; k <<= 1) d += shfl_x(d, k);
            stsf(sb + OFF_CST + 8 + (w4 & 1) * 4, d);
        }
        __syncwarp();
        e_arrive(BAR(B_PAR));
        if (warp == 9) TS(6);
        if (w4 < 2) {
            mbar_wait(BAR(B_PAR), 0);
            const uint4 ta = lds128(sb + OFF_T2 + lane * 16);
            const uint2 gb = lds64(sb + OFF_T3 + lane * 8);
            uint4* d = pin_ptr(p.s->llrowh + (rb * 2 + w4) * 256 + hg * 32 + lane);
            mbar_wait(BAR(B_KEYS), 0);
            const uint4 kk = lds128(sb + OFF_KEY + lane * 16);
            uint32_t k[4] = {kk.x, kk.y, kk.z, kk.w}, b0, b1;
            top2<4>(k, b0, b1);
            const uint32_t cd = ~(w4 ? b1 : b0) & 127u;
            const uint32_t xa = sb + OFF_R0 + (g >> 2) * (OFF_X1 - OFF_R0) + cd * 128u + ((((g & 3) * 2) ^ (cd & 7)) << 4) + c * 4;
            const uint32_t x0 = lds32(xa), x1 = lds32(xa ^ 16);
            const uint4 st = lds128(sb + OFF_ST2 + cd * 16);
            st_ll(d, lnmod(x0, st.x, st.y, st.z, ta.x, ta.z), lnmod(x1, st.x, st.y, st.z, ta.y, ta.w), gb.x, tag);
            st_ll(d + 8192, x0, x1, gb.y, tag);
            sts32(sb + OFF_CST + 16 + w4 * 4, cd);
            __syncwarp();
            e_arrive(BAR(B_CAND));
            if (warp == 8) TS(9);
        } else if (w4 == 2) {
            uint4* cp = pin_ptr(p.s->llcand + lane);
            mbar_wait(BAR(B_KEYS), 0);
            if (hg == (rb & 7)) {
                const uint4 kk = lds128(sb + OFF_KEY + lane * 16);
                uint32_t k[4] = {kk.x, kk.y, kk.z, kk.w}, b0, b1;
                top2<4>(k, b0, b1);
                if ((lane >> 1) == rb) st_ll(cp, (lane & 1) ? b1 : b0, tag, tag, tag);
            } else spin_until(clk32() + CWAIT);
            uint2 v = make_uint2(0, 0);
            #pragma unroll 1
            for (int it = 0; it < POLL_MAX; it++) {
                if (v.y != tag) asm volatile("ld.relaxed.gpu.global.v2.b32 {%0,%1}, [%2];" : "=r"(v.x), "=r"(v.y) : "l"(cp) : "memory");
                if (__all_sync(0xffffffffu, v.y == tag)) break;
            }
            uint32_t k[1] = {v.x}, b0, b1;
            top2<1>(k, b0, b1);
            sts64(sb + OFF_CST + 24, b0, b1);
            __syncwarp();
            e_arrive(BAR(B_SEL));
        }
    } else {
        reg_inc<232>();
        float a0[96], a1[96];
        {
            const int g = lane >> 2, c = lane & 3;
            uint4* stp = p.s->llstat + b * 16 + warp * 2 + (lane >> 4);
            if (lane == 0 || lane == 18) stg_zero(stp);
            spin_until(cstart + XD + XSTEP * warp);
            e_arrive_tx(BAR(B_XP + warp), 4096);
            bulk_load(sb + OFF_R0 + warp * 4096u, p.x + (size_t)(b * 16 + 2 * warp) * 1024, 4096, BAR(B_XP + warp));
            const uint32_t tag = get_tag(sb);
            if (tid < 64) sts128(sb + OFF_ONES + tid * 16, make_uint4(ONE2, ONE2, ONE2, ONE2));
            if (tid == 64) { sts64(sb + OFF_CST, role, tag); stsf(sb + OFF_CST + 48, -LOG2E); }
            if (AWAKE & 1) mbar_wait_awake(BAR(B_XP + warp), 0); else mbar_wait(BAR(B_XP + warp), 0);
            e_arrive(BAR(B_STP));
            if (warp == 7) TS(14);
            float s[2][4], q0[2][4], q1[2][4];
            #pragma unroll
            for (int i = 0; i < 4; i++) s[0][i] = s[1][i] = q0[0][i] = q0[1][i] = q1[0][i] = q1[1][i] = 0.f;
            uint32_t xa[8][4], xb[8][4];
            const uint32_t la = sb + OFF_R0 + warp * 4096u + (lane & 7) * 16u;
            #pragma unroll
            for (int i = 0; i < 8; i++) {
                ldsm4(xa[i], la + ((lane >> 3) & 1) * 2048u + (lane >> 4) * 128u + i * 256u);
                ldsm4(xb[i], la + ((lane >> 3) & 1) * 128u + (lane >> 4) * 2048u + i * 256u);
            }
            #pragma unroll
            for (int i = 0; i < 8; i++) {
                mma16816(q0[i & 1], xa[i][0], xa[i][1], xa[i][2], xa[i][3], xb[i][0], xb[i][1]);
                mma16816(q1[i & 1], xa[i][0], xa[i][1], xa[i][2], xa[i][3], xb[i][2], xb[i][3]);
                mma16816(s[i & 1], xa[i][0], xa[i][1], xa[i][2], xa[i][3], ONE2, ONE2);
            }
            const float s0 = s[0][0] + s[1][0], s1 = s[0][2] + s[1][2];
            const float sq0 = (g & 1) ? q0[0][1] + q0[1][1] : q0[0][0] + q0[1][0], sq1 = (g & 1) ? q1[0][3] + q1[1][3] : q1[0][2] + q1[1][2];
            const bool up = lane >= 16;
            float sm = (up ? s1 : s0) + shfl_x(up ? s0 : s1, 18), sq = (up ? sq1 : sq0) + shfl_x(up ? sq0 : sq1, 18);
            sm += shfl_x(sm, 9); sq += shfl_x(sq, 9);
            sm += shfl_x(sm, 4); sq += shfl_x(sq, 4);
            uint32_t m2, rh, rl; float rinv;
            ln_final(sm, sq, m2, rinv);
            split_rcp(rinv, rh, rl);
            if (lane == 0 || lane == 18) st_ll(stp, m2, rh, rl, tag);
            if (warp == 7) TS(15);
            uint4 st[2];
            if (PWAIT) { mbar_wait(BAR(B_STP), 0); if (warp < 7) spin_until(clk32() + PWAIT); }
            #pragma unroll 1
            for (int it = 0; it < POLL_MAX; it++) {
                st[0] = ld_ll(p.s->llstat + (b >> 3) * 128 + warp * 16 + g); st[1] = ld_ll(p.s->llstat + (b >> 3) * 128 + warp * 16 + g + 8);
                const uint32_t o = RDV ? ld_rlx(&p.s->llstat[((b >> 5) * 4 + c) * 128 + warp * 16 + 15].w) : tag;
                if (__all_sync(0xffffffffu, !tag_bad(tag_bad(o ^ tag, st[0].w, tag), st[1].w, tag))) break;
                if (AWAKE & 1) it += awake_zero();
            }
            e_arrive(BAR(B_STS));
            if (warp == 0) TS(16);
            const uint32_t lrow = warp * 16 + (lane & 15);
            uint32_t aad = sb + OFF_A + lrow * 128u + (((lane >> 4) ^ (lrow & 7)) << 4);
            uint32_t tad = sb + OFF_TAB + c * 16, ab = BAR(B_FA), pa = 0;
            uint32_t f0[4], f1[4];
            #define PREP(f, q) do { \
                const uint4 t = lds128(tad + (q) * 64); \
                ldsm4(f, aad ^ ((q) << 5)); \
                f[0] = lnmod(f[0], st[0].x, st[0].y, st[0].z, t.x, t.z); f[1] = lnmod(f[1], st[1].x, st[1].y, st[1].z, t.x, t.z); \
                f[2] = lnmod(f[2], st[0].x, st[0].y, st[0].z, t.y, t.w); f[3] = lnmod(f[3], st[1].x, st[1].y, st[1].z, t.y, t.w); } while (0)
            #define MMA(f, off) do { wg_fence(); mma192_rs<(off), H128>(a0, f, blo); mma192_rs<(off) + 768, H128>(a1, f, blo); wg_commit(); wg_wait<1>(); } while (0)
            mbar_wait(ab, 0);
            PREP(f0, 0);
            if (RDV) mbar_wait(BAR(B_STS), 0);
            #pragma unroll 1
            for (int j = 0; j < 16; j++) {
                const uint32_t bb = BAR(B_FB) + (j & 1) * 16, blo = desc_lo(sb + OFF_B, 4096) + (j & 1) * 3072, pb = (j >> 1) & 1;
                mbar_wait(bb, pb);
                wg_fence(); mma192_rsp<0, H128>(a0, f0, blo, j); mma192_rsp<768, H128>(a1, f0, blo, j); wg_commit(); wg_wait<1>();
                if (j) e_arrive((bb ^ 16) + 8 * (B_EB - B_FB) + 8);
                PREP(f1, 1);
                MMA(f1, 128);
                PREP(f0, 2);
                mbar_wait(bb + 8, pb);
                MMA(f0, 1536);
                e_arrive(bb + 8 * (B_EB - B_FB));
                PREP(f1, 3);
                MMA(f1, 1536 + 128);
                e_arrive(ab + 8 * (B_EA - B_FA));
                ab += 8; aad += 16384; tad += 256;
                if (ab == BAR(B_FA + 3)) { ab -= 24; aad -= 49152; pa ^= 1; }
                if (j < 15) mbar_wait(ab, pa);
                PREP(f0, 0);
            }
            #undef PREP
            #undef MMA
        }
        int tid_o; asm volatile("mov.u32 %0, %%tid.x;" : "=r"(tid_o) :: "memory");
        const int tid = tid_o, lane = tid & 31, warp = __shfl_sync(0xffffffffu, tid >> 5, 0), wgi = warp >> 2, g = lane >> 2, c = lane & 3;
        const uint32_t srow = warp * 16 + (lane & 15);
        #define T128(t) (sb + (((t) >> 5) * 16 + ((t) & 15)) * 128u + (((((t) >> 4) & 1) ^ ((t) & 7)) << 4))
        const uint32_t pa = T128(tid);
        mbar_wait(BAR(B_WPHI), 0);
        mbar_wait(BAR(B_EA), 1);
        wg_wait<0>();
        acc_fence(a0); acc_fence(a1);
        e_arrive(BAR(B_QE));
        if (warp == 0) TS(18);
        uint32_t ph0[16], ph1[16], kq[32];
        {
        uint32_t pk[16], mm[4], mn[2];
        float ea[32], eb[32];
        {
            float p0[16], p1[16];
            const uint32_t dw = desc_lo(sb + OFF_WPHI, 16);
            #define PMMA(f, o) do { wg_fence(); mma32_rs0<(o), H64>(p0, f, dw); mma32_rs0<(o) + 128, H64>(p1, f + 8, dw); \
                mma32_rs<(o) + 64, H64>(p0, f + 4, dw); mma32_rs<(o) + 192, H64>(p1, f + 12, dw); wg_commit(); } while (0)
            #define V_OUT(lo) _Pragma("unroll") for (int i = lo; i < lo + 4; i++) { const int o = 32 + 8 * i; \
                stsm4(sb + OFF_V + (i >> 1) * 8192u + srow * 64u + (((2 * (i & 1) + (lane >> 4)) ^ ((srow >> 1) & 3)) << 4), \
                      pack2(a1[o], a1[o + 1]), pack2(a1[o + 2], a1[o + 3]), pack2(a1[o + 4], a1[o + 5]), pack2(a1[o + 6], a1[o + 7])); }
            V_OUT(0);
            #pragma unroll
            for (int i = 0; i < 16; i++) ph0[i] = pack2(a0[64 + 2 * i], a0[65 + 2 * i]);
            PMMA(ph0, 0);
            V_OUT(4);
            #undef V_OUT
            wg_wait<0>();
            acc_fence(p0); acc_fence(p1);
            fm_max(p0, pk, mm); fm_max(p1, pk + 8, mm + 2);
            #pragma unroll
            for (int i = 0; i < 16; i++) ph1[i] = pack2(a1[2 * i], a1[2 * i + 1]);
            PMMA(ph1, 256);
            if (warp == 0) TS(19);
            fm_pos(pk, mm, ea);
            #pragma unroll
            for (int i = 0; i < 32; i++) kq[i] = pack2(a0[2 * i], a0[2 * i + 1]);
            acc_fence(ea); pin<32>(kq);
            wg_wait<0>();
            acc_fence(p0); acc_fence(p1);
            #define PHI_OUT(ph, i) do { if (u < 2) { \
                    mbar_wait(u ? BAR(B_PE + (i)) : (i) ? BAR(B_LMD) : BAR(B_QE), 0);          \
                    _Pragma("unroll") for (int q = 0; q < 4; q++) stsm4((pa ^ (q << 5)) + OFF_PHI + (i) * 16384u, ph[4 * q], ph[4 * q + 1], ph[4 * q + 2], ph[4 * q + 3]); \
                    __syncwarp(); \
                    e_arrive(BAR(B_PF + (i)) + u * 16); } } while (0)
            reg_dec<216>();
            #pragma unroll 1
            for (int u = 0; u < 4; u++) {
                fm_neg(mm, ldsf(sb + OFF_CST + 48), ea); fm_pos(pk + 8, mm + 2, eb);
                fm_norm(ea, ph0); fm_max(p0, pk, mm); fm_max(p1, pk + 8, mn);
                PHI_OUT(ph0, 0);
                if (warp == 0) TR(130 + (u & 1) * 6);
                if (u == 0) PMMA(kq, 0); else PMMA(kq + 16, 256);
                fm_neg(mm + 2, ldsf(sb + OFF_CST + 48), eb); fm_pos(pk, mm, ea);
                fm_norm(eb, ph1);
                mm[2] = mn[0]; mm[3] = mn[1];
                PHI_OUT(ph1, 1);
                wg_wait<0>();
                acc_fence(p0); acc_fence(p1);
                if (u == 2) {
                    e_arrive(BAR(B_STP));
                    mbar_wait(BAR(B_GF), 0);
                    #pragma unroll
                    for (int i = 0; i < 16; i++) { kq[i] = ph0[i]; kq[16 + i] = ph1[i]; }
                }
                if (warp == 0) TR(133 + (u & 1) * 6);
                if (warp == 0) TS(21 + u);
            }
            #undef PHI_OUT
            #undef PMMA
        }
        }
        uint32_t gf[16][4], uf[16][4];
        const uint32_t fo = sb + (warp >> 1) * 2048u + ((lane & 7) + (lane >> 4) * 8) * 64u + (((2 * (warp & 1) + ((lane >> 3) & 1)) ^ ((lane >> 1) & 3)) << 4);
        #define F_LOAD(f, off, i) ldsm4t(f[i], fo + (off) + ((i) >> 1) * 8192u + ((i) & 1) * 1024u)
        #define G_LOAD(lo, n, k) do { _Pragma("unroll") for (int i = lo; i < lo + n; i++) F_LOAD(gf, OFF_R0, i); e_arrive(BAR(B_GE + k)); } while (0)
        #define O_BLOCK(pp, ph0, ph1) do { \
            if ((AWAKE & 2) && !(pp)) mbar_wait_awake(BAR(B_KVT + (pp)), 0); else mbar_wait(BAR(B_KVT + (pp)), 0); \
            if (warp == 0) TS(25 + 3 * (pp)); \
            const uint32_t oa = T128(tid + (lds32(sb + OFF_CST) >> 16)); \
            float o0[20], o1[20]; \
            const uint32_t dk = (pp) ? desc_lo(sb + OFF_KL, OFF_Z + 32 - OFF_KL) : desc_lo(sb + OFF_KVT, OFF_Z - OFF_KVT); \
            constexpr uint32_t K1 = 256u - (255u << 16);          \
            wg_fence(); \
            mma40_rs0<0, H64>(o0, ph0, dk); mma40_rs0<K1, H64>(o1, ph1, dk); \
            mma40_rs<64, H64>(o0, ph0 + 4, dk); mma40_rs<K1 + 64, H64>(o1, ph1 + 4, dk); \
            mma40_rs<128, H64>(o0, ph0 + 8, dk); mma40_rs<K1 + 128, H64>(o1, ph1 + 8, dk); \
            mma40_rs<192, H64>(o0, ph0 + 12, dk); mma40_rs<K1 + 192, H64>(o1, ph1 + 12, dk); \
            wg_commit(); \
            wg_wait<0>(); \
            acc_fence(o0); acc_fence(o1); \
            if (pp) e_arrive(BAR(B_ED)); \
            if (warp == 0) TS(26 + 3 * (pp)); \
            mbar_wait(BAR(B_GE + (pp)), 0); \
            _Pragma("unroll") for (int hh = 0; hh < 2; hh++) { \
                const float (&o)[20] = hh ? o1 : o0; \
                uint32_t h0, l0, h1, l1; \
                split_rcp(rcp(rbf(rbf(o[16]) + 1e-6f)), h0, l0); split_rcp(rcp(rbf(rbf(o[18]) + 1e-6f)), h1, l1); \
                _Pragma("unroll") for (int q = 0; q < 2; q++) \
                    stsm4((oa ^ ((2 * hh + q) << 5)) + OFF_R0 + (pp) * 16384u, hdiv2(pack2(o[8 * q], o[8 * q + 1]), h0, l0), hdiv2(pack2(o[8 * q + 2], o[8 * q + 3]), h1, l1), \
                          hdiv2(pack2(o[8 * q + 4], o[8 * q + 5]), h0, l0), hdiv2(pack2(o[8 * q + 6], o[8 * q + 7]), h1, l1)); \
            } \
            fence_async_smem(); \
            __syncwarp(); \
            e_arrive(BAR(B_OWN + (pp))); \
            if (warp == 0) TS(27 + 3 * (pp)); \
        } while (0)
        float acc[64];
        const uint32_t da = desc_lo(sb + OFF_R0 + wgi * 8192u, 16), db = desc_lo(sb + OFF_DB, 8192);
        #define D_MMA(first, a, s) do { \
            wg_fence(); \
            first<(a), H128, (s) * 1024, H128>(acc, da, db); mma128_ss<(a) + 2, H128, (s) * 1024 + 128, H128>(acc, da, db); \
            mma128_ss<(a) + 4, H128, (s) * 1024 + 256, H128>(acc, da, db); mma128_ss<(a) + 6, H128, (s) * 1024 + 384, H128>(acc, da, db); \
            wg_commit(); } while (0)
        G_LOAD(0, 4, 0);
        O_BLOCK(0, kq, (kq + 16));
        G_LOAD(4, NG1, 1);
        mbar_wait(BAR(B_OWN), 0);
        mbar_wait(BAR(B_FD), 0);
        D_MMA(mma128_ss0, 0, 0);
        O_BLOCK(1, ph0, ph1);
        G_LOAD(4 + NG1, 12 - NG1, 2);
        reg_inc<232>();
        mbar_wait(BAR(B_OWN + 1), 0);
        #undef O_BLOCK
        #define D_STEP(n) do { \
            mbar_wait(BAR(B_FD + ((n) & 3)), ((n) >> 2) & 1); \
            if (warp == 0) TR(112 + (n)); \
            D_MMA(mma128_ss, (n) == 5 ? OFF_X1 / 16 : ((n) & 3) * 1024, (n) & 3); \
            if ((n) == 3) mbar_wait(BAR(B_UF), 0); \
            if ((n) >= 3 && (n) < 7) { F_LOAD(uf, OFF_F2, 2 * (((n) + 5) & 7)); F_LOAD(uf, OFF_F2, 2 * (((n) + 5) & 7) + 1); } \
            wg_wait<1>(); \
            if ((n) > 2) e_arrive(BAR(B_ED + (((n) + 3) & 3))); } while (0)
        D_STEP(1);
        wg_wait<0>();
        e_arrive(BAR(B_ED + 1));
        D_STEP(2);
        if (warp == 0) TS(31);
        D_STEP(3); D_STEP(4); D_STEP(5); D_STEP(6); D_STEP(7); D_STEP(8); D_STEP(9); D_STEP(10); D_STEP(11); D_STEP(12); D_STEP(13); D_STEP(14); D_STEP(15);
        #undef D_STEP
        #undef D_MMA
        #define XADDR(i) ((xa ^ (((i) & 3) << 5)) + ((i) < 4 ? OFF_R0 : OFF_X1))
        mbar_wait(BAR(B_PAR), 0);
        const uint4 cst = lds128(sb + OFF_CST);
        const int b = cst.x & 255;
        const uint32_t tag = cst.y, xa = T128(tid + (cst.x >> 16));
        uint4 w[4];
        const uint32_t rl = warp * 16 + g + 8 * (c & 1);
        const uint4* ws = pin_ptr(p.s->llln2 + ((b & ~7) + (c >> 1) * 4) * 128 + rl);
        {
        {
            uint32_t x2[8][4];
            mbar_wait(BAR(B_WPHI), 1);
            #pragma unroll
            for (int i = 0; i < 8; i++) ldsm4(x2[i], XADDR(i));
            uint4* d = pin_ptr(p.s->llln2 + b * 128 + warp * 16 + g);
            const uint32_t ta = sb + OFF_T1 + (g & 1) * 512 + c * 16;
            uint4 t = lds128(ta), tn = lds128(ta + 64);
            wg_wait<0>();
            acc_fence(acc);
            e_arrive(BAR(B_ED + 3));
            if (warp == 0) TS(32);
            float sd[4] = {0.f, 0.f, 0.f, 0.f}, qa[4] = {0.f, 0.f, 0.f, 0.f}, qb[4] = {0.f, 0.f, 0.f, 0.f};
            #pragma unroll
            for (int i = 0; i < 8; i++) {
                x2[i][0] = hadd2(x2[i][0], hmul2(t.x, pack2(acc[8 * i], acc[8 * i + 1]))); x2[i][1] = hadd2(x2[i][1], hmul2(t.x, pack2(acc[8 * i + 2], acc[8 * i + 3])));
                x2[i][2] = hadd2(x2[i][2], hmul2(t.y, pack2(acc[8 * i + 4], acc[8 * i + 5]))); x2[i][3] = hadd2(x2[i][3], hmul2(t.y, pack2(acc[8 * i + 6], acc[8 * i + 7])));
                mma16816(sd, x2[i][0], x2[i][1], x2[i][2], x2[i][3], t.z, t.w);
                t = tn;
                if (i < 6) tn = lds128(ta + (i + 2) * 64);
                mma16816(qa, x2[i][0], x2[i][1], x2[i][2], x2[i][3], x2[i][0], x2[i][2]);
                mma16816(qb, x2[i][0], x2[i][1], x2[i][2], x2[i][3], x2[i][1], x2[i][3]);
            }
            if (c == (g >> 1)) {
                st_ll(d, f2u(sd[0]), f2u((g & 1) ? qa[1] : qa[0]), f2u(sd[1]), tag);
                st_ll(d + 8, f2u(sd[2]), f2u((g & 1) ? qb[3] : qb[2]), f2u(sd[3]), tag);
            }
            __syncwarp();
            #pragma unroll
            for (int i = 0; i < 4; i++) w[i] = ld_ll(ws + i * 128);
            if (warp == 0) TS(33);
            #pragma unroll
            for (int i = 0; i < 8; i++) stsm4(XADDR(i), x2[i][0], x2[i][1], x2[i][2], x2[i][3]);
        }
        uint4 t2[8]; uint2 t3[8];
        #pragma unroll
        for (int i = 0; i < 8; i++) { t2[i] = lds128(sb + OFF_T2 + i * 64 + c * 16); t3[i] = lds64(sb + OFF_T3 + i * 32 + c * 8); }
        mbar_wait(BAR(B_ED + 3), 1);
        {
            #pragma unroll 1
            for (int it = 0; it < POLL_MAX; it++) {
                if (__all_sync(0xffffffffu, !(tag_bad(w[0].w ^ tag, w[1].w, tag) | tag_bad(w[2].w ^ tag, w[3].w, tag)))) break;
                #pragma unroll
                for (int i = 0; i < 4; i++) if (w[i].w != tag) w[i] = ld_ll(ws + i * 128);
            }
            float s1 = (u2f(w[0].x) + u2f(w[1].x)) + (u2f(w[2].x) + u2f(w[3].x));
            float s2 = (u2f(w[0].y) + u2f(w[1].y)) + (u2f(w[2].y) + u2f(w[3].y));
            float dt = (u2f(w[0].z) + u2f(w[1].z)) + (u2f(w[2].z) + u2f(w[3].z));
            s1 += shfl_x(s1, 2); s2 += shfl_x(s2, 2); dt += shfl_x(dt, 2);
            uint32_t m2, rh, rl2; float rinv;
            ln_final(s1, s2, m2, rinv);
            const uint32_t key = (f2key(fmaf(fmaf(-bf_lo(m2), u2f(cst.z), dt), rinv, u2f(cst.w))) | 2047u) ^ ((b >> 3) * 128 + rl);
            split_rcp(rinv, rh, rl2);
            if (c < 2) { sts32(sb + OFF_KEY + rl * 4, key); sts128(sb + OFF_ST2 + rl * 16, make_uint4(m2, rh, rl2, 0)); }
            __syncwarp();
            e_arrive(BAR(B_KEYS));
        }
        if (warp == 0) TS(34);
        {
            const uint4 s0 = lds128(sb + OFF_ST2 + (warp * 16 + g) * 16), s1 = lds128(sb + OFF_ST2 + (warp * 16 + g + 8) * 16);
            uint32_t x2[8][4];
            #pragma unroll
            for (int i = 0; i < 8; i++) ldsm4(x2[i], XADDR(i));
            const uint32_t oa = xa + warp * 2048u;
            #pragma unroll
            for (int i = 0; i < 8; i++) {
                const uint4 t = t2[i]; const uint2 gb = t3[i];
                stsm4((oa ^ ((i & 3) << 5)) + OFF_OUT + (i >> 2) * 2048u,
                      hadd2(x2[i][0], hmul2(gb.x, lnmod(x2[i][0], s0.x, s0.y, s0.z, t.x, t.z))), hadd2(x2[i][1], hmul2(gb.x, lnmod(x2[i][1], s1.x, s1.y, s1.z, t.x, t.z))),
                      hadd2(x2[i][2], hmul2(gb.y, lnmod(x2[i][2], s0.x, s0.y, s0.z, t.y, t.w))), hadd2(x2[i][3], hmul2(gb.y, lnmod(x2[i][3], s1.x, s1.y, s1.z, t.y, t.w))));
            }
            __syncwarp();
            e_arrive(BAR(B_SWP));
        }
        }
        #undef XADDR
        if (warp == 0) TS(35);
        uint32_t fx = 0, fh = 0, fg = 0, fs2, frow;
        uint32_t df[16][4];
        const uint32_t dfo = sb + warp * 4096u + ((lane & 7) + (lane >> 4) * 8) * 128u + ((((lane >> 3) & 1) ^ (lane & 7)) << 4);
        #define DF_LOAD(i) ldsm4t(df[i], (dfo + ((i) < 8 ? OFF_F2 : OFF_DB) + ((i) & 1) * 2048u) ^ ((((i) >> 1) & 3) << 5))
        {
            const int wi = ((tid >> 3) & 7) * 32 + (tid >> 6) * 8 + (tid & 7);
            const uint4* rh = pin_ptr(p.s->llrowh + wi);
            #pragma unroll
            for (int i = 8; i < 16; i++) F_LOAD(uf, OFF_F2, i);
            mbar_wait(BAR(B_SEL) + ((AWAKE & 4) ? awake_zero() : 0), 0);
            const uint2 bb = lds64(sb + OFF_CST + 24);
            const uint32_t b0 = bb.x, b1 = bb.y;
            if (warp == 0) TS(36);
            const uint32_t o0 = (~b0 & 0x780u) * 4, o1 = (~b1 & 0x780u) * 4, slot0 = o0, slot1 = o1 + (o0 == o1 ? 256 : 0);
            const int wd = ((g & 1) ? slot1 : slot0) + b * 2 + (c >> 1) - wi;
            uint4 hv[2], fv[2];
            #pragma unroll 1
            for (int it = 0; it < POLL_MAX; it++) {
                hv[0] = ld_ll(rh + slot0); hv[1] = ld_ll(rh + slot1);
                uint32_t bad = 0;
                if (warp == 0) {
                    fv[0] = ld_ll(rh + wd + 8192); fv[1] = ld_ll(rh + wd);
                    bad = tag_bad(fv[0].w ^ tag, fv[1].w, tag);
                    fx = (g & 2) ? fv[0].y : fv[0].x; fh = (g & 2) ? fv[1].y : fv[1].x; fg = (g & 2) ? fv[0].z : fv[1].z;
                }
                if (it == 0) {
                    mbar_wait(BAR(B_WD), 0);
                    #pragma unroll
                    for (int i = 0; i < NDF; i++) DF_LOAD(i);
                }
                if (__all_sync(0xffffffffu, !ll_bad<1>(ll_bad<1>(bad, hv[0], tag), hv[1], tag))) break;
            }
            const uint32_t ha = sb + OFF_HSEL + (tid >> 3) * 128u + c * 16u + (g & 1) * 8u;
            sts64(ha, hv[0].x, hv[0].y); sts64(ha + 64, hv[1].x, hv[1].y);
            bar_sync(2 + (warp >> 1), 64);
            const uint32_t bk = (g & 1) ? b1 : b0;
            frow = ~bk & 2047u;
            const float sg = sigmoid_f(rbf(key2f((bk & ~2047u) | 1024u)));
            fs2 = pack2(sg, sg);
        }
        if (warp == 0) TS(37);
        uint4* yd = p.s->lly + (cst.x >> 8) * 512 + (warp * 8 + c) * 8 + g;
        const uint4* ys = p.s->lly + (tid >> 2) * 512 + b * 4 + c;
        uint16_t* od = (uint16_t*)p.out + (size_t)frow * 1024 + (b >> 1) * 16 + (b & 1) * 4 + c + 8 * (g >> 1);
        {
            float ag[2][4], au[2][4];
            #pragma unroll
            for (int i = 0; i < 4; i++) ag[0][i] = ag[1][i] = au[0][i] = au[1][i] = 0.f;
            const uint32_t ha = sb + OFF_HSEL + (warp >> 1) * 1024u + (lane & 7) * 16u;
            uint4 hn = lds128(ha), hm = lds128(ha + 128);
            #pragma unroll
            for (int i = 0; i < 8; i++) {
                const uint4 h = hn;
                hn = hm;
                if (i < 6) hm = lds128(ha + (i + 2) * 128u);
                mma16816(ag[0], gf[2 * i][0], gf[2 * i][1], gf[2 * i][2], gf[2 * i][3], h.x, h.y);
                mma16816(au[0], uf[2 * i][0], uf[2 * i][1], uf[2 * i][2], uf[2 * i][3], h.x, h.y);
                mma16816(ag[1], gf[2 * i + 1][0], gf[2 * i + 1][1], gf[2 * i + 1][2], gf[2 * i + 1][3], h.z, h.w);
                mma16816(au[1], uf[2 * i + 1][0], uf[2 * i + 1][1], uf[2 * i + 1][2], uf[2 * i + 1][3], h.z, h.w);
                if (NDF + 2 * i < 16) { DF_LOAD((NDF + 2 * i) & 15); DF_LOAD((NDF + 2 * i + 1) & 15); }
            }
            sts64(sb + OFF_RED + (warp >> 1) * 512u + (c & 1) * 256u + ((warp & 1) * 16 + (c >> 1) * 8 + g) * 8u,
                  f2u(sel4(c, ag[0][0], ag[0][1], ag[0][2], ag[0][3]) + sel4(c, ag[1][0], ag[1][1], ag[1][2], ag[1][3])),
                  f2u(sel4(c, au[0][0], au[0][1], au[0][2], au[0][3]) + sel4(c, au[1][0], au[1][1], au[1][2], au[1][3])));
        }
        yd = pin_ptr(yd); ys = pin_ptr(ys); od = pin_ptr(od); pin<1>(&fs2);
        bar_sync(1, 256);
        {
            const uint32_t ra = sb + OFF_RED + lane * 16u;
            const uint4 r0 = lds128(ra), r1 = lds128(ra + 512), r2 = lds128(ra + 1024), r3 = lds128(ra + 1536);
            #define F4(f) ((u2f(r0.f) + u2f(r1.f)) + (u2f(r2.f) + u2f(r3.f)))
            const uint32_t hid = hmul2(silu2(pack2(F4(x), F4(z))), pack2(F4(y), F4(w)));
            #undef F4
            if (warp == 0) TS(38);
            const int src = (g & 1) * 16 + c;
            const uint32_t b0 = __shfl_sync(0xffffffffu, hid, src), b1 = __shfl_sync(0xffffffffu, hid, src + 4), b2 = __shfl_sync(0xffffffffu, hid, src + 8), b3 = __shfl_sync(0xffffffffu, hid, src + 12);
            float y[8][4];
            #pragma unroll
            for (int i = 0; i < 8; i++) {
                y[i][0] = y[i][1] = y[i][2] = y[i][3] = 0.f;
                mma16816(y[i], df[2 * i][0], df[2 * i][1], df[2 * i][2], df[2 * i][3], b0, b1);
            }
            #pragma unroll
            for (int i = 0; i < 8; i++) mma16816(y[i], df[2 * i + 1][0], df[2 * i + 1][1], df[2 * i + 1][2], df[2 * i + 1][3], b2, b3);
            if (cst.x < 112 * 256) {
                #pragma unroll
                for (int h = 0; h < 2; h++) {
                    #define YS(e) sel4(c, y[4 * h][e], y[4 * h + 1][e], y[4 * h + 2][e], y[4 * h + 3][e])
                    st_ll4(yd + 32 * h, YS(0), YS(1), YS(2), YS(3), tag);
                    #undef YS
                }
            }
        }
        if (warp == 0) TS(39);
        if (warp < 7) {
            uint4 v[2];
            v[0].w = v[1].w = 0;
            spin_until(clk32() + YWAIT);
            #pragma unroll 1
            for (int it = 0; it < POLL_MAX; it++) {
                if ((v[0].w ^ tag) & 3) v[0] = ld_ll(ys);
                if ((v[1].w ^ tag) & 3) v[1] = ld_ll(ys + 56 * 512);
                if (__all_sync(0xffffffffu, !(tag_bad(v[0].w ^ tag, v[1].w, tag) & 3))) break;
            }
            float y0 = u2f(v[0].x) + u2f(v[1].x), y1 = u2f(v[0].y) + u2f(v[1].y), y2 = u2f(v[0].z) + u2f(v[1].z), y3 = u2f(v[0].w) + u2f(v[1].w);
            const bool g0 = g & 1, g1 = g & 2;
            const float k0 = (g0 ? y1 : y0) + shfl_x(g0 ? y0 : y1, 4), k1 = (g0 ? y3 : y2) + shfl_x(g0 ? y2 : y3, 4);
            const float y = (g1 ? k1 : k0) + shfl_x(g1 ? k0 : k1, 8);
            stsf(sb + OFF_RED2 + (lane & 15) * 64u + (lane >> 4) * 32u + warp * 4u, y);
            bar_sync(6, 224);
            if (tid < 16) {
                const uint32_t a = sb + OFF_RED2 + lane * 64u;
                const uint4 ya = lds128(a), yb = lds128(a + 16), yc = lds128(a + 32), ye = lds128(a + 48);
                const float s = (((u2f(ya.x) + u2f(ya.y)) + (u2f(ya.z) + u2f(ya.w))) + ((u2f(yb.x) + u2f(yb.y)) + u2f(yb.z)))
                              + (((u2f(yc.x) + u2f(yc.y)) + (u2f(yc.z) + u2f(yc.w))) + ((u2f(ye.x) + u2f(ye.y)) + u2f(ye.z)));
                const uint32_t o = hadd2(fx, hmul2(fg, hadd2(fh, hmul2(pack2(s, s), fs2))));
                *od = (c & 1) ? o >> 16 : o;
                if (b == 0 && tid == 0) p.s->done[0] = tag;
                TS(40);
            }
        }
    }
}

typedef CUresult (*EncodeFn)(CUtensorMap*, CUtensorMapDataType, cuuint32_t, void*, const cuuint64_t*, const cuuint64_t*, const cuuint32_t*,
                             const cuuint32_t*, CUtensorMapInterleave, CUtensorMapSwizzle, CUtensorMapL2promotion, CUtensorMapFloatOOBfill);

CUtensorMap make_map(EncodeFn enc, const void* ptr, uint64_t cols, uint64_t rows, uint32_t bc, uint32_t br, CUtensorMapSwizzle swz, CUtensorMapL2promotion promo) {
    CUtensorMap m;
    cuuint64_t dims[2] = {cols, rows}, strides[1] = {cols * 2};
    cuuint32_t box[2] = {bc, br}, es[2] = {1, 1};
    enc(&m, CU_TENSOR_MAP_DATA_TYPE_BFLOAT16, 2, const_cast<void*>(ptr), dims, strides, box, es, CU_TENSOR_MAP_INTERLEAVE_NONE, swz, promo,
        CU_TENSOR_MAP_FLOAT_OOB_FILL_NONE);
    return m;
}
CUtensorMap make_map4(EncodeFn enc, const void* ptr, uint32_t groups, uint64_t rows, uint32_t br, CUtensorMapL2promotion promo) {
    CUtensorMap m;
    cuuint64_t dims[4] = {64, rows, 16, groups}, strides[3] = {groups * 2048ull, 128, 2048};
    cuuint32_t box[4] = {64, br, 2, groups}, es[4] = {1, 1, 1, 1};
    enc(&m, CU_TENSOR_MAP_DATA_TYPE_BFLOAT16, 4, const_cast<void*>(ptr), dims, strides, box, es, CU_TENSOR_MAP_INTERLEAVE_NONE, CU_TENSOR_MAP_SWIZZLE_128B, promo,
        CU_TENSOR_MAP_FLOAT_OOB_FILL_NONE);
    return m;
}

}

extern "C" void kernel_launch(void* const* d_in, const int* in_sizes, int n_in, void* d_out, int out_size) {
    (void)in_sizes; (void)n_in; (void)out_size;
    void* fn = nullptr; cudaDriverEntryPointQueryResult qr;
    cudaGetDriverEntryPoint("cuTensorMapEncodeTiled", &fn, cudaEnableDefault, &qr);
    EncodeFn enc = (EncodeFn)fn;
    void* hs = nullptr;
    cudaGetSymbolAddress(&hs, g_scratch);
    int dev = 0, sms = 0;
    cudaGetDevice(&dev);
    cudaDeviceGetAttribute(&sms, cudaDevAttrMultiProcessorCount, dev);
    const CUtensorMapL2promotion P256 = CU_TENSOR_MAP_L2_PROMOTION_L2_256B, P128 = CU_TENSOR_MAP_L2_PROMOTION_L2_128B, P0 = CU_TENSOR_MAP_L2_PROMOTION_NONE;
    CUtensorMap tmW = make_map4(enc, d_in[1], 3, 1024, 32, P256);
    CUtensorMap tmWo = make_map4(enc, d_in[3], 1, 1024, 64, P256);
    CUtensorMap tmO = make_map4(enc, d_out, 1, 2048, 16, P0);
    CUtensorMap tmPhi = make_map(enc, d_in[2], 32, 1024, 32, 128, CU_TENSOR_MAP_SWIZZLE_64B, P128);
    CUtensorMap tmG = make_map(enc, d_in[6], 3584, 1024, 32, 128, CU_TENSOR_MAP_SWIZZLE_64B, P0);
    CUtensorMap tmU = make_map(enc, d_in[7], 3584, 1024, 32, 128, CU_TENSOR_MAP_SWIZZLE_64B, P0);
    CUtensorMap tmD = make_map(enc, d_in[8], 1024, 3584, 64, 32, CU_TENSOR_MAP_SWIZZLE_128B, P128);
    CUtensorMap tmX = make_map(enc, d_in[0], 1024, 2048, 64, 128, CU_TENSOR_MAP_SWIZZLE_128B, P128);
    CUtensorMap tmM = make_map(enc, d_in[10], 6144, 1024, 64, 256, CU_TENSOR_MAP_SWIZZLE_128B, MPROMO);
    Ptrs p;
    p.x = (const bf16*)d_in[0]; p.c = (const bf16*)d_in[9]; p.wmod = (const bf16*)d_in[10]; p.wr = (const bf16*)d_in[5];
    p.wg = (const bf16*)d_in[6]; p.wu = (const bf16*)d_in[7]; p.wd = (const bf16*)d_in[8]; p.out = (bf16*)d_out; p.s = (Scratch*)hs;
    p.wqkv = (const bf16*)d_in[1]; p.wo = (const bf16*)d_in[3];
    p.by_sm = sms == 132;
    for (int sm = 0; sm < 132; sm++) {
        const int tp = sm >> 1, u = tp - 32;
        const int gp = (GPERM >> (4 * (tp < 32 ? tp & 7 : tp < 60 ? 1 + u % 7 : 0))) & 7, sl = 2 * (tp < 32 ? tp >> 3 : tp < 60 ? 4 + u / 7 : tp - 58) + (sm & 1);
        const int b = (tp >> 1) == 30 ? sm + 8 : ((gp >> 1) * 4 + (sl & 3)) * 8 + (gp & 1) * 4 + (sl >> 2);
        const int f = FMODE == 0 ? (b < 112 ? b : 255) : FMODE == 1 ? (sl < 14 && b < 128 ? gp * 14 + sl : 255) : (sm < 112 ? sm : 255);
        p.role[sm] = (uint16_t)(b | f << 8);
    }
    cudaFuncSetAttribute(fused_kernel, cudaFuncAttributeMaxDynamicSharedMemorySize, SMEM_BYTES);
    fused_kernel<<<132, NTHREADS, SMEM_BYTES, cudaStreamPerThread>>>(p, tmM, tmX, tmW, tmWo, tmPhi, tmG, tmU, tmD, tmO);
}
```

```cpp
#include <cuda_runtime.h>
#include <cuda.h>
#include <cuda_bf16.h>
#include <stdint.h>

namespace {

typedef __nv_bfloat16 bf16;

#define NFREE 4
constexpr int NTHREADS = 512;
constexpr int POLL_MAX = 400000;

constexpr uint32_t OFF_R0   = 0;
constexpr uint32_t OFF_A    = 65536;
constexpr uint32_t OFF_B    = 114688;
constexpr uint32_t OFF_V    = 65536;
constexpr uint32_t OFF_PHI  = 98304;
constexpr uint32_t OFF_F2   = 65536;
constexpr uint32_t OFF_DB   = 131072;
constexpr uint32_t OFF_KL   = 196608;
constexpr uint32_t OFF_WPHI = 214016;
constexpr uint32_t OFF_KVT  = OFF_WPHI;
constexpr uint32_t OFF_Z    = 222208;
constexpr uint32_t OFF_TAB  = OFF_Z;
constexpr uint32_t OFF_ONES = 226304;
constexpr uint32_t OFF_BAR  = 227328;
constexpr uint32_t OFF_CST  = OFF_BAR + 640;
constexpr uint32_t OFF_T1   = OFF_ONES;
constexpr uint32_t OFF_T2   = OFF_CST + 64;
constexpr uint32_t OFF_T3   = OFF_T2 + 512;
constexpr uint32_t OFF_KEY  = OFF_T3 + 256;
constexpr uint32_t OFF_ST2  = OFF_KEY + 512;
constexpr uint32_t OFF_CHK  = OFF_KEY;
constexpr uint32_t OFF_ZS   = OFF_ST2;
constexpr uint32_t SMEM_BYTES = 232448;
constexpr uint32_t OFF_X1   = OFF_KL;
constexpr uint32_t OFF_OUT  = OFF_R0 + 32768;
constexpr uint32_t OFF_HSEL = OFF_WPHI;
constexpr uint32_t OFF_RED  = OFF_WPHI + 4096;
constexpr uint32_t OFF_RED2 = OFF_RED + 2048;
static_assert(OFF_ST2 + 2048 <= SMEM_BYTES, "layout");

enum {
    B_O1 = 0, B_UF = 1, B_UD = 2, B_WPHI = 3, B_FB = 4  , B_OST = 8, B_GF = 9, B_WD = 10, B_KVL = 11  , B_KZ = 13, B_LMF = 14, B_SEL = 15, B_XP = 16  , B_TAG = 24,
    B_FA = 25  , B_FD = 30  , B_CAND = 34,
    B_PE = 35  , B_KST = 37  , B_KVT = 41  , B_LMD = 43, B_PAR = 44,
    B_EA = 45  , B_EB = 48  , B_PF = 56  , B_OWN = 60  , B_QE = 62, B_STP = 63, B_KEYS = 64, B_SWP = 65, B_STS = 66, B_GE = 67, B_CS = B_GE + 1  ,
    B_ED = 70  ,
    B_RD = 75
};

struct Scratch {
    uint4 os[16 * 16 * 1024];
    uint4 kvacc[8 * 4 * 528];
    uint4 flk[3 * 128 * 2];
    uint4 llstat[2048];
    uint4 llm1[16 * 64];
    uint4 flo[3 * 128 * 2];
    uint4 llmod2[2 * 256];
    uint4 llg[2 * 4 * 256];
    uint4 llln2[16 * 8 * 128];
    uint4 llcand[16 * 2];
    uint4 llrowh[32 * 256];
    uint4 llrowx[32 * 256];
    uint4 lly[128 * 512];
    unsigned done[4];
};
__device__ __align__(1024) Scratch g_scratch;
#define GT(i) do {} while (0)
#define TS(i) do {} while (0)
#define TR(i) do {} while (0)

__device__ __forceinline__ uint32_t smem_u32(const void* p) { return (uint32_t)__cvta_generic_to_shared(p); }
__device__ __forceinline__ uint32_t clk32() { uint32_t c; asm volatile("mov.u32 %0, %%clock;" : "=r"(c) :: "memory"); return c; }
__device__ __forceinline__ void spin_until(uint32_t t) { while ((int)(clk32() - t) < 0) {} }
__device__ __forceinline__ void sleep_until(uint32_t t) { while ((int)(clk32() - t) < 0) __nanosleep(40); }
__device__ __forceinline__ void mbar_init_fence() { asm volatile("fence.mbarrier_init.release.cluster;" ::: "memory"); }
__device__ __forceinline__ void mbar_wait(uint32_t bar, uint32_t parity) {
    asm volatile("{\n.reg .pred P1;\nLAB_WAIT:\nmbarrier.try_wait.parity.shared::cta.b64 P1, [%0], %1;\n@!P1 bra LAB_WAIT;\n}" :: "r"(bar), "r"(parity) : "memory");
}
__device__ __forceinline__ uint64_t policy_evict_first() { uint64_t p; asm("createpolicy.fractional.L2::evict_first.b64 %0, 1.0;" : "=l"(p)); return p; }
#define ELECT "{\n.reg .pred e;\nelect.sync _|e, 0xffffffff;\n@e "
__device__ __forceinline__ void e_arrive(uint32_t bar) { asm volatile(ELECT "mbarrier.arrive.shared::cta.b64 _, [%0];\n}" :: "r"(bar) : "memory"); }
__device__ __forceinline__ void e_arrive_after(uint32_t bar, uint32_t v) {
    asm volatile("{\n.reg .pred e;\n.reg .b32 n;\npopc.b32 n, %1;\nshr.u32 n, n, 4;\nmul.lo.u32 n, n, n;\nshr.u32 n, n, 3;\nadd.u32 n, n, %0;\n"
        "elect.sync _|e, 0xffffffff;\n@e mbarrier.arrive.shared::cta.b64 _, [n];\n}" :: "r"(bar), "r"(v) : "memory");
}
__device__ __forceinline__ void e_arrive_tx(uint32_t bar, uint32_t bytes) { asm volatile(ELECT "mbarrier.arrive.expect_tx.shared::cta.b64 _, [%0], %1;\n}" :: "r"(bar), "r"(bytes) : "memory"); }
__device__ __forceinline__ void e_init(uint32_t bar, uint32_t cnt) { asm volatile(ELECT "mbarrier.init.shared::cta.b64 [%0], %1;\n}" :: "r"(bar), "r"(cnt) : "memory"); }
__device__ __forceinline__ void tma_load_ef(uint32_t dst, const CUtensorMap* tm, int c0, int c1, uint32_t bar) {
    asm volatile(ELECT "cp.async.bulk.tensor.2d.shared::cluster.global.mbarrier::complete_tx::bytes.L2::cache_hint [%0], [%1, {%3, %4}], [%2], %5;\n}"
        :: "r"(dst), "l"(tm), "r"(bar), "r"(c0), "r"(c1), "l"(policy_evict_first()) : "memory");
}
__device__ __forceinline__ void tma_load(uint32_t dst, const CUtensorMap* tm, int c0, int c1, uint32_t bar) {
    asm volatile(ELECT "cp.async.bulk.tensor.2d.shared::cluster.global.mbarrier::complete_tx::bytes [%0], [%1, {%3, %4}], [%2];\n}"
        :: "r"(dst), "l"(tm), "r"(bar), "r"(c0), "r"(c1) : "memory");
}
__device__ __forceinline__ void tma_load4(uint32_t dst, const CUtensorMap* tm, int row, int blk, uint32_t bar) {
    asm volatile(ELECT "cp.async.bulk.tensor.4d.shared::cluster.global.mbarrier::complete_tx::bytes [%0], [%1, {0, %3, %4, 0}], [%2];\n}"
        :: "r"(dst), "l"(tm), "r"(bar), "r"(row), "r"(blk) : "memory");
}
__device__ __forceinline__ void tma_store4(const CUtensorMap* tm, int row, int blk, uint32_t src) {
    asm volatile(ELECT "cp.async.bulk.tensor.4d.global.shared::cta.bulk_group [%0, {0, %2, %3, 0}], [%1];\n}" :: "l"(tm), "r"(src), "r"(row), "r"(blk) : "memory");
}
__device__ __forceinline__ void bulk_load(uint32_t dst, const void* src, uint32_t bytes, uint32_t bar) {
    asm volatile(ELECT "cp.async.bulk.shared::cluster.global.mbarrier::complete_tx::bytes [%0], [%1], %2, [%3];\n}" :: "r"(dst), "l"(src), "r"(bytes), "r"(bar) : "memory");
}
__device__ __forceinline__ void bulk_store(void* dst, uint32_t src, uint32_t bytes) {
    asm volatile(ELECT "cp.async.bulk.global.shared::cta.bulk_group [%0], [%1], %2;\n}" :: "l"(dst), "r"(src), "r"(bytes) : "memory");
}
__device__ __forceinline__ void bulk_reduce(void* dst, uint32_t src, uint32_t bytes) {
    asm volatile(ELECT "cp.reduce.async.bulk.global.shared::cta.bulk_group.add.f32 [%0], [%1], %2;\n}" :: "l"(dst), "r"(src), "r"(bytes) : "memory");
}
__device__ __forceinline__ void tma_prefetch(const CUtensorMap* tm, int c0, int c1) {
    asm volatile(ELECT "cp.async.bulk.prefetch.tensor.2d.L2.global [%0, {%1, %2}];\n}" :: "l"(tm), "r"(c0), "r"(c1) : "memory");
}
__device__ __forceinline__ void l2_prefetch(const void* p, uint32_t bytes) {
    asm volatile(ELECT "cp.async.bulk.prefetch.L2.global [%0], %1;\n}" :: "l"(p), "r"(bytes) : "memory");
}
__device__ __forceinline__ void bulk_wait_read() { asm volatile("cp.async.bulk.commit_group;\ncp.async.bulk.wait_group.read 0;" ::: "memory"); }
__device__ __forceinline__ void bulk_wait() { asm volatile("cp.async.bulk.commit_group;\ncp.async.bulk.wait_group 0;" ::: "memory"); }
__device__ __forceinline__ void tmap_prefetch(const CUtensorMap* tm) { asm volatile("prefetch.tensormap [%0];" :: "l"(tm) : "memory"); }
__device__ __forceinline__ void wg_fence() { asm volatile("wgmma.fence.sync.aligned;" ::: "memory"); }
__device__ __forceinline__ void wg_commit() { asm volatile("wgmma.commit_group.sync.aligned;" ::: "memory"); }
template<int N> __device__ __forceinline__ void wg_wait() { asm volatile("wgmma.wait_group.sync.aligned %0;" :: "n"(N) : "memory"); }
template<int N> __device__ __forceinline__ void acc_fence(float (&d)[N]) {
    #pragma unroll
    for (int i = 0; i < N; i++) asm volatile("" : "+f"(d[i]) :: "memory");
}
__device__ __forceinline__ uint32_t desc_lo(uint32_t addr, uint32_t lbo) { return (addr >> 4) | ((lbo >> 4) << 16); }
constexpr uint32_t H128 = 0x40000040u;
constexpr uint32_t H64 = 0x80000020u;
__device__ __forceinline__ void fence_async_smem() { asm volatile("fence.proxy.async.shared::cta;" ::: "memory"); }
__device__ __forceinline__ void bar_sync(int id, int n) { asm volatile("bar.sync %0, %1;" :: "r"(id), "r"(n) : "memory"); }
template<int R> __device__ __forceinline__ void reg_inc() { asm volatile("setmaxnreg.inc.sync.aligned.u32 %0;" :: "n"(R)); }
template<int R> __device__ __forceinline__ void reg_dec() { asm volatile("setmaxnreg.dec.sync.aligned.u32 %0;" :: "n"(R)); }

__device__ __forceinline__ void stsm4(uint32_t addr, uint32_t r0, uint32_t r1, uint32_t r2, uint32_t r3) {
    asm volatile("stmatrix.sync.aligned.m8n8.x4.shared.b16 [%0], {%1,%2,%3,%4};" :: "r"(addr), "r"(r0), "r"(r1), "r"(r2), "r"(r3) : "memory");
}
__device__ __forceinline__ void ldsm4(uint32_t* r, uint32_t addr) {
    asm volatile("ldmatrix.sync.aligned.m8n8.x4.shared.b16 {%0,%1,%2,%3}, [%4];" : "=r"(r[0]), "=r"(r[1]), "=r"(r[2]), "=r"(r[3]) : "r"(addr) : "memory");
}
__device__ __forceinline__ void ldsm4t(uint32_t* r, uint32_t addr) {
    asm volatile("ldmatrix.sync.aligned.m8n8.x4.trans.shared.b16 {%0,%1,%2,%3}, [%4];" : "=r"(r[0]), "=r"(r[1]), "=r"(r[2]), "=r"(r[3]) : "r"(addr) : "memory");
}
__device__ __forceinline__ void mma16816(float (&d)[4], uint32_t a0, uint32_t a1, uint32_t a2, uint32_t a3, uint32_t b0, uint32_t b1) {
    asm volatile("mma.sync.aligned.m16n8k16.row.col.f32.bf16.bf16.f32 {%0,%1,%2,%3}, {%4,%5,%6,%7}, {%8,%9}, {%0,%1,%2,%3};"
        : "+f"(d[0]), "+f"(d[1]), "+f"(d[2]), "+f"(d[3]) : "r"(a0), "r"(a1), "r"(a2), "r"(a3), "r"(b0), "r"(b1));
}
__device__ __forceinline__ uint32_t awake_zero() {
    uint32_t r;
    asm volatile("{\n.reg .f32 d<4>;\nmma.sync.aligned.m16n8k8.row.col.f32.bf16.bf16.f32 {d0,d1,d2,d3}, {%1,%1}, {%1}, {%2,%2,%2,%2};\nmov.b32 %0, d0;\n}" : "=r"(r) : "r"(0), "f"(0.f));
    return r;
}
__device__ __forceinline__ void mbar_wait_awake(uint32_t bar, uint32_t parity) {
    #pragma unroll 1
    for (int it = 0; it < POLL_MAX; it++) {
        uint32_t ok;
        asm volatile("{\n.reg .pred p;\nmbarrier.try_wait.parity.shared::cta.b64 p, [%1], %2;\nselp.u32 %0, 0, 1, p;\n}" : "=r"(ok) : "r"(bar), "r"(parity) : "memory");
        if (__all_sync(0xffffffffu, ok == 0)) break;
        it += awake_zero();
    }
}
__device__ __forceinline__ uint4 lds128(uint32_t a) { uint4 v; asm volatile("ld.shared.v4.b32 {%0,%1,%2,%3}, [%4];" : "=r"(v.x), "=r"(v.y), "=r"(v.z), "=r"(v.w) : "r"(a) : "memory"); return v; }
__device__ __forceinline__ uint32_t lds32(uint32_t a) { uint32_t v; asm volatile("ld.shared.b32 %0, [%1];" : "=r"(v) : "r"(a) : "memory"); return v; }
__device__ __forceinline__ uint2 lds64(uint32_t a) { uint2 v; asm volatile("ld.shared.v2.b32 {%0,%1}, [%2];" : "=r"(v.x), "=r"(v.y) : "r"(a) : "memory"); return v; }
__device__ __forceinline__ float ldsf(uint32_t a) { float v; asm volatile("ld.shared.f32 %0, [%1];" : "=f"(v) : "r"(a) : "memory"); return v; }
__device__ __forceinline__ void sts128(uint32_t a, uint4 v) { asm volatile("st.shared.v4.b32 [%0], {%1,%2,%3,%4};" :: "r"(a), "r"(v.x), "r"(v.y), "r"(v.z), "r"(v.w) : "memory"); }
__device__ __forceinline__ void sts64(uint32_t a, uint32_t x, uint32_t y) { asm volatile("st.shared.v2.b32 [%0], {%1,%2};" :: "r"(a), "r"(x), "r"(y) : "memory"); }
__device__ __forceinline__ void sts32(uint32_t a, uint32_t x) { asm volatile("st.shared.b32 [%0], %1;" :: "r"(a), "r"(x) : "memory"); }
__device__ __forceinline__ void stsf(uint32_t a, float x) { asm volatile("st.shared.f32 [%0], %1;" :: "r"(a), "f"(x) : "memory"); }
__device__ __forceinline__ float u2f(uint32_t v) { return __uint_as_float(v); }
__device__ __forceinline__ uint32_t f2u(float v) { return __float_as_uint(v); }

__device__ __forceinline__ uint32_t ldg32(const void* p) { uint32_t v; asm volatile("ld.global.nc.b32 %0, [%1];" : "=r"(v) : "l"(p)); return v; }
__device__ __forceinline__ void stg128(void* p, uint4 v) { asm volatile("st.global.v4.b32 [%0], {%1,%2,%3,%4};" :: "l"(p), "r"(v.x), "r"(v.y), "r"(v.z), "r"(v.w) : "memory"); }
__device__ __forceinline__ void stg_zero(void* p) { stg128(p, make_uint4(0, 0, 0, 0)); }
__device__ __forceinline__ void fence_gpu() { asm volatile("fence.release.gpu;" ::: "memory"); }
__device__ __forceinline__ void st_ll(uint4* p, uint32_t x, uint32_t y, uint32_t z, uint32_t w) {
    asm volatile("st.relaxed.gpu.global.v4.b32 [%0], {%1,%2,%3,%4};" :: "l"(p), "r"(x), "r"(y), "r"(z), "r"(w) : "memory");
}
__device__ __forceinline__ uint4 ld_ll(const uint4* p) {
    uint4 v;
    asm volatile("ld.relaxed.gpu.global.v4.b32 {%0,%1,%2,%3}, [%4];" : "=r"(v.x), "=r"(v.y), "=r"(v.z), "=r"(v.w) : "l"(p) : "memory");
    return v;
}
template<uint32_t LUT> __device__ __forceinline__ uint32_t lop3(uint32_t a, uint32_t b, uint32_t c) { uint32_t d; asm("lop3.b32 %0, %1, %2, %3, %4;" : "=r"(d) : "r"(a), "r"(b), "r"(c), "n"(LUT)); return d; }
__device__ __forceinline__ uint32_t tag_bad(uint32_t bad, uint32_t w, uint32_t tag) { return lop3<0xF6>(bad, w, tag); }
__device__ __forceinline__ void st_ll4(uint4* p, float a, float b, float c, float d, uint32_t tag) { st_ll(p, f2u(a), f2u(b), f2u(c), lop3<0xD8>(f2u(d), tag, 3u)); }
__device__ __forceinline__ unsigned ld_rlx(const void* p) { unsigned v; asm volatile("ld.relaxed.gpu.global.u32 %0, [%1];" : "=r"(v) : "l"(p) : "memory"); return v; }
__device__ __forceinline__ void st_flag(uint4* p, uint32_t tag, uint32_t v, int lane) { if (lane < 2) st_ll(p + lane, tag, v, tag, v); }
__device__ __forceinline__ uint2 ld_flag(const uint4* p) { uint2 v; asm volatile("ld.relaxed.gpu.global.v2.b32 {%0,%1}, [%2];" : "=r"(v.x), "=r"(v.y) : "l"(p) : "memory"); return v; }
__device__ __forceinline__ uint32_t poll_flags(const uint4* f, uint32_t tag) {
    uint2 v = make_uint2(0, 0);
    #pragma unroll 1
    for (int it = 0; it < POLL_MAX; it++) {
        if (v.x != tag) v = ld_flag(f);
        if (__all_sync(0xffffffffu, v.x == tag)) break;
    }
    return v.y;
}
template<int Z> __device__ __forceinline__ uint32_t ll_bad(uint32_t bad, const uint4& v, uint32_t tag) {
    bad = tag_bad(bad, v.w, tag);
    return Z && lop3<0x80>(v.x, v.y, v.z) == ~0u ? 1u : bad;
}
template<int N, int Z, uint32_t M = ~0u, int AW = 0> __device__ __forceinline__ void poll_words(uint4 (&v)[N], const uint4* p, int stride, uint32_t tag) {
    #pragma unroll 1
    for (int it = 0; it < POLL_MAX; it++) {
        uint32_t bad = 0;
        #pragma unroll
        for (int i = 0; i < N; i++) v[i] = ld_ll(p + i * stride);
        #pragma unroll
        for (int i = 0; i < N; i++) bad = ll_bad<Z>(bad, v[i], tag);
        if (__all_sync(0xffffffffu, !(bad & M))) break;
        if (AW) it += awake_zero();
    }
}
constexpr uint32_t ONE2 = 0x3F803F80u;
__device__ __forceinline__ uint32_t pack2(float lo, float hi) { uint32_t d; asm("cvt.rn.bf16x2.f32 %0, %1, %2;" : "=r"(d) : "f"(hi), "f"(lo)); return d; }
__device__ __forceinline__ float bf_lo(uint32_t v) { return u2f(v << 16); }
__device__ __forceinline__ float bf_hi(uint32_t v) { return u2f(v & 0xffff0000u); }
__device__ __forceinline__ float rbf(float x) { return bf_lo(pack2(x, 0.f)); }
__device__ __forceinline__ uint32_t hsub2(uint32_t a, uint32_t b) { uint32_t d; asm("sub.rn.bf16x2 %0, %1, %2;" : "=r"(d) : "r"(a), "r"(b)); return d; }
__device__ __forceinline__ uint32_t hadd2(uint32_t a, uint32_t b) { uint32_t d; asm("add.rn.bf16x2 %0, %1, %2;" : "=r"(d) : "r"(a), "r"(b)); return d; }
__device__ __forceinline__ uint32_t hmul2(uint32_t a, uint32_t b) { uint32_t d; asm("mul.rn.bf16x2 %0, %1, %2;" : "=r"(d) : "r"(a), "r"(b)); return d; }
__device__ __forceinline__ uint32_t hfma2(uint32_t a, uint32_t b, uint32_t c) { uint32_t d; asm("fma.rn.bf16x2 %0, %1, %2, %3;" : "=r"(d) : "r"(a), "r"(b), "r"(c)); return d; }
__device__ __forceinline__ uint32_t hmax2(uint32_t a, uint32_t b) { uint32_t d; asm("max.bf16x2 %0, %1, %2;" : "=r"(d) : "r"(a), "r"(b)); return d; }
__device__ __forceinline__ uint32_t hmin2(uint32_t a, uint32_t b) { uint32_t d; asm("min.bf16x2 %0, %1, %2;" : "=r"(d) : "r"(a), "r"(b)); return d; }
__device__ __forceinline__ float ex2(float x) { float y; asm("ex2.approx.ftz.f32 %0, %1;" : "=f"(y) : "f"(x)); return y; }
__device__ __forceinline__ float rcp(float x) { float y; asm("rcp.approx.ftz.f32 %0, %1;" : "=f"(y) : "f"(x)); return y; }
__device__ __forceinline__ float shfl_x(float v, int m) { return __shfl_xor_sync(0xffffffffu, v, m); }
__device__ __forceinline__ uint32_t hdiv2(uint32_t d, uint32_t rh, uint32_t rl) { return hfma2(d, rh, hmul2(d, rl)); }
__device__ __forceinline__ void split_rcp(float r, uint32_t& rh, uint32_t& rl) { rh = pack2(r, r); const float l = r - bf_lo(rh); rl = pack2(l, l); }
__device__ __forceinline__ uint32_t lnmod(uint32_t x, uint32_t m, uint32_t rh, uint32_t rl, uint32_t a, uint32_t s) { return hadd2(hmul2(hdiv2(hsub2(x, m), rh, rl), a), s); }
__device__ __forceinline__ void ln_final(float s1, float s2, uint32_t& m2, float& rinv) {
    const float mean = s1 * (1.0f / 1024.0f), var = fmaf(-mean, mean, s2 * (1.0f / 1024.0f));
    m2 = pack2(mean, mean);
    float sd;
    asm("sqrt.approx.ftz.f32 %0, %1;" : "=f"(sd) : "f"(rbf(rbf(fmaxf(var, 0.f)) + 1e-5f)));
    rinv = rcp(rbf(sd));
}
__device__ __forceinline__ float sigmoid_f(float x) { return rcp(1.0f + ex2(-1.4426950408889634f * x)); }
__device__ __forceinline__ uint32_t silu2(uint32_t v) { return pack2(bf_lo(v) * sigmoid_f(bf_lo(v)), bf_hi(v) * sigmoid_f(bf_hi(v))); }
__device__ __forceinline__ uint32_t f2key(float f) { uint32_t u = f2u(f); return (u & 0x80000000u) ? ~u : (u | 0x80000000u); }
__device__ __forceinline__ float key2f(uint32_t k) { return u2f((k & 0x80000000u) ? k ^ 0x80000000u : ~k); }
template<int N> __device__ __forceinline__ void top2(uint32_t (&k)[N], uint32_t& b0, uint32_t& b1) {
    uint32_t m = k[0];
    #pragma unroll
    for (int i = 1; i < N; i++) m = max(m, k[i]);
    b0 = __reduce_max_sync(0xffffffffu, m);
    m = 0;
    #pragma unroll
    for (int i = 0; i < N; i++) m = max(m, k[i] == b0 ? 0u : k[i]);
    b1 = __reduce_max_sync(0xffffffffu, m);
}
template<class T> __device__ __forceinline__ T sel4(int c, T a0, T a1, T a2, T a3) { return (c & 2) ? ((c & 1) ? a3 : a2) : ((c & 1) ? a1 : a0); }

__device__ __forceinline__ void fm_max(const float (&a)[16], uint32_t* p, uint32_t* mm) {
    #pragma unroll
    for (int i = 0; i < 8; i++) p[i] = pack2(a[2 * i], a[2 * i + 1]);
    #pragma unroll
    for (int h = 0; h < 2; h++) {
        const uint32_t mx = hmax2(hmax2(p[h], p[2 + h]), hmax2(p[4 + h], p[6 + h]));
        const uint32_t mn = hmin2(hmin2(p[h], p[2 + h]), hmin2(p[4 + h], p[6 + h])) ^ 0x80008000u;
        mm[h] = hmax2(__byte_perm(mx, mn, 0x5410), __byte_perm(mx, mn, 0x7632));
    }
    #pragma unroll
    for (int d = 1; d <= 2; d++) { mm[0] = hmax2(mm[0], __shfl_xor_sync(0xffffffffu, mm[0], d)); mm[1] = hmax2(mm[1], __shfl_xor_sync(0xffffffffu, mm[1], d)); }
}
constexpr float LOG2E = 1.4426950408889634f;
__device__ __forceinline__ void fm_pos(const uint32_t* p, const uint32_t* mm, float (&e)[32]) {
    #pragma unroll
    for (int h = 0; h < 2; h++) {
        const float cp = -bf_lo(mm[h]) * LOG2E;
        #pragma unroll
        for (int j = 0; j < 4; j++) {
            const float f0 = bf_lo(p[2 * j + h]), f1 = bf_hi(p[2 * j + h]);
            e[8 * h + 2 * j] = ex2(fmaf(f0, LOG2E, cp)); e[8 * h + 2 * j + 1] = ex2(fmaf(f1, LOG2E, cp));
            e[16 + 8 * h + 2 * j] = f0; e[16 + 8 * h + 2 * j + 1] = f1;
        }
    }
}
__device__ __forceinline__ void fm_neg(const uint32_t* mm, float nl, float (&e)[32]) {
    #pragma unroll
    for (int i = 16; i < 32; i++) e[i] = ex2(fmaf(e[i], -LOG2E, bf_hi(mm[(i >> 3) & 1]) * (i < 16 + NFREE ? -LOG2E : nl)));
}
__device__ __forceinline__ void fm_norm(const float (&e)[32], uint32_t* ph) {
    float s[4];
    #pragma unroll
    for (int k = 0; k < 4; k++) s[k] = ((e[8 * k] + e[8 * k + 1]) + (e[8 * k + 2] + e[8 * k + 3])) + ((e[8 * k + 4] + e[8 * k + 5]) + (e[8 * k + 6] + e[8 * k + 7]));
    #pragma unroll
    for (int k = 0; k < 4; k++) s[k] += shfl_x(s[k], 1);
    #pragma unroll
    for (int k = 0; k < 4; k++) s[k] = rcp(s[k] + shfl_x(s[k], 2));
    #pragma unroll
    for (int k = 0; k < 4; k++)
        #pragma unroll
        for (int j = 0; j < 4; j++) ph[8 * (k >> 1) + 2 * j + (k & 1)] = pack2(e[8 * k + 2 * j] * s[k], e[8 * k + 2 * j + 1] * s[k]);
}
template<class T> __device__ __forceinline__ T* pin_ptr(T* p) { asm volatile("" : "+l"(p) :: "memory"); return p; }
template<int N> __device__ __forceinline__ void pin(uint32_t* d) {
    #pragma unroll
    for (int i = 0; i < N; i++) asm volatile("" : "+r"(d[i]) :: "memory");
}

template<uint32_t BO, uint32_t BH> __device__ __forceinline__ void mma192_rs(float (&d)[96], const uint32_t* a, uint32_t blo) {
  asm volatile("{\n.reg .pred p;\n.reg .b32 ta, tb;\n.reg .b64 da, db;\nadd.u32 tb, %100, %101;\nmov.b64 db, {tb, %102};\nsetp.ne.b32 p, 1, 0;\n"
    "wgmma.mma_async.sync.aligned.m64n192k16.f32.bf16.bf16 {%0, %1, %2, %3, %4, %5, %6, %7, %8, %9, %10, %11, %12, %13, %14, %15, %16, %17, %18, %19, %20, %21, %22, %23, %24, %25, %26, %27, %28, %29, %30, %31, %32, %33, %34, %35, %36, %37, %38, %39, %40, %41, %42, %43, %44, %45, %46, %47, %48, %49, %50, %51, %52, %53, %54, %55, %56, %57, %58, %59, %60, %61, %62, %63, %64, %65, %66, %67, %68, %69, %70, %71, %72, %73, %74, %75, %76, %77, %78, %79, %80, %81, %82, %83, %84, %85, %86, %87, %88, %89, %90, %91, %92, %93, %94, %95}, {%96,%97,%98,%99}, db, p, 1, 1, 1;\n}\n"
    : "+f"(d[0]), "+f"(d[1]), "+f"(d[2]), "+f"(d[3]), "+f"(d[4]), "+f"(d[5]), "+f"(d[6]), "+f"(d[7]), "+f"(d[8]), "+f"(d[9]), "+f"(d[10]), "+f"(d[11]), "+f"(d[12]), "+f"(d[13]), "+f"(d[14]), "+f"(d[15]), "+f"(d[16]), "+f"(d[17]), "+f"(d[18]), "+f"(d[19]), "+f"(d[20]), "+f"(d[21]), "+f"(d[22]), "+f"(d[23]), "+f"(d[24]), "+f"(d[25]), "+f"(d[26]), "+f"(d[27]), "+f"(d[28]), "+f"(d[29]), "+f"(d[30]), "+f"(d[31]), "+f"(d[32]), "+f"(d[33]), "+f"(d[34]), "+f"(d[35]), "+f"(d[36]), "+f"(d[37]), "+f"(d[38]), "+f"(d[39]), "+f"(d[40]), "+f"(d[41]), "+f"(d[42]), "+f"(d[43]), "+f"(d[44]), "+f"(d[45]), "+f"(d[46]), "+f"(d[47]), "+f"(d[48]), "+f"(d[49]), "+f"(d[50]), "+f"(d[51]), "+f"(d[52]), "+f"(d[53]), "+f"(d[54]), "+f"(d[55]), "+f"(d[56]), "+f"(d[57]), "+f"(d[58]), "+f"(d[59]), "+f"(d[60]), "+f"(d[61]), "+f"(d[62]), "+f"(d[63]), "+f"(d[64]), "+f"(d[65]), "+f"(d[66]), "+f"(d[67]), "+f"(d[68]), "+f"(d[69]), "+f"(d[70]), "+f"(d[71]), "+f"(d[72]), "+f"(d[73]), "+f"(d[74]), "+f"(d[75]), "+f"(d[76]), "+f"(d[77]), "+f"(d[78]), "+f"(d[79]), "+f"(d[80]), "+f"(d[81]), "+f"(d[82]), "+f"(d[83]), "+f"(d[84]), "+f"(d[85]), "+f"(d[86]), "+f"(d[87]), "+f"(d[88]), "+f"(d[89]), "+f"(d[90]), "+f"(d[91]), "+f"(d[92]), "+f"(d[93]), "+f"(d[94]), "+f"(d[95])
    : "r"(a[0]), "r"(a[1]), "r"(a[2]), "r"(a[3]), "r"(blo), "n"(BO), "n"(BH));
}
template<uint32_t BO, uint32_t BH> __device__ __forceinline__ void mma192_rsp(float (&d)[96], const uint32_t* a, uint32_t blo, int sc) {
  asm volatile("{\n.reg .pred p;\n.reg .b32 ta, tb;\n.reg .b64 da, db;\nadd.u32 tb, %100, %101;\nmov.b64 db, {tb, %102};\nsetp.ne.b32 p, %103, 0;\n"
    "wgmma.mma_async.sync.aligned.m64n192k16.f32.bf16.bf16 {%0, %1, %2, %3, %4, %5, %6, %7, %8, %9, %10, %11, %12, %13, %14, %15, %16, %17, %18, %19, %20, %21, %22, %23, %24, %25, %26, %27, %28, %29, %30, %31, %32, %33, %34, %35, %36, %37, %38, %39, %40, %41, %42, %43, %44, %45, %46, %47, %48, %49, %50, %51, %52, %53, %54, %55, %56, %57, %58, %59, %60, %61, %62, %63, %64, %65, %66, %67, %68, %69, %70, %71, %72, %73, %74, %75, %76, %77, %78, %79, %80, %81, %82, %83, %84, %85, %86, %87, %88, %89, %90, %91, %92, %93, %94, %95}, {%96,%97,%98,%99}, db, p, 1, 1, 1;\n}\n"
    : "+f"(d[0]), "+f"(d[1]), "+f"(d[2]), "+f"(d[3]), "+f"(d[4]), "+f"(d[5]), "+f"(d[6]), "+f"(d[7]), "+f"(d[8]), "+f"(d[9]), "+f"(d[10]), "+f"(d[11]), "+f"(d[12]), "+f"(d[13]), "+f"(d[14]), "+f"(d[15]), "+f"(d[16]), "+f"(d[17]), "+f"(d[18]), "+f"(d[19]), "+f"(d[20]), "+f"(d[21]), "+f"(d[22]), "+f"(d[23]), "+f"(d[24]), "+f"(d[25]), "+f"(d[26]), "+f"(d[27]), "+f"(d[28]), "+f"(d[29]), "+f"(d[30]), "+f"(d[31]), "+f"(d[32]), "+f"(d[33]), "+f"(d[34]), "+f"(d[35]), "+f"(d[36]), "+f"(d[37]), "+f"(d[38]), "+f"(d[39]), "+f"(d[40]), "+f"(d[41]), "+f"(d[42]), "+f"(d[43]), "+f"(d[44]), "+f"(d[45]), "+f"(d[46]), "+f"(d[47]), "+f"(d[48]), "+f"(d[49]), "+f"(d[50]), "+f"(d[51]), "+f"(d[52]), "+f"(d[53]), "+f"(d[54]), "+f"(d[55]), "+f"(d[56]), "+f"(d[57]), "+f"(d[58]), "+f"(d[59]), "+f"(d[60]), "+f"(d[61]), "+f"(d[62]), "+f"(d[63]), "+f"(d[64]), "+f"(d[65]), "+f"(d[66]), "+f"(d[67]), "+f"(d[68]), "+f"(d[69]), "+f"(d[70]), "+f"(d[71]), "+f"(d[72]), "+f"(d[73]), "+f"(d[74]), "+f"(d[75]), "+f"(d[76]), "+f"(d[77]), "+f"(d[78]), "+f"(d[79]), "+f"(d[80]), "+f"(d[81]), "+f"(d[82]), "+f"(d[83]), "+f"(d[84]), "+f"(d[85]), "+f"(d[86]), "+f"(d[87]), "+f"(d[88]), "+f"(d[89]), "+f"(d[90]), "+f"(d[91]), "+f"(d[92]), "+f"(d[93]), "+f"(d[94]), "+f"(d[95])
    : "r"(a[0]), "r"(a[1]), "r"(a[2]), "r"(a[3]), "r"(blo), "n"(BO), "n"(BH), "r"(sc));
}
template<uint32_t BO, uint32_t BH> __device__ __forceinline__ void mma32_rs(float (&d)[16], const uint32_t* a, uint32_t blo) {
  asm volatile("{\n.reg .pred p;\n.reg .b32 ta, tb;\n.reg .b64 da, db;\nadd.u32 tb, %20, %21;\nmov.b64 db, {tb, %22};\nsetp.ne.b32 p, 1, 0;\n"
    "wgmma.mma_async.sync.aligned.m64n32k16.f32.bf16.bf16 {%0, %1, %2, %3, %4, %5, %6, %7, %8, %9, %10, %11, %12, %13, %14, %15}, {%16,%17,%18,%19}, db, p, 1, 1, 1;\n}\n"
    : "+f"(d[0]), "+f"(d[1]), "+f"(d[2]), "+f"(d[3]), "+f"(d[4]), "+f"(d[5]), "+f"(d[6]), "+f"(d[7]), "+f"(d[8]), "+f"(d[9]), "+f"(d[10]), "+f"(d[11]), "+f"(d[12]), "+f"(d[13]), "+f"(d[14]), "+f"(d[15])
    : "r"(a[0]), "r"(a[1]), "r"(a[2]), "r"(a[3]), "r"(blo), "n"(BO), "n"(BH));
}
template<uint32_t BO, uint32_t BH> __device__ __forceinline__ void mma32_rs0(float (&d)[16], const uint32_t* a, uint32_t blo) {
  asm volatile("{\n.reg .pred p;\n.reg .b32 ta, tb;\n.reg .b64 da, db;\nadd.u32 tb, %20, %21;\nmov.b64 db, {tb, %22};\nsetp.ne.b32 p, 0, 0;\n"
    "wgmma.mma_async.sync.aligned.m64n32k16.f32.bf16.bf16 {%0, %1, %2, %3, %4, %5, %6, %7, %8, %9, %10, %11, %12, %13, %14, %15}, {%16,%17,%18,%19}, db, p, 1, 1, 1;\n}\n"
    : "=f"(d[0]), "=f"(d[1]), "=f"(d[2]), "=f"(d[3]), "=f"(d[4]), "=f"(d[5]), "=f"(d[6]), "=f"(d[7]), "=f"(d[8]), "=f"(d[9]), "=f"(d[10]), "=f"(d[11]), "=f"(d[12]), "=f"(d[13]), "=f"(d[14]), "=f"(d[15])
    : "r"(a[0]), "r"(a[1]), "r"(a[2]), "r"(a[3]), "r"(blo), "n"(BO), "n"(BH));
}
template<uint32_t BO, uint32_t BH> __device__ __forceinline__ void mma40_rs(float (&d)[20], const uint32_t* a, uint32_t blo) {
  asm volatile("{\n.reg .pred p;\n.reg .b32 ta, tb;\n.reg .b64 da, db;\nadd.u32 tb, %24, %25;\nmov.b64 db, {tb, %26};\nsetp.ne.b32 p, 1, 0;\n"
    "wgmma.mma_async.sync.aligned.m64n40k16.f32.bf16.bf16 {%0, %1, %2, %3, %4, %5, %6, %7, %8, %9, %10, %11, %12, %13, %14, %15, %16, %17, %18, %19}, {%20,%21,%22,%23}, db, p, 1, 1, 1;\n}\n"
    : "+f"(d[0]), "+f"(d[1]), "+f"(d[2]), "+f"(d[3]), "+f"(d[4]), "+f"(d[5]), "+f"(d[6]), "+f"(d[7]), "+f"(d[8]), "+f"(d[9]), "+f"(d[10]), "+f"(d[11]), "+f"(d[12]), "+f"(d[13]), "+f"(d[14]), "+f"(d[15]), "+f"(d[16]), "+f"(d[17]), "+f"(d[18]), "+f"(d[19])
    : "r"(a[0]), "r"(a[1]), "r"(a[2]), "r"(a[3]), "r"(blo), "n"(BO), "n"(BH));
}
template<uint32_t BO, uint32_t BH> __device__ __forceinline__ void mma40_rs0(float (&d)[20], const uint32_t* a, uint32_t blo) {
  asm volatile("{\n.reg .pred p;\n.reg .b32 ta, tb;\n.reg .b64 da, db;\nadd.u32 tb, %24, %25;\nmov.b64 db, {tb, %26};\nsetp.ne.b32 p, 0, 0;\n"
    "wgmma.mma_async.sync.aligned.m64n40k16.f32.bf16.bf16 {%0, %1, %2, %3, %4, %5, %6, %7, %8, %9, %10, %11, %12, %13, %14, %15, %16, %17, %18, %19}, {%20,%21,%22,%23}, db, p, 1, 1, 1;\n}\n"
    : "=f"(d[0]), "=f"(d[1]), "=f"(d[2]), "=f"(d[3]), "=f"(d[4]), "=f"(d[5]), "=f"(d[6]), "=f"(d[7]), "=f"(d[8]), "=f"(d[9]), "=f"(d[10]), "=f"(d[11]), "=f"(d[12]), "=f"(d[13]), "=f"(d[14]), "=f"(d[15]), "=f"(d[16]), "=f"(d[17]), "=f"(d[18]), "=f"(d[19])
    : "r"(a[0]), "r"(a[1]), "r"(a[2]), "r"(a[3]), "r"(blo), "n"(BO), "n"(BH));
}
template<uint32_t AO, uint32_t AH, uint32_t BO, uint32_t BH> __device__ __forceinline__ void mma40_tt(float (&d)[20], uint32_t alo, uint32_t blo) {
  asm volatile("{\n.reg .pred p;\n.reg .b32 ta, tb;\n.reg .b64 da, db;\nadd.u32 ta, %20, %21;\nmov.b64 da, {ta, %22};\nadd.u32 tb, %23, %24;\nmov.b64 db, {tb, %25};\nsetp.ne.b32 p, 1, 0;\n"
    "wgmma.mma_async.sync.aligned.m64n40k16.f32.bf16.bf16 {%0, %1, %2, %3, %4, %5, %6, %7, %8, %9, %10, %11, %12, %13, %14, %15, %16, %17, %18, %19}, da, db, p, 1, 1, 1, 1;\n}\n"
    : "+f"(d[0]), "+f"(d[1]), "+f"(d[2]), "+f"(d[3]), "+f"(d[4]), "+f"(d[5]), "+f"(d[6]), "+f"(d[7]), "+f"(d[8]), "+f"(d[9]), "+f"(d[10]), "+f"(d[11]), "+f"(d[12]), "+f"(d[13]), "+f"(d[14]), "+f"(d[15]), "+f"(d[16]), "+f"(d[17]), "+f"(d[18]), "+f"(d[19])
    : "r"(alo), "n"(AO), "n"(AH), "r"(blo), "n"(BO), "n"(BH));
}
template<uint32_t AO, uint32_t AH, uint32_t BO, uint32_t BH> __device__ __forceinline__ void mma40_tt0(float (&d)[20], uint32_t alo, uint32_t blo) {
  asm volatile("{\n.reg .pred p;\n.reg .b32 ta, tb;\n.reg .b64 da, db;\nadd.u32 ta, %20, %21;\nmov.b64 da, {ta, %22};\nadd.u32 tb, %23, %24;\nmov.b64 db, {tb, %25};\nsetp.ne.b32 p, 0, 0;\n"
    "wgmma.mma_async.sync.aligned.m64n40k16.f32.bf16.bf16 {%0, %1, %2, %3, %4, %5, %6, %7, %8, %9, %10, %11, %12, %13, %14, %15, %16, %17, %18, %19}, da, db, p, 1, 1, 1, 1;\n}\n"
    : "=f"(d[0]), "=f"(d[1]), "=f"(d[2]), "=f"(d[3]), "=f"(d[4]), "=f"(d[5]), "=f"(d[6]), "=f"(d[7]), "=f"(d[8]), "=f"(d[9]), "=f"(d[10]), "=f"(d[11]), "=f"(d[12]), "=f"(d[13]), "=f"(d[14]), "=f"(d[15]), "=f"(d[16]), "=f"(d[17]), "=f"(d[18]), "=f"(d[19])
    : "r"(alo), "n"(AO), "n"(AH), "r"(blo), "n"(BO), "n"(BH));
}
template<uint32_t AO, uint32_t AH, uint32_t BO, uint32_t BH> __device__ __forceinline__ void mma8_tn(float (&d)[4], uint32_t alo, uint32_t blo) {
  asm volatile("{\n.reg .pred p;\n.reg .b32 ta, tb;\n.reg .b64 da, db;\nadd.u32 ta, %4, %5;\nmov.b64 da, {ta, %6};\nadd.u32 tb, %7, %8;\nmov.b64 db, {tb, %9};\nsetp.ne.b32 p, 1, 0;\n"
    "wgmma.mma_async.sync.aligned.m64n8k16.f32.bf16.bf16 {%0, %1, %2, %3}, da, db, p, 1, 1, 1, 0;\n}\n"
    : "+f"(d[0]), "+f"(d[1]), "+f"(d[2]), "+f"(d[3])
    : "r"(alo), "n"(AO), "n"(AH), "r"(blo), "n"(BO), "n"(BH));
}
template<uint32_t AO, uint32_t AH, uint32_t BO, uint32_t BH> __device__ __forceinline__ void mma8_tn0(float (&d)[4], uint32_t alo, uint32_t blo) {
  asm volatile("{\n.reg .pred p;\n.reg .b32 ta, tb;\n.reg .b64 da, db;\nadd.u32 ta, %4, %5;\nmov.b64 da, {ta, %6};\nadd.u32 tb, %7, %8;\nmov.b64 db, {tb, %9};\nsetp.ne.b32 p, 0, 0;\n"
    "wgmma.mma_async.sync.aligned.m64n8k16.f32.bf16.bf16 {%0, %1, %2, %3}, da, db, p, 1, 1, 1, 0;\n}\n"
    : "=f"(d[0]), "=f"(d[1]), "=f"(d[2]), "=f"(d[3])
    : "r"(alo), "n"(AO), "n"(AH), "r"(blo), "n"(BO), "n"(BH));
}
template<uint32_t AO, uint32_t AH, uint32_t BO, uint32_t BH> __device__ __forceinline__ void mma128_ss(float (&d)[64], uint32_t alo, uint32_t blo) {
  asm volatile("{\n.reg .pred p;\n.reg .b32 ta, tb;\n.reg .b64 da, db;\nadd.u32 ta, %64, %65;\nmov.b64 da, {ta, %66};\nadd.u32 tb, %67, %68;\nmov.b64 db, {tb, %69};\nsetp.ne.b32 p, 1, 0;\n"
    "wgmma.mma_async.sync.aligned.m64n128k16.f32.bf16.bf16 {%0, %1, %2, %3, %4, %5, %6, %7, %8, %9, %10, %11, %12, %13, %14, %15, %16, %17, %18, %19, %20, %21, %22, %23, %24, %25, %26, %27, %28, %29, %30, %31, %32, %33, %34, %35, %36, %37, %38, %39, %40, %41, %42, %43, %44, %45, %46, %47, %48, %49, %50, %51, %52, %53, %54, %55, %56, %57, %58, %59, %60, %61, %62, %63}, da, db, p, 1, 1, 0, 1;\n}\n"
    : "+f"(d[0]), "+f"(d[1]), "+f"(d[2]), "+f"(d[3]), "+f"(d[4]), "+f"(d[5]), "+f"(d[6]), "+f"(d[7]), "+f"(d[8]), "+f"(d[9]), "+f"(d[10]), "+f"(d[11]), "+f"(d[12]), "+f"(d[13]), "+f"(d[14]), "+f"(d[15]), "+f"(d[16]), "+f"(d[17]), "+f"(d[18]), "+f"(d[19]), "+f"(d[20]), "+f"(d[21]), "+f"(d[22]), "+f"(d[23]), "+f"(d[24]), "+f"(d[25]), "+f"(d[26]), "+f"(d[27]), "+f"(d[28]), "+f"(d[29]), "+f"(d[30]), "+f"(d[31]), "+f"(d[32]), "+f"(d[33]), "+f"(d[34]), "+f"(d[35]), "+f"(d[36]), "+f"(d[37]), "+f"(d[38]), "+f"(d[39]), "+f"(d[40]), "+f"(d[41]), "+f"(d[42]), "+f"(d[43]), "+f"(d[44]), "+f"(d[45]), "+f"(d[46]), "+f"(d[47]), "+f"(d[48]), "+f"(d[49]), "+f"(d[50]), "+f"(d[51]), "+f"(d[52]), "+f"(d[53]), "+f"(d[54]), "+f"(d[55]), "+f"(d[56]), "+f"(d[57]), "+f"(d[58]), "+f"(d[59]), "+f"(d[60]), "+f"(d[61]), "+f"(d[62]), "+f"(d[63])
    : "r"(alo), "n"(AO), "n"(AH), "r"(blo), "n"(BO), "n"(BH));
}
template<uint32_t AO, uint32_t AH, uint32_t BO, uint32_t BH> __device__ __forceinline__ void mma128_ss0(float (&d)[64], uint32_t alo, uint32_t blo) {
  asm volatile("{\n.reg .pred p;\n.reg .b32 ta, tb;\n.reg .b64 da, db;\nadd.u32 ta, %64, %65;\nmov.b64 da, {ta, %66};\nadd.u32 tb, %67, %68;\nmov.b64 db, {tb, %69};\nsetp.ne.b32 p, 0, 0;\n"
    "wgmma.mma_async.sync.aligned.m64n128k16.f32.bf16.bf16 {%0, %1, %2, %3, %4, %5, %6, %7, %8, %9, %10, %11, %12, %13, %14, %15, %16, %17, %18, %19, %20, %21, %22, %23, %24, %25, %26, %27, %28, %29, %30, %31, %32, %33, %34, %35, %36, %37, %38, %39, %40, %41, %42, %43, %44, %45, %46, %47, %48, %49, %50, %51, %52, %53, %54, %55, %56, %57, %58, %59, %60, %61, %62, %63}, da, db, p, 1, 1, 0, 1;\n}\n"
    : "=f"(d[0]), "=f"(d[1]), "=f"(d[2]), "=f"(d[3]), "=f"(d[4]), "=f"(d[5]), "=f"(d[6]), "=f"(d[7]), "=f"(d[8]), "=f"(d[9]), "=f"(d[10]), "=f"(d[11]), "=f"(d[12]), "=f"(d[13]), "=f"(d[14]), "=f"(d[15]), "=f"(d[16]), "=f"(d[17]), "=f"(d[18]), "=f"(d[19]), "=f"(d[20]), "=f"(d[21]), "=f"(d[22]), "=f"(d[23]), "=f"(d[24]), "=f"(d[25]), "=f"(d[26]), "=f"(d[27]), "=f"(d[28]), "=f"(d[29]), "=f"(d[30]), "=f"(d[31]), "=f"(d[32]), "=f"(d[33]), "=f"(d[34]), "=f"(d[35]), "=f"(d[36]), "=f"(d[37]), "=f"(d[38]), "=f"(d[39]), "=f"(d[40]), "=f"(d[41]), "=f"(d[42]), "=f"(d[43]), "=f"(d[44]), "=f"(d[45]), "=f"(d[46]), "=f"(d[47]), "=f"(d[48]), "=f"(d[49]), "=f"(d[50]), "=f"(d[51]), "=f"(d[52]), "=f"(d[53]), "=f"(d[54]), "=f"(d[55]), "=f"(d[56]), "=f"(d[57]), "=f"(d[58]), "=f"(d[59]), "=f"(d[60]), "=f"(d[61]), "=f"(d[62]), "=f"(d[63])
    : "r"(alo), "n"(AO), "n"(AH), "r"(blo), "n"(BO), "n"(BH));
}
template<uint32_t AO, uint32_t AH, uint32_t BO, uint32_t BH> __device__ __forceinline__ void mma128_ssp(float (&d)[64], uint32_t alo, uint32_t blo, int sc) {
  asm volatile("{\n.reg .pred p;\n.reg .b32 ta, tb;\n.reg .b64 da, db;\nadd.u32 ta, %64, %65;\nmov.b64 da, {ta, %66};\nadd.u32 tb, %67, %68;\nmov.b64 db, {tb, %69};\nsetp.ne.b32 p, %70, 0;\n"
    "wgmma.mma_async.sync.aligned.m64n128k16.f32.bf16.bf16 {%0, %1, %2, %3, %4, %5, %6, %7, %8, %9, %10, %11, %12, %13, %14, %15, %16, %17, %18, %19, %20, %21, %22, %23, %24, %25, %26, %27, %28, %29, %30, %31, %32, %33, %34, %35, %36, %37, %38, %39, %40, %41, %42, %43, %44, %45, %46, %47, %48, %49, %50, %51, %52, %53, %54, %55, %56, %57, %58, %59, %60, %61, %62, %63}, da, db, p, 1, 1, 0, 1;\n}\n"
    : "+f"(d[0]), "+f"(d[1]), "+f"(d[2]), "+f"(d[3]), "+f"(d[4]), "+f"(d[5]), "+f"(d[6]), "+f"(d[7]), "+f"(d[8]), "+f"(d[9]), "+f"(d[10]), "+f"(d[11]), "+f"(d[12]), "+f"(d[13]), "+f"(d[14]), "+f"(d[15]), "+f"(d[16]), "+f"(d[17]), "+f"(d[18]), "+f"(d[19]), "+f"(d[20]), "+f"(d[21]), "+f"(d[22]), "+f"(d[23]), "+f"(d[24]), "+f"(d[25]), "+f"(d[26]), "+f"(d[27]), "+f"(d[28]), "+f"(d[29]), "+f"(d[30]), "+f"(d[31]), "+f"(d[32]), "+f"(d[33]), "+f"(d[34]), "+f"(d[35]), "+f"(d[36]), "+f"(d[37]), "+f"(d[38]), "+f"(d[39]), "+f"(d[40]), "+f"(d[41]), "+f"(d[42]), "+f"(d[43]), "+f"(d[44]), "+f"(d[45]), "+f"(d[46]), "+f"(d[47]), "+f"(d[48]), "+f"(d[49]), "+f"(d[50]), "+f"(d[51]), "+f"(d[52]), "+f"(d[53]), "+f"(d[54]), "+f"(d[55]), "+f"(d[56]), "+f"(d[57]), "+f"(d[58]), "+f"(d[59]), "+f"(d[60]), "+f"(d[61]), "+f"(d[62]), "+f"(d[63])
    : "r"(alo), "n"(AO), "n"(AH), "r"(blo), "n"(BO), "n"(BH), "r"(sc));
}

#define XD 600
#define XSTEP 300
#define XPD 450
#define XPB 8192
#define SPG 5600
#define WL0 1800
#define WLS 350
#define NB0 2
#define WP1 2000
#define PF_START 5600
#define PFP 126
#define GPERM 0x76543210u
#define FMODE 2
#define NM0 3
#define PWAIT 600
#define AWAKE 1
#define WDW 3
#define WDGAP 300
#define YWAIT 500
#define CWAIT 500
#define NDF 8
#define RDV 1
#define MSTEP 1200
#define MSLP 1000
#define MPOLL 3200
#define LMP 8
#define FLO(q, cta) (p.s->flo + (q) * 256 + (cta) * 2)
#define WD0 10
#define CLR0 22000
#define UPGAP 250
#define OUTGAP 150
#define MPROMO P128
#define MLOAD tma_load_ef
struct Ptrs { const bf16 *x, *wmod, *c, *wr, *wqkv; int by_sm; Scratch* s; const bf16 *wg, *wu, *wd, *wo; bf16* out; uint16_t role[132]; };

#define BAR(i) (sb + OFF_BAR + 8u * (i))

__device__ __forceinline__ uint32_t get_tag(uint32_t sb) { mbar_wait(BAR(B_TAG), 0); const uint32_t d = __shfl_sync(0xffffffffu, lds32(sb + OFF_CST + 32), 0); return d + 1 + (d & 2); }
__device__ __forceinline__ int d_kb(int n, int hg) {
    if (n < 2) return 2 * hg + n;
    const int h = n >= 9, q = n - 2 - 7 * h;
    return 2 * (q + (q >= hg)) + h;
}

__global__ void __launch_bounds__(NTHREADS, 1)
fused_kernel(const Ptrs p, const __grid_constant__ CUtensorMap tmM, const __grid_constant__ CUtensorMap tmX, const __grid_constant__ CUtensorMap tmW,
             const __grid_constant__ CUtensorMap tmWo, const __grid_constant__ CUtensorMap tmPhi, const __grid_constant__ CUtensorMap tmG,
             const __grid_constant__ CUtensorMap tmU, const __grid_constant__ CUtensorMap tmD, const __grid_constant__ CUtensorMap tmO)
{
    extern __shared__ __align__(1024) uint8_t smem_raw[];
    const uint32_t sb = smem_u32(smem_raw);
    const uint32_t cstart = __shfl_sync(0xffffffffu, clk32(), 0);
    const int tid = threadIdx.x, lane = tid & 31, warp = __shfl_sync(0xffffffffu, tid >> 5, 0);
    if (blockIdx.x < 128) {
        if (warp == 8) asm volatile("prefetch.global.L2 [%0];" :: "l"(p.wmod + (size_t)(blockIdx.x * 8 + (lane >> 2)) * 6144 + (lane & 1) * 64 + (lane & 2) * 512));
        if (warp == 13 && (lane & 1) < NM0 - 2) asm volatile("prefetch.global.L2 [%0];" :: "l"(p.wmod + (size_t)(blockIdx.x * 8 + (lane >> 2)) * 6144 + 128 + (lane & 1) * 64 + (lane & 2) * 512));
        if (warp == 12) l2_prefetch(p.wqkv + (size_t)blockIdx.x * 1536, 3072);
        if (warp == 9) { spin_until(cstart + XPD); l2_prefetch(p.x + (size_t)blockIdx.x * 16384, XPB); }
    }
    if (warp == 10) { tmap_prefetch(&tmM); tmap_prefetch(&tmX); tmap_prefetch(&tmW); }
    if (warp == 11) asm volatile("prefetch.global.L2 [%0];" :: "l"((lane < 16 ? p.c : p.wr) + (lane & 15) * 64));
    #pragma unroll
    for (int i = 0; i < 5; i++) e_init(BAR(5 * warp + i), warp < 5 ? 1 : warp < 7 ? 2 : warp < 9 ? 4 : warp < 14 ? 8 : warp < 15 ? 12 : 1);
    mbar_init_fence();
    if (warp == B_TAG / 5) { e_arrive_tx(BAR(B_TAG), 16); bulk_load(sb + OFF_CST + 32, p.s->done, 16, BAR(B_TAG)); }
    uint32_t role;
    asm("mov.u32 %0, %%smid;" : "=r"(role));
    role = p.role[p.by_sm ? role : blockIdx.x];
    const int b = role & 255;
    if (b >= 128 && warp == 0) {
        #pragma unroll
        for (int i = 0; i < 2; i++) { e_arrive_tx(BAR(i), 32768); MLOAD(sb + i * 32768u, &tmM, (b & 1) * 1024, (b & 2) * 256 + i * 256, BAR(i)); }
    }
    __syncthreads();

    if (b >= 128) {
        const int sp = b & 3;
        if (warp == 8) {
            #pragma unroll 1
            for (int j = 2, st = 2, ph = 1; j < 64; j++) {
                if (j == 2 * NM0) spin_until(cstart + SPG);
                mbar_wait(BAR(B_EA + st), ph);
                e_arrive_tx(BAR(st), 32768);
                MLOAD(sb + st * 32768u, &tmM, j < 32 ? (sp & 1) * 1024 + (j >> 1) * 64 : 2560 + sp * 512 + (j >> 2) * 64, (j < 32 ? (sp & 2) + (j & 1) : j & 3) * 256, BAR(st));
                if (++st == 6) { st = 0; ph ^= 1; }
            }
        } else if (warp < 8) {
            const int g = lane >> 2, c = lane & 3;
            {
                const bf16* cp = p.c + (tid >> 3) * 32 + (tid & 1) * 16 + (tid & 6);
                const uint32_t c0 = ldg32(cp), c1 = ldg32(cp + 8);
                stg_zero(p.s->llm1 + (tid >> 4) * 64 + sp * 16 + (tid & 15));
                if (tid < 128) stg_zero(p.s->llmod2 + sp * 128 + tid);
                sts64(sb + 200704u + tid * 8, silu2(c0), silu2(c1));
                bar_sync(1, 256);
                TR(57);
            }
            const uint32_t tag = get_tag(sb);
            const uint32_t wa = sb + (warp * 32 + (lane & 7) + (lane >> 4) * 8) * 128u + ((((lane >> 3) & 1) ^ (lane & 7)) << 4);
            float m[4][4];
            #pragma unroll
            for (int i = 0; i < 4; i++) m[i][0] = m[i][1] = m[i][2] = m[i][3] = 0.f;
            #pragma unroll 1
            for (int r = 0, st = 0, ph = 0; r < 32; r++) {
                const int n = r < 16 ? r : (r >> 1) + 8;
                const bf16* wr = p.wr + (sp & 1) * 512 + (n & 7) * 64 + (g & 3) * 16 + 2 * c;
                const uint32_t wr0 = ldg32(wr), wr1 = ldg32(wr + 8);
                const uint32_t sa = sb + 200704u + ((r < 16 ? sp >> 1 : r & 1) * 16 + warp) * 64 + c * 16;
                const uint4 sv0 = lds128(sa), sv1 = lds128(sa + 512);
                uint32_t f[16][4];
                #pragma unroll
                for (int q = 0; q < 2; q++) {
                    mbar_wait(BAR(st + q), ph);
                    if (r == 0 && warp == 0) TR(60 + q);
                    #pragma unroll
                    for (int i = 0; i < 8; i++) ldsm4t(f[8 * q + i], (wa + (st + q) * 32768u + (i >> 2) * 2048u) ^ ((i & 3) << 5));
                }
                #pragma unroll
                for (int i = 0; i < 16; i++) {
                    const uint4& sv = i < 8 ? sv0 : sv1;
                    mma16816(m[i & 3], f[i][0], f[i][1], f[i][2], f[i][3], (i & 4) ? sv.z : sv.x, (i & 4) ? sv.w : sv.y);
                    if ((i & 7) == 7) e_arrive_after(BAR(B_EA + st + (i >> 3)), f2u(m[0][0]) ^ f2u(m[1][0]) ^ f2u(m[2][0]) ^ f2u(m[3][0]));
                }
                st += 2; if (st == 6) { st = 0; ph ^= 1; }
                if (r >= 16 && !(r & 1)) continue;
                const uint32_t red = sb + 196608u + (n & 1) * 2048u;
                const uint32_t a = red + warp * 256u + (c * 16 + (g >> 1) * 4 + (g & 1)) * 4u;
                stsf(a, sel4(c, m[0][0], m[1][0], m[2][0], m[3][0])); stsf(a + 8, sel4(c, m[0][2], m[1][2], m[2][2], m[3][2]));
                #pragma unroll
                for (int i = 0; i < 4; i++) m[i][0] = m[i][1] = m[i][2] = m[i][3] = 0.f;
                bar_sync(1, 256);
                if (warp == (n & 7)) {
                    const uint32_t ra = red + (lane >> 4) * 1024u + (lane & 15) * 16u;
                    const uint4 r0 = lds128(ra), r1 = lds128(ra + 256), r2 = lds128(ra + 512), r3 = lds128(ra + 768);
                    #define F4(f) ((u2f(r0.f) + u2f(r1.f)) + (u2f(r2.f) + u2f(r3.f)))
                    float x = F4(x), y = F4(y), z = F4(z), w = F4(w);
                    #undef F4
                    x += shfl_x(x, 16); y += shfl_x(y, 16); z += shfl_x(z, 16); w += shfl_x(w, 16);
                    if (n < 16) {
                        if (lane < 16) st_ll4(p.s->llm1 + n * 64 + sp * 16 + lane, x, y, z, w, tag);
                    } else {
                        uint32_t lo = pack2(x, y), hi2 = pack2(z, w);
                        float d = fmaf(bf_lo(lo), bf_lo(wr0), bf_hi(lo) * bf_hi(wr0)) + fmaf(bf_lo(hi2), bf_lo(wr1), bf_hi(hi2) * bf_hi(wr1));
                        if (sp >= 2) {
                            lo = hadd2(lo, ONE2); hi2 = hadd2(hi2, ONE2);
                            const uint32_t r0 = hmul2(lo, wr0), r1 = hmul2(hi2, wr1);
                            d = (bf_lo(r0) + bf_hi(r0)) + (bf_lo(r1) + bf_hi(r1));
                        }
                        #pragma unroll 1
                        for (int k = 1; k < 16; k <<= 1) d += shfl_x(d, k);
                        if (lane < 16) st_ll(p.s->llmod2 + sp * 128 + (n & 7) * 16 + lane, lo, hi2, f2u(d), tag);
                    }
                    TR(n);
                }
            }
        }
    } else if (warp >= 12) {
        reg_dec<24>();
        const int rb = b >> 3, hg = b & 7, fs = role >> 8;
        const bool ffn = fs < 112;
        if (warp == 12) {
            #pragma unroll 1
            for (int j = 0, s = 0, ph = 1; j < 16; j++) {
                if (j < 2) mbar_wait(j ? BAR(B_STS) : BAR(B_STP), 0);
                mbar_wait(BAR(B_EA + s), ph);
                e_arrive_tx(BAR(B_FA + s), 16384); tma_load(sb + OFF_A + s * 16384u, &tmX, j * 64, rb * 128, BAR(B_FA + s));
                if (j == 0) TS(2);
                if (j == 1) GT(0);
                if (j == 6) GT(1);
                if (j == 11) GT(2);
                if (++s == 3) { s = 0; ph ^= 1; }
            }
            tmap_prefetch(&tmO);
            const uint32_t tag = get_tag(sb);
            e_arrive(BAR(B_FD)); e_arrive(BAR(B_FD + 1));
            const uint4* osrc = pin_ptr(p.s->os + (size_t)rb * 16 * 1024);
            #pragma unroll 1
            for (int q = 0; q < 3; q++) {
                mbar_wait(q < 2 ? BAR(B_KST + 1 + 2 * q) : BAR(B_OWN), 0);
                const uint32_t chk = poll_flags(q < 2 ? p.s->flk + (q + 1) * 256 + (hg * 16 + (lane & 15)) * 2 : FLO(0, rb * 8 + (lane & 7)), tag);
                if (q == 2) { sts32(sb + OFF_CHK + 64 + (lane & 7) * 8, chk); __syncwarp(); break; }
                e_arrive_tx(BAR(B_KVL + q), 16896); bulk_load(sb + (q ? OFF_PHI : OFF_KL), p.s->kvacc + hg * 2112 + q * 1056, 16896, BAR(B_KVL + q));
                TS(12 + q);
                if (!q) GT(4);
            }
            TS(3); GT(5);
            #pragma unroll
            for (int n = 2; n < 6; n++) {
                if (n >= 4) mbar_wait(BAR(B_ED + (n & 3)), 0); else if (n == 3) mbar_wait(BAR(B_OWN + 1), 0);
                e_arrive_tx(BAR(B_FD + (n & 3)), 16384);
                bulk_load(sb + (n == 5 ? OFF_X1 : OFF_R0 + (n & 3) * 16384u), osrc + (n - 2 >= hg ? n - 1 : n - 2) * 2048, 16384, BAR(B_FD + (n & 3)));
                TR(32 + n);
            }
            #pragma unroll 1
            for (int n = 6; n < 16; n++) {
                const uint32_t s = n & 3, fb = BAR(B_FD + s);
                const uint4* src = osrc + d_kb(n, hg) * 1024;
                if (n == 9) mbar_wait(BAR(B_O1), 0);
                mbar_wait(BAR(B_ED + s), ((n >> 2) - 1) & 1);
                e_arrive_tx(fb, 16384);
                bulk_load(sb + OFF_R0 + s * 16384u, src, 16384, fb);
                TR(32 + n);
            }
            e_arrive_tx(BAR(B_WPHI), 32768);
            mbar_wait(BAR(B_ED), 1);
            tma_load(sb + OFF_R0, &tmX, hg * 128, rb * 128, BAR(B_WPHI));
            tma_load(sb + OFF_X1, &tmX, hg * 128 + 64, rb * 128, BAR(B_WPHI));
            GT(6);
            mbar_wait(BAR(B_CAND), 0);
            GT(7);
            const uint2 lc = lds64(sb + OFF_CST + 16);
            const uint32_t w0 = __shfl_sync(0xffffffffu, lc.x >> 4, 0), w1 = __shfl_sync(0xffffffffu, lc.y >> 4, 0);
            mbar_wait(BAR(B_SWP), 0);
            fence_async_smem();
            #pragma unroll 1
            for (uint32_t w = 0; w < 8; w++)
                if (w != w0 && w != w1) { tma_store4(&tmO, rb * 128 + w * 16, hg * 2, sb + OFF_OUT + w * 4096u); spin_until(clk32() + OUTGAP); }
            mbar_wait(BAR(B_SEL), 0);
            const uint2 sel = lds64(sb + OFF_CST + 24);
            #pragma unroll 1
            for (uint32_t i = 0; i < (w0 == w1 ? 8u : 16u); i++) {
                const uint32_t w = i < 8 ? w0 : w1, r = (i & 7) * 2 + (lane >> 4), row = rb * 128 + w * 16 + r;
                const uint4 o = lds128(sb + OFF_OUT + w * 4096u + ((lane >> 3) & 1) * 2048u + r * 128u + (((lane ^ r) & 7) << 4));
                if (row != (~sel.x & 2047u) && row != (~sel.y & 2047u)) stg128(p.out + (size_t)row * 1024 + hg * 128 + (lane & 15) * 8, o);
            }
            bulk_wait_read();
        } else if (warp == 14) {
            const uint32_t fb = ffn ? 65536 : 0;
            e_arrive_tx(BAR(B_GF), fb); e_arrive_tx(BAR(B_UD), fb); e_arrive_tx(BAR(B_UF), fb); e_arrive_tx(BAR(B_WD), fb);
            uint32_t due = cstart + WP1;
            #pragma unroll 1
            for (int i = -2; i < 26; i++) {
                if (i >= 0) {
                    const bf16* a = i < 8 ? p.wg + (size_t)(i * 128 + b) * 3584 : i < 16 ? p.wu + (size_t)((i - 8) * 128 + b) * 3584
                                  : i < 18 ? p.wo + (size_t)(b * 2 + i - 16) * 4096 : p.wd + (size_t)(b * 8 + i - 18) * 3584;
                    sleep_until(due);
                    l2_prefetch(a, (i >> 1) == 8 ? 8192 : 7168);
                    due += 7 * PFP;
                }
                if (i == 1) { tmap_prefetch(&tmPhi); tmap_prefetch(&tmG); tmap_prefetch(&tmWo); tmap_prefetch(&tmU); tmap_prefetch(&tmD); mbar_wait(BAR(B_STS), 0); }
                if (ffn && (uint32_t)(i - 3) < 8u) tma_load_ef(sb + OFF_R0 + (i - 3) * 8192u, &tmG, fs * 32, (i - 3) * 128, BAR(B_GF));
                if (ffn && (uint32_t)(i - 11) < 8u) tma_load(sb + OFF_WPHI, &tmU, fs * 32, (i - 11) * 128, BAR(B_UD));
                if (i == 19) { mbar_wait(BAR(B_UD), 0); e_arrive_tx(BAR(B_WPHI), 8192); tma_load(sb + OFF_WPHI, &tmPhi, 0, hg * 128, BAR(B_WPHI)); }
                if (i == LMP + 2 * (b & 3) + (b >> 6)) tma_prefetch(&tmM, 2048 + (b >> 6) * 2048 + (b >> 2) * 64, (b & 3) * 256);
                if (i < 13) {
                    sleep_until(due);
                    l2_prefetch(p.wqkv + (size_t)((i + 3) * 128 + b) * 1536, 3072);
                    due += i == -2 ? PF_START - WP1 : 3 * PFP;
                }
            }
            if (lane < 4) stg_zero(FLO(lane >> 1, b) + (lane & 1));
            const uint32_t tag = get_tag(sb);
            #pragma unroll 1
            for (int q = 0; q < 2; q++) {
                mbar_wait(BAR(B_OWN + q), 0);
                if (q) mbar_wait(BAR(B_FD + 2), 0);
                bulk_store(p.s->os + ((size_t)b * 2 + q) * 1024, sb + OFF_R0 + q * 16384u, 16384);
                mbar_wait(BAR(B_CS + q), 0);
                uint32_t chk = __reduce_xor_sync(0xffffffffu, lane < 8 ? lds32(sb + OFF_CHK + q * 32 + lane * 4) : 0u);
                bulk_wait();
                __syncwarp();
                st_flag(FLO(q, b), tag, chk, lane);
                TS(7 + q);
            }
            e_arrive(BAR(B_OST));
            fence_gpu();
            __syncwarp();
            st_flag(FLO(2, b), tag, 0, lane);
        } else {
            uint4* fk = p.s->flk + (hg * 16 + rb) * 2;
            if (warp == 13) {
                #pragma unroll 1
                for (int i = 0; i < 32; i++) {
                    const uint32_t s = i & 3;
                    if (i < NB0) spin_until(cstart + WL0 + WLS * i); else if (i == NB0) mbar_wait(BAR(B_STS), 0);
                    mbar_wait(BAR(B_EB + s), ((i >> 2) - 1) & 1);
                    e_arrive_tx(BAR(B_FB + s), 24576); tma_load4(sb + OFF_B + s * 24576u, &tmW, i * 32, hg * 2, BAR(B_FB + s));
                    TR(64 + i);
                }
                mbar_wait(BAR(B_EB), 1); mbar_wait(BAR(B_EB + 1), 1);
                e_arrive_tx(BAR(B_LMF), 32768); tma_load_ef(sb + OFF_B, &tmM, 2048 + (b >> 6) * 2048 + (b >> 2) * 64, (b & 3) * 256, BAR(B_LMF));
                mbar_wait(BAR(B_LMD), 0);
                #pragma unroll 1
                for (int n = 0; n < 4; n++) {
                    e_arrive_tx(BAR(B_FD + n), 16384); tma_load4(sb + OFF_DB + n * 16384u, &tmWo, d_kb(n, hg) * 64, hg * 2, BAR(B_FD + n));
                }
            } else {
                sleep_until(cstart + CLR0);
                const uint32_t tag = get_tag(sb);
                #pragma unroll 1
                for (int i = lane; i < 132; i += 32) stg_zero(p.s->kvacc + hg * 2112 + rb * 132 + i);
                if (lane < 4) stg_zero(fk + 256 + (lane >> 1) * 256 + (lane & 1));
                fence_gpu();
                __syncwarp();
                st_flag(fk, tag, 0, lane);
                sleep_until(clk32() + 2000);
                poll_flags(p.s->flk + (hg * 16 + (lane & 15)) * 2, tag);
                mbar_wait(BAR(B_QE), 0);
                #pragma unroll 1
                for (int i = 0; i < 4; i++) {
                    stg_zero(p.s->llln2 + b * 128 + i * 32 + lane);
                    stg_zero(p.s->llrowh + (i >> 1) * 8192 + (rb * 2 + (i & 1)) * 256 + hg * 32 + lane);
                    #pragma unroll
                    for (int k = 0; k < 4; k++) stg_zero(p.s->lly + (fs & 127) * 512 + i * 128 + k * 32 + lane);
                }
                if (lane < 2 && hg == (rb & 7)) stg_zero(p.s->llcand + rb * 2 + lane);
                __syncwarp();
                e_arrive(BAR(B_KZ));
            }
            const int q = warp == 13;
            const uint32_t tag = get_tag(sb);
            mbar_wait(BAR(B_KZ), 0);
            #pragma unroll 1
            for (int h = 2 * q; h < 2 * q + 2; h++) {
                mbar_wait(BAR(B_KST + h), 0);
                uint4* acc = p.s->kvacc + (hg * 4 + h) * 528;
                bulk_reduce(acc, sb + OFF_V + h * 8192u, 8192); bulk_reduce(acc + 512, sb + OFF_ZS + h * 256u, 256);
            }
            bulk_wait();
            if (q) e_arrive(BAR(B_KZ));
            TR(158 + q);
            fence_gpu();
            __syncwarp();
            st_flag(fk + 256 + q * 256, tag, 0, lane);
            TS(10 + q);
            if (q) {
                #pragma unroll 1
                for (int n = 4; n < 16; n++) {
                    const uint32_t s = n & 3;
                    mbar_wait(BAR(B_ED + s), ((n >> 2) - 1) & 1);
                    e_arrive_tx(BAR(B_FD + s), 16384);
                    tma_load4(sb + OFF_DB + s * 16384u, &tmWo, d_kb(n, hg) * 64, hg * 2, BAR(B_FD + s));
                    TR(96 + n);
                    if (ffn && (uint32_t)(n - WD0) < 4u) {
                        #pragma unroll
                        for (int k = 0; k < 2; k++) tma_load_ef(sb + OFF_F2 + (n - WD0) * 8192u + k * 4096u, &tmD, (n - WD0) * 256 + k * 128, fs * 32, BAR(B_WD));
                    }
                }
                if (ffn) {
                    mbar_wait(BAR(B_ED + WDW), 1);
                    #pragma unroll 1
                    for (int z = 0; z < 8; z++) { tma_load_ef(sb + OFF_DB + z * 4096u, &tmD, z * 128 + 64, fs * 32, BAR(B_WD)); sleep_until(clk32() + WDGAP); }
                }
            } else {
                if (ffn) {
                    mbar_wait(BAR(B_KZ), 1);
                    #pragma unroll 1
                    for (int i = 7; i < 15; i++) {
                        if (i == 12) mbar_wait(BAR(B_KVT + 1), 0);
                        tma_load_ef(sb + OFF_F2 + (i & 7) * 8192u, &tmU, fs * 32, (i & 7) * 128, BAR(B_UF));
                        sleep_until(clk32() + UPGAP);
                    }
                }
                mbar_wait(BAR(B_OST), 0);
                sts32(sb + OFF_CHK + 68 + (lane & 7) * 8, poll_flags(FLO(1, rb * 8 + (lane & 7)), tag));
                __syncwarp();
                e_arrive(BAR(B_O1));
                TS(4);
            }
        }
    } else if (warp >= 8) {
        reg_dec<24>();
        const int rb = b >> 3, hg = b & 7, w4 = warp & 3, g = lane >> 2, c = lane & 3, t = tid & 127;
        const uint32_t sv = silu2(ldg32(p.c + (b & 3) * 256 + 2 * t)), tag = get_tag(sb);
        if (w4 < 3) {
            spin_until(cstart + MPOLL + MSTEP * w4);
            #pragma unroll 1
            for (int j = w4, ph = 1; j < 16; j += 3, ph ^= 1) {
                uint4 w[2];
                poll_words<2, 0, 3>(w, p.s->llm1 + j * 64 + lane, 32, tag);
                uint32_t lo = pack2(u2f(w[0].x) + u2f(w[1].x), u2f(w[0].y) + u2f(w[1].y)), hi = pack2(u2f(w[0].z) + u2f(w[1].z), u2f(w[0].w) + u2f(w[1].w));
                if (lane >= 16) { lo = hadd2(lo, ONE2); hi = hadd2(hi, ONE2); }
                sts64(sb + OFF_TAB + j * 256 + (lane & 15) * 16 + (lane < 16 ? 8 : 0), lo, hi);
                __syncwarp();
                if (j == 0) TS(5);
                TR(16 + j);
                mbar_wait(BAR(B_EA + w4), ph);
                e_arrive(BAR(B_FA + w4));
                __nanosleep(MSLP);
            }
        }
        mbar_wait(BAR(B_QE), 0);
        if (warp == 8) GT(3);
        sts32(sb + OFF_KL + w4 * 1024u + lane * 4, sv);
        fence_async_smem();
        bar_sync(2, 128);
        reg_inc<56>();
        {
            float m0[4], m1[4];
            const uint32_t da = desc_lo(sb + OFF_B, 16), db = desc_lo(sb + OFF_KL, 16);
            mbar_wait(BAR(B_LMF), 0);
            wg_fence();
            #define LMS(f, i) f<(i) * 256, H128, ((i) >> 1) * 64 + ((i) & 1) * 4, H128>(m0, da, db); f<(i) * 256 + 128, H128, ((i) >> 1) * 64 + ((i) & 1) * 4 + 2, H128>(m1, da, db)
            LMS(mma8_tn0, 0); LMS(mma8_tn, 1); LMS(mma8_tn, 2); LMS(mma8_tn, 3); LMS(mma8_tn, 4); LMS(mma8_tn, 5); LMS(mma8_tn, 6); LMS(mma8_tn, 7);
            #undef LMS
            wg_commit();
            wg_wait<0>();
            acc_fence(m0); acc_fence(m1);
            e_arrive(BAR(B_LMD));
            const float v0 = m0[0] + m1[0], v1 = m0[2] + m1[2], u0 = shfl_x(v0, 4), u1 = shfl_x(v1, 4);
            if (!(lane & 7)) st_ll4(p.s->llg + (b >> 6) * 1024 + (b & 3) * 256 + ((b >> 2) & 15) * 16 + w4 * 4 + (lane >> 3), v0, u0, v1, u1, tag);
            if (warp == 8) TR(150);
        }
        #pragma unroll 1
        for (int h = 0; h < 4; h++) {
            float okv[20];
            const uint32_t vb = OFF_V + h * 8192u, dp = desc_lo(sb + OFF_PHI + (h & 1) * 16384u, 16), dv = desc_lo(sb + vb, OFF_ONES - vb);
            mbar_wait(BAR(B_PF + h), 0);
            fence_async_smem();
            wg_fence();
            #define KVS(i) mma40_tt<(i) * 128, H128, (i) * (64u - (64u << 16)), H64>(okv, dp, dv)
            mma40_tt0<0, H128, 0, H64>(okv, dp, dv); KVS(1); KVS(2); KVS(3); KVS(4); KVS(5); KVS(6); KVS(7);
            #undef KVS
            wg_commit();
            wg_wait<0>();
            acc_fence(okv);
            if (h < 2) e_arrive(BAR(B_PE + h));
            bar_sync(2, 128);
            #pragma unroll
            for (int k = 0; k < 4; k++) sts128(sb + vb + (k * 128 + t) * 16u, make_uint4(f2u(okv[4 * k]), f2u(okv[4 * k + 1]), f2u(okv[4 * k + 2]), f2u(okv[4 * k + 3])));
            if (c == 0) sts64(sb + OFF_ZS + h * 256u + (w4 * 8 + g) * 8u, f2u(okv[16]), f2u(okv[18]));
            fence_async_smem();
            __syncwarp();
            e_arrive(BAR(B_KST + h));
            if (warp == 8) TR(151 + h);
        }
        e_arrive(BAR(B_ED)); e_arrive(BAR(B_ED + 1));
        if (w4 == 0 || w4 == 3) {
            uint4 w[4];
            poll_words<4, 0, 3>(w, p.s->llg + (w4 & 1) * 1024 + hg * 32 + lane, 256, tag);
            #define F4(f) ((u2f(w[0].f) + u2f(w[1].f)) + (u2f(w[2].f) + u2f(w[3].f)))
            const uint32_t lo = pack2(F4(x), F4(y)), hi = pack2(F4(z), F4(w));
            #undef F4
            sts64(w4 ? sb + OFF_T3 + lane * 8 : sb + OFF_T1 + lane * 16, lo, hi);
            if (!w4) sts64(sb + OFF_T1 + 512 + lane * 16, lo, hi);
        } else {
            const bf16* wr = p.wr + hg * 128 + g * 16 + 2 * c;
            const uint32_t wr0 = ldg32(wr), wr1 = ldg32(wr + 8);
            uint4 w[2];
            poll_words<2, 1>(w, p.s->llmod2 + (w4 - 1) * 256 + hg * 32 + lane, (lane & 15) * 16 - hg * 32 - lane, tag);
            sts64(sb + OFF_T2 + lane * 16 + (w4 & 1) * 8, w[0].x, w[0].y);
            if (w4 == 2) sts64(sb + OFF_T1 + 512 + lane * 16 + 8, hmul2(w[0].x, wr0), hmul2(w[0].y, wr1));
            float d = u2f(w[1].z);
            #pragma unroll 1
            for (int k = 1; k < 16; k <<= 1) d += shfl_x(d, k);
            stsf(sb + OFF_CST + 8 + (w4 & 1) * 4, d);
        }
        if (warp == 9) TS(6);
        #pragma unroll 1
        for (int q = 0; q < 2; q++) {
            const uint32_t f = w4 * 16 + g, kl = sb + (q ? OFF_PHI : OFF_KL), ta = sb + (q ? OFF_KL : OFF_KVT) + f * 64u + ((g >> 1) << 4) + 4 * c;
            const uint32_t za = sb + OFF_Z + (f + 8 * (c & 1)) * 64u + (((2 * q) ^ (g >> 1)) << 4) + (c >> 1) * 8;
            mbar_wait(q ? BAR(B_KVT) : BAR(B_STP), q ^ 1);
            mbar_wait(BAR(B_KVL + q), 0);
            uint4 v[8]; float z[2];
            #pragma unroll
            for (int k = 0; k < 8; k++) v[k] = lds128(kl + (k >> 2) * 8448u + (k & 3) * 2048u + t * 16u);
            #pragma unroll
            for (int hh = 0; hh < 2; hh++) z[hh] = ldsf(kl + hh * 8448u + 8192u + (w4 * 8 + g) * 8u + (c & 1) * 4);
            #pragma unroll
            for (int k = 0; k < 8; k++) {
                sts32((ta ^ ((k & 3) << 4)) + (k >> 2) * 4096u, pack2(u2f(v[k].x), u2f(v[k].y))); sts32((ta ^ ((k & 3) << 4)) + (k >> 2) * 4096u + 512, pack2(u2f(v[k].z), u2f(v[k].w)));
            }
            #pragma unroll
            for (int hh = 0; hh < 2; hh++) { const uint32_t zz = pack2(z[hh], z[hh]); sts64(za ^ (hh << 4), zz, zz); }
            fence_async_smem();
            __syncwarp();
            e_arrive(BAR(B_KVT + q));
            if (warp == 8) TR(155 + q);
        }
        reg_dec<24>();
        {
            const uint32_t a = sb + w4 * 4096u + g * 128u + (((2 * c) ^ g) << 4) + (g >> 1) * 4;
            uint32_t x = 0;
            #pragma unroll 1
            for (int n = 2; n < 16; n++) {
                const uint32_t ta = a + (n == 5 ? OFF_X1 : OFF_R0 + (n & 3) * 16384u), ca = sb + OFF_CHK + 64 + d_kb(n, hg) * 4;
                mbar_wait(BAR(B_FD + (n & 3)), (n >> 2) & 1);
                const uint32_t v0 = lds32(ta), v1 = lds32(ta + 1024), v2 = lds32(ta + 2048), v3 = lds32(ta + 3072);
                x = __funnelshift_l(x, x, 1) ^ v0 ^ v1 ^ v2 ^ v3;
                e_arrive_after(BAR(B_ED + (n & 3)), x);
                if (t == 0) x ^= lds32(ca);
            }
            sts32(sb + OFF_CHK + 128 + w4 * 4, __reduce_xor_sync(0xffffffffu, x));
        }
        __syncwarp();
        e_arrive(BAR(B_PAR));
        if (w4 < 2) {
            mbar_wait(BAR(B_PAR), 0);
            const uint4 ta = lds128(sb + OFF_T2 + lane * 16);
            const uint2 gb = lds64(sb + OFF_T3 + lane * 8);
            uint4* d = pin_ptr(p.s->llrowh + (rb * 2 + w4) * 256 + hg * 32 + lane);
            mbar_wait(BAR(B_KEYS), 0);
            const uint4 kk = lds128(sb + OFF_KEY + lane * 16);
            uint32_t k[4] = {kk.x, kk.y, kk.z, kk.w}, b0, b1;
            top2<4>(k, b0, b1);
            const uint32_t cd = ~(w4 ? b1 : b0) & 127u;
            const uint32_t xa = sb + OFF_R0 + (g >> 2) * (OFF_X1 - OFF_R0) + cd * 128u + ((((g & 3) * 2) ^ (cd & 7)) << 4) + c * 4;
            const uint32_t x0 = lds32(xa), x1 = lds32(xa ^ 16);
            const uint4 st = lds128(sb + OFF_ST2 + cd * 16);
            st_ll(d, lnmod(x0, st.x, st.y, st.z, ta.x, ta.z), lnmod(x1, st.x, st.y, st.z, ta.y, ta.w), gb.x, tag);
            st_ll(d + 8192, x0, x1, gb.y, tag);
            sts32(sb + OFF_CST + 16 + w4 * 4, cd);
            __syncwarp();
            e_arrive(BAR(B_CAND));
            if (warp == 8) TS(9);
        } else if (w4 == 2) {
            uint4* cp = pin_ptr(p.s->llcand + lane);
            mbar_wait(BAR(B_KEYS), 0);
            if (hg == (rb & 7)) {
                const uint4 kk = lds128(sb + OFF_KEY + lane * 16);
                uint32_t k[4] = {kk.x, kk.y, kk.z, kk.w}, b0, b1;
                top2<4>(k, b0, b1);
                if ((lane >> 1) == rb) st_ll(cp, tag, (lane & 1) ? b1 : b0, tag, tag);
            } else spin_until(clk32() + CWAIT);
            uint32_t k[1] = {poll_flags(cp, tag)}, b0, b1;
            top2<1>(k, b0, b1);
            sts64(sb + OFF_CST + 24, b0, b1);
            __syncwarp();
            e_arrive(BAR(B_SEL));
        }
    } else {
        reg_inc<232>();
        float a0[96], a1[96];
        {
            const int g = lane >> 2, c = lane & 3;
            uint4* stp = p.s->llstat + b * 16 + warp * 2 + (lane >> 4);
            if (lane == 0 || lane == 18) stg_zero(stp);
            spin_until(cstart + XD + XSTEP * warp);
            e_arrive_tx(BAR(B_XP + warp), 4096);
            bulk_load(sb + OFF_R0 + warp * 4096u, p.x + (size_t)(b * 16 + 2 * warp) * 1024, 4096, BAR(B_XP + warp));
            const uint32_t tag = get_tag(sb);
            if (tid < 64) sts128(sb + OFF_ONES + tid * 16, make_uint4(ONE2, ONE2, ONE2, ONE2));
            if (tid == 64) { sts64(sb + OFF_CST, role, tag); stsf(sb + OFF_CST + 48, -LOG2E); }
            if (AWAKE & 1) mbar_wait_awake(BAR(B_XP + warp), 0); else mbar_wait(BAR(B_XP + warp), 0);
            e_arrive(BAR(B_STP));
            if (warp == 7) TS(14);
            float s[2][4], q0[2][4], q1[2][4];
            #pragma unroll
            for (int i = 0; i < 4; i++) s[0][i] = s[1][i] = q0[0][i] = q0[1][i] = q1[0][i] = q1[1][i] = 0.f;
            uint32_t xa[8][4], xb[8][4];
            const uint32_t la = sb + OFF_R0 + warp * 4096u + (lane & 7) * 16u;
            #pragma unroll
            for (int i = 0; i < 8; i++) {
                ldsm4(xa[i], la + ((lane >> 3) & 1) * 2048u + (lane >> 4) * 128u + i * 256u);
                ldsm4(xb[i], la + ((lane >> 3) & 1) * 128u + (lane >> 4) * 2048u + i * 256u);
            }
            #pragma unroll
            for (int i = 0; i < 8; i++) {
                mma16816(q0[i & 1], xa[i][0], xa[i][1], xa[i][2], xa[i][3], xb[i][0], xb[i][1]);
                mma16816(q1[i & 1], xa[i][0], xa[i][1], xa[i][2], xa[i][3], xb[i][2], xb[i][3]);
                mma16816(s[i & 1], xa[i][0], xa[i][1], xa[i][2], xa[i][3], ONE2, ONE2);
            }
            const float s0 = s[0][0] + s[1][0], s1 = s[0][2] + s[1][2];
            const float sq0 = (g & 1) ? q0[0][1] + q0[1][1] : q0[0][0] + q0[1][0], sq1 = (g & 1) ? q1[0][3] + q1[1][3] : q1[0][2] + q1[1][2];
            const bool up = lane >= 16;
            float sm = (up ? s1 : s0) + shfl_x(up ? s0 : s1, 18), sq = (up ? sq1 : sq0) + shfl_x(up ? sq0 : sq1, 18);
            sm += shfl_x(sm, 9); sq += shfl_x(sq, 9);
            sm += shfl_x(sm, 4); sq += shfl_x(sq, 4);
            uint32_t m2, rh, rl; float rinv;
            ln_final(sm, sq, m2, rinv);
            split_rcp(rinv, rh, rl);
            if (lane == 0 || lane == 18) st_ll(stp, m2, rh, rl, tag);
            if (warp == 7) TS(15);
            uint4 st[2];
            if (PWAIT) { mbar_wait(BAR(B_STP), 0); if (warp < 7) spin_until(clk32() + PWAIT); }
            #pragma unroll 1
            for (int it = 0; it < POLL_MAX; it++) {
                st[0] = ld_ll(p.s->llstat + (b >> 3) * 128 + warp * 16 + g); st[1] = ld_ll(p.s->llstat + (b >> 3) * 128 + warp * 16 + g + 8);
                const uint32_t o = RDV ? ld_rlx(&p.s->llstat[((b >> 5) * 4 + c) * 128 + warp * 16 + 15].w) : tag;
                if (__all_sync(0xffffffffu, !tag_bad(tag_bad(o ^ tag, st[0].w, tag), st[1].w, tag))) break;
                if (AWAKE & 1) it += awake_zero();
            }
            e_arrive(BAR(B_STS));
            if (warp == 0) TS(16);
            const uint32_t lrow = warp * 16 + (lane & 15);
            uint32_t aad = sb + OFF_A + lrow * 128u + (((lane >> 4) ^ (lrow & 7)) << 4);
            uint32_t tad = sb + OFF_TAB + c * 16, ab = BAR(B_FA), pa = 0;
            uint32_t f0[4], f1[4];
            #define PREP(f, q) do { \
                const uint4 t = lds128(tad + (q) * 64); \
                ldsm4(f, aad ^ ((q) << 5)); \
                f[0] = lnmod(f[0], st[0].x, st[0].y, st[0].z, t.x, t.z); f[1] = lnmod(f[1], st[1].x, st[1].y, st[1].z, t.x, t.z); \
                f[2] = lnmod(f[2], st[0].x, st[0].y, st[0].z, t.y, t.w); f[3] = lnmod(f[3], st[1].x, st[1].y, st[1].z, t.y, t.w); } while (0)
            #define MMA(f, off) do { wg_fence(); mma192_rs<(off), H128>(a0, f, blo); mma192_rs<(off) + 768, H128>(a1, f, blo); wg_commit(); wg_wait<1>(); } while (0)
            mbar_wait(ab, 0);
            PREP(f0, 0);
            if (RDV) mbar_wait(BAR(B_STS), 0);
            #pragma unroll 1
            for (int j = 0; j < 16; j++) {
                const uint32_t bb = BAR(B_FB) + (j & 1) * 16, blo = desc_lo(sb + OFF_B, 4096) + (j & 1) * 3072, pb = (j >> 1) & 1;
                mbar_wait(bb, pb);
                wg_fence(); mma192_rsp<0, H128>(a0, f0, blo, j); mma192_rsp<768, H128>(a1, f0, blo, j); wg_commit(); wg_wait<1>();
                if (j) e_arrive((bb ^ 16) + 8 * (B_EB - B_FB) + 8);
                PREP(f1, 1);
                MMA(f1, 128);
                PREP(f0, 2);
                mbar_wait(bb + 8, pb);
                MMA(f0, 1536);
                e_arrive(bb + 8 * (B_EB - B_FB));
                PREP(f1, 3);
                MMA(f1, 1536 + 128);
                e_arrive(ab + 8 * (B_EA - B_FA));
                ab += 8; aad += 16384; tad += 256;
                if (ab == BAR(B_FA + 3)) { ab -= 24; aad -= 49152; pa ^= 1; }
                if (j < 15) mbar_wait(ab, pa);
                PREP(f0, 0);
            }
            #undef PREP
            #undef MMA
        }
        int tid_o; asm volatile("mov.u32 %0, %%tid.x;" : "=r"(tid_o) :: "memory");
        const int tid = tid_o, lane = tid & 31, warp = __shfl_sync(0xffffffffu, tid >> 5, 0), wgi = warp >> 2, g = lane >> 2, c = lane & 3;
        const uint32_t srow = warp * 16 + (lane & 15);
        #define T128(t) (sb + (((t) >> 5) * 16 + ((t) & 15)) * 128u + (((((t) >> 4) & 1) ^ ((t) & 7)) << 4))
        const uint32_t pa = T128(tid);
        mbar_wait(BAR(B_WPHI), 0);
        mbar_wait(BAR(B_EA), 1);
        wg_wait<0>();
        acc_fence(a0); acc_fence(a1);
        e_arrive(BAR(B_QE));
        if (warp == 0) TS(18);
        uint32_t ph0[16], ph1[16], kq[32];
        {
        uint32_t pk[16], mm[4], mn[2];
        float ea[32], eb[32];
        {
            float p0[16], p1[16];
            const uint32_t dw = desc_lo(sb + OFF_WPHI, 16);
            #define PMMA(f, o) do { wg_fence(); mma32_rs0<(o), H64>(p0, f, dw); mma32_rs0<(o) + 128, H64>(p1, f + 8, dw); \
                mma32_rs<(o) + 64, H64>(p0, f + 4, dw); mma32_rs<(o) + 192, H64>(p1, f + 12, dw); wg_commit(); } while (0)
            #define V_OUT(lo) _Pragma("unroll") for (int i = lo; i < lo + 4; i++) { const int o = 32 + 8 * i; \
                stsm4(sb + OFF_V + (i >> 1) * 8192u + srow * 64u + (((2 * (i & 1) + (lane >> 4)) ^ ((srow >> 1) & 3)) << 4), \
                      pack2(a1[o], a1[o + 1]), pack2(a1[o + 2], a1[o + 3]), pack2(a1[o + 4], a1[o + 5]), pack2(a1[o + 6], a1[o + 7])); }
            V_OUT(0);
            #pragma unroll
            for (int i = 0; i < 16; i++) ph0[i] = pack2(a0[64 + 2 * i], a0[65 + 2 * i]);
            PMMA(ph0, 0);
            V_OUT(4);
            #undef V_OUT
            wg_wait<0>();
            acc_fence(p0); acc_fence(p1);
            fm_max(p0, pk, mm); fm_max(p1, pk + 8, mm + 2);
            #pragma unroll
            for (int i = 0; i < 16; i++) ph1[i] = pack2(a1[2 * i], a1[2 * i + 1]);
            PMMA(ph1, 256);
            if (warp == 0) TS(19);
            fm_pos(pk, mm, ea);
            #pragma unroll
            for (int i = 0; i < 32; i++) kq[i] = pack2(a0[2 * i], a0[2 * i + 1]);
            acc_fence(ea); pin<32>(kq);
            wg_wait<0>();
            acc_fence(p0); acc_fence(p1);
            #define PHI_OUT(ph, i) do { if (u < 2) { \
                    mbar_wait(u ? BAR(B_PE + (i)) : (i) ? BAR(B_LMD) : BAR(B_QE), 0);          \
                    _Pragma("unroll") for (int q = 0; q < 4; q++) stsm4((pa ^ (q << 5)) + OFF_PHI + (i) * 16384u, ph[4 * q], ph[4 * q + 1], ph[4 * q + 2], ph[4 * q + 3]); \
                    __syncwarp(); \
                    e_arrive(BAR(B_PF + (i)) + u * 16); } } while (0)
            reg_dec<216>();
            #pragma unroll 1
            for (int u = 0; u < 4; u++) {
                fm_neg(mm, ldsf(sb + OFF_CST + 48), ea); fm_pos(pk + 8, mm + 2, eb);
                fm_norm(ea, ph0); fm_max(p0, pk, mm); fm_max(p1, pk + 8, mn);
                PHI_OUT(ph0, 0);
                if (warp == 0) TR(130 + (u & 1) * 6);
                if (u == 0) PMMA(kq, 0); else PMMA(kq + 16, 256);
                fm_neg(mm + 2, ldsf(sb + OFF_CST + 48), eb); fm_pos(pk, mm, ea);
                fm_norm(eb, ph1);
                mm[2] = mn[0]; mm[3] = mn[1];
                PHI_OUT(ph1, 1);
                wg_wait<0>();
                acc_fence(p0); acc_fence(p1);
                if (u == 2) {
                    e_arrive(BAR(B_STP));
                    mbar_wait(BAR(B_GF), 0);
                    #pragma unroll
                    for (int i = 0; i < 16; i++) { kq[i] = ph0[i]; kq[16 + i] = ph1[i]; }
                }
                if (warp == 0) TR(133 + (u & 1) * 6);
                if (warp == 0) TS(21 + u);
            }
            #undef PHI_OUT
            #undef PMMA
        }
        }
        uint32_t gf[16][4], uf[16][4];
        const uint32_t fo = sb + (warp >> 1) * 2048u + ((lane & 7) + (lane >> 4) * 8) * 64u + (((2 * (warp & 1) + ((lane >> 3) & 1)) ^ ((lane >> 1) & 3)) << 4);
        #define F_LOAD(f, off, i) ldsm4t(f[i], fo + (off) + ((i) >> 1) * 8192u + ((i) & 1) * 1024u)
        #define G_LOAD(lo, n) _Pragma("unroll") for (int i = lo; i < lo + n; i++) F_LOAD(gf, OFF_R0, i)
        #define O_BLOCK(pp, ph0, ph1) do { \
            if ((AWAKE & 2) && !(pp)) mbar_wait_awake(BAR(B_KVT + (pp)), 0); else mbar_wait(BAR(B_KVT + (pp)), 0); \
            if (warp == 0) TS(25 + 3 * (pp)); \
            const uint32_t oa = T128(tid + (lds32(sb + OFF_CST) >> 16)); \
            float o0[20], o1[20]; \
            const uint32_t dk = (pp) ? desc_lo(sb + OFF_KL, OFF_Z + 32 - OFF_KL) : desc_lo(sb + OFF_KVT, OFF_Z - OFF_KVT); \
            constexpr uint32_t K1 = 256u - (255u << 16);          \
            wg_fence(); \
            mma40_rs0<0, H64>(o0, ph0, dk); mma40_rs0<K1, H64>(o1, ph1, dk); \
            mma40_rs<64, H64>(o0, ph0 + 4, dk); mma40_rs<K1 + 64, H64>(o1, ph1 + 4, dk); \
            mma40_rs<128, H64>(o0, ph0 + 8, dk); mma40_rs<K1 + 128, H64>(o1, ph1 + 8, dk); \
            mma40_rs<192, H64>(o0, ph0 + 12, dk); mma40_rs<K1 + 192, H64>(o1, ph1 + 12, dk); \
            wg_commit(); \
            wg_wait<0>(); \
            acc_fence(o0); acc_fence(o1); \
            if (pp) e_arrive(BAR(B_ED)); \
            if (warp == 0) TS(26 + 3 * (pp)); \
              \
            if (pp) { G_LOAD(12, 4); } \
            mbar_wait(BAR(B_GE + (pp)), 0);          \
            uint32_t chk = 0; \
            _Pragma("unroll") for (int hh = 0; hh < 2; hh++) { \
                const float (&o)[20] = hh ? o1 : o0; \
                uint32_t h0, l0, h1, l1; \
                split_rcp(rcp(rbf(rbf(o[16]) + 1e-6f)), h0, l0); split_rcp(rcp(rbf(rbf(o[18]) + 1e-6f)), h1, l1); \
                _Pragma("unroll") for (int q = 0; q < 2; q++) { \
                    const uint32_t r0 = hdiv2(pack2(o[8 * q], o[8 * q + 1]), h0, l0), r1 = hdiv2(pack2(o[8 * q + 2], o[8 * q + 3]), h1, l1); \
                    stsm4((oa ^ ((2 * hh + q) << 5)) + OFF_R0 + (pp) * 16384u, r0, r1, \
                          hdiv2(pack2(o[8 * q + 4], o[8 * q + 5]), h0, l0), hdiv2(pack2(o[8 * q + 6], o[8 * q + 7]), h1, l1)); \
                    chk ^= r0 ^ r1; \
                } \
            } \
            fence_async_smem(); \
            __syncwarp(); \
            e_arrive(BAR(B_OWN + (pp))); \
            sts32(sb + OFF_CHK + (pp) * 32 + warp * 4, __reduce_xor_sync(0xffffffffu, c == (g >> 1) ? chk : 0u)); \
            if (!(pp)) { G_LOAD(4, 8); fence_async_smem(); } \
            __syncwarp(); \
            e_arrive(BAR(B_CS + (pp))); \
            if (warp == 0) TS(27 + 3 * (pp)); \
        } while (0)
        float acc[64];
        const uint32_t da = desc_lo(sb + OFF_R0 + wgi * 8192u, 16), db = desc_lo(sb + OFF_DB, 8192);
        #define D_MMA(first, a, s) do { \
            wg_fence(); \
            first<(a), H128, (s) * 1024, H128>(acc, da, db); mma128_ss<(a) + 2, H128, (s) * 1024 + 128, H128>(acc, da, db); \
            mma128_ss<(a) + 4, H128, (s) * 1024 + 256, H128>(acc, da, db); mma128_ss<(a) + 6, H128, (s) * 1024 + 384, H128>(acc, da, db); \
            wg_commit(); } while (0)
        G_LOAD(0, 4);
        e_arrive(BAR(B_GE));
        O_BLOCK(0, kq, (kq + 16));
        mbar_wait(BAR(B_OWN), 0);
        mbar_wait(BAR(B_FD), 0);
        D_MMA(mma128_ss0, 0, 0);
        O_BLOCK(1, ph0, ph1);
        reg_inc<232>();
        mbar_wait(BAR(B_OWN + 1), 0);
        #undef O_BLOCK
        #define D_STEP(n) do { \
            mbar_wait(BAR(B_FD + ((n) & 3)), ((n) >> 2) & 1); \
            if (warp == 0) TR(112 + (n)); \
            D_MMA(mma128_ss, (n) == 5 ? OFF_X1 / 16 : ((n) & 3) * 1024, (n) & 3); \
            if ((n) == 3) mbar_wait(BAR(B_UF), 0); \
            if ((n) >= 3 && (n) < 7) { F_LOAD(uf, OFF_F2, 2 * (((n) + 5) & 7)); F_LOAD(uf, OFF_F2, 2 * (((n) + 5) & 7) + 1); } \
            wg_wait<1>(); \
            if ((n) == 7) fence_async_smem();         \
            if ((n) > 2) e_arrive(BAR(B_ED + (((n) + 3) & 3))); } while (0)
        D_STEP(1);
        wg_wait<0>();
        e_arrive(BAR(B_ED + 1));
        D_STEP(2);
        if (warp == 0) TS(31);
        D_STEP(3); D_STEP(4); D_STEP(5); D_STEP(6); D_STEP(7); D_STEP(8); D_STEP(9); D_STEP(10); D_STEP(11); D_STEP(12); D_STEP(13); D_STEP(14); D_STEP(15);
        #undef D_STEP
        #undef D_MMA
        mbar_wait(BAR(B_PAR), 0);
        const uint4 mis = lds128(sb + OFF_CHK + 128);
        if (mis.x ^ mis.y ^ mis.z ^ mis.w) {
            const uint2 rt = lds64(sb + OFF_CST);
            const int rb = (rt.x >> 3) & 15;
            wg_wait<0>();
            poll_flags(FLO(2, rb * 8 + (lane & 7)), rt.y);
            #pragma unroll 1
            for (int kb = 0; kb < 16; kb++) {
                bar_sync(1, 256);
                if (warp == 0) {
                    e_arrive_tx(BAR(B_RD), 32768);
                    bulk_load(sb + OFF_R0 + 32768, p.s->os + (size_t)(rb * 16 + kb) * 1024, 16384, BAR(B_RD));
                    tma_load4(sb + OFF_DB + 32768, &tmWo, kb * 64, (rt.x & 7) * 2, BAR(B_RD));
                }
                mbar_wait(BAR(B_RD), kb & 1);
                wg_fence();
                mma128_ssp<2048, H128, 2048, H128>(acc, da, db, kb); mma128_ss<2050, H128, 2048 + 128, H128>(acc, da, db);
                mma128_ss<2052, H128, 2048 + 256, H128>(acc, da, db); mma128_ss<2054, H128, 2048 + 384, H128>(acc, da, db);
                wg_commit();
                wg_wait<0>();
            }
        }
        #define XADDR(i) ((xa ^ (((i) & 3) << 5)) + ((i) < 4 ? OFF_R0 : OFF_X1))
        const uint4 cst = lds128(sb + OFF_CST);
        const int b = cst.x & 255;
        const uint32_t tag = cst.y, xa = T128(tid + (cst.x >> 16));
        uint4 w[4];
        const uint32_t rl = warp * 16 + g + 8 * (c & 1);
        const uint4* ws = pin_ptr(p.s->llln2 + ((b & ~7) + (c >> 1) * 4) * 128 + rl);
        {
        {
            uint32_t x2[8][4];
            mbar_wait(BAR(B_WPHI), 1);
            #pragma unroll
            for (int i = 0; i < 8; i++) ldsm4(x2[i], XADDR(i));
            uint4* d = pin_ptr(p.s->llln2 + b * 128 + warp * 16 + g);
            const uint32_t ta = sb + OFF_T1 + (g & 1) * 512 + c * 16;
            uint4 t = lds128(ta), tn = lds128(ta + 64);
            wg_wait<0>();
            acc_fence(acc);
            e_arrive(BAR(B_ED + 3));
            if (warp == 0) TS(32);
            float sd[4] = {0.f, 0.f, 0.f, 0.f}, qa[4] = {0.f, 0.f, 0.f, 0.f}, qb[4] = {0.f, 0.f, 0.f, 0.f};
            #pragma unroll
            for (int i = 0; i < 8; i++) {
                x2[i][0] = hadd2(x2[i][0], hmul2(t.x, pack2(acc[8 * i], acc[8 * i + 1]))); x2[i][1] = hadd2(x2[i][1], hmul2(t.x, pack2(acc[8 * i + 2], acc[8 * i + 3])));
                x2[i][2] = hadd2(x2[i][2], hmul2(t.y, pack2(acc[8 * i + 4], acc[8 * i + 5]))); x2[i][3] = hadd2(x2[i][3], hmul2(t.y, pack2(acc[8 * i + 6], acc[8 * i + 7])));
                mma16816(sd, x2[i][0], x2[i][1], x2[i][2], x2[i][3], t.z, t.w);
                t = tn;
                if (i < 6) tn = lds128(ta + (i + 2) * 64);
                mma16816(qa, x2[i][0], x2[i][1], x2[i][2], x2[i][3], x2[i][0], x2[i][2]);
                mma16816(qb, x2[i][0], x2[i][1], x2[i][2], x2[i][3], x2[i][1], x2[i][3]);
            }
            if (c == (g >> 1)) {
                st_ll(d, f2u(sd[0]), f2u((g & 1) ? qa[1] : qa[0]), f2u(sd[1]), tag);
                st_ll(d + 8, f2u(sd[2]), f2u((g & 1) ? qb[3] : qb[2]), f2u(sd[3]), tag);
            }
            __syncwarp();
            #pragma unroll
            for (int i = 0; i < 4; i++) w[i] = ld_ll(ws + i * 128);
            if (warp == 0) TS(33);
            #pragma unroll
            for (int i = 0; i < 8; i++) stsm4(XADDR(i), x2[i][0], x2[i][1], x2[i][2], x2[i][3]);
        }
        uint4 t2[8]; uint2 t3[8];
        #pragma unroll
        for (int i = 0; i < 8; i++) { t2[i] = lds128(sb + OFF_T2 + i * 64 + c * 16); t3[i] = lds64(sb + OFF_T3 + i * 32 + c * 8); }
        mbar_wait(BAR(B_ED + 3), 1);
        {
            #pragma unroll 1
            for (int it = 0; it < POLL_MAX; it++) {
                if (__all_sync(0xffffffffu, !(tag_bad(w[0].w ^ tag, w[1].w, tag) | tag_bad(w[2].w ^ tag, w[3].w, tag)))) break;
                #pragma unroll
                for (int i = 0; i < 4; i++) if (w[i].w != tag) w[i] = ld_ll(ws + i * 128);
            }
            float s1 = (u2f(w[0].x) + u2f(w[1].x)) + (u2f(w[2].x) + u2f(w[3].x));
            float s2 = (u2f(w[0].y) + u2f(w[1].y)) + (u2f(w[2].y) + u2f(w[3].y));
            float dt = (u2f(w[0].z) + u2f(w[1].z)) + (u2f(w[2].z) + u2f(w[3].z));
            s1 += shfl_x(s1, 2); s2 += shfl_x(s2, 2); dt += shfl_x(dt, 2);
            uint32_t m2, rh, rl2; float rinv;
            ln_final(s1, s2, m2, rinv);
            const uint32_t key = (f2key(fmaf(fmaf(-bf_lo(m2), u2f(cst.z), dt), rinv, u2f(cst.w))) | 2047u) ^ ((b >> 3) * 128 + rl);
            split_rcp(rinv, rh, rl2);
            if (c < 2) { sts32(sb + OFF_KEY + rl * 4, key); sts128(sb + OFF_ST2 + rl * 16, make_uint4(m2, rh, rl2, 0)); }
            __syncwarp();
            e_arrive(BAR(B_KEYS));
        }
        if (warp == 0) TS(34);
        {
            const uint4 s0 = lds128(sb + OFF_ST2 + (warp * 16 + g) * 16), s1 = lds128(sb + OFF_ST2 + (warp * 16 + g + 8) * 16);
            uint32_t x2[8][4];
            #pragma unroll
            for (int i = 0; i < 8; i++) ldsm4(x2[i], XADDR(i));
            const uint32_t oa = xa + warp * 2048u;
            #pragma unroll
            for (int i = 0; i < 8; i++) {
                const uint4 t = t2[i]; const uint2 gb = t3[i];
                stsm4((oa ^ ((i & 3) << 5)) + OFF_OUT + (i >> 2) * 2048u,
                      hadd2(x2[i][0], hmul2(gb.x, lnmod(x2[i][0], s0.x, s0.y, s0.z, t.x, t.z))), hadd2(x2[i][1], hmul2(gb.x, lnmod(x2[i][1], s1.x, s1.y, s1.z, t.x, t.z))),
                      hadd2(x2[i][2], hmul2(gb.y, lnmod(x2[i][2], s0.x, s0.y, s0.z, t.y, t.w))), hadd2(x2[i][3], hmul2(gb.y, lnmod(x2[i][3], s1.x, s1.y, s1.z, t.y, t.w))));
            }
            __syncwarp();
            e_arrive(BAR(B_SWP));
        }
        }
        #undef XADDR
        if (warp == 0) TS(35);
        uint32_t fx = 0, fh = 0, fg = 0, fs2, frow;
        uint32_t df[16][4];
        const uint32_t dfo = sb + warp * 4096u + ((lane & 7) + (lane >> 4) * 8) * 128u + ((((lane >> 3) & 1) ^ (lane & 7)) << 4);
        #define DF_LOAD(i) ldsm4t(df[i], (dfo + ((i) < 8 ? OFF_F2 : OFF_DB) + ((i) & 1) * 2048u) ^ ((((i) >> 1) & 3) << 5))
        {
            const int wi = ((tid >> 3) & 7) * 32 + (tid >> 6) * 8 + (tid & 7);
            const uint4* rh = pin_ptr(p.s->llrowh + wi);
            #pragma unroll
            for (int i = 8; i < 16; i++) F_LOAD(uf, OFF_F2, i);
            mbar_wait(BAR(B_SEL) + ((AWAKE & 4) ? awake_zero() : 0), 0);
            const uint2 bb = lds64(sb + OFF_CST + 24);
            const uint32_t b0 = bb.x, b1 = bb.y;
            if (warp == 0) TS(36);
            const uint32_t o0 = (~b0 & 0x780u) * 4, o1 = (~b1 & 0x780u) * 4, slot0 = o0, slot1 = o1 + (o0 == o1 ? 256 : 0);
            const int wd = ((g & 1) ? slot1 : slot0) + b * 2 + (c >> 1) - wi;
            uint4 hv[2], fv[2];
            #pragma unroll 1
            for (int it = 0; it < POLL_MAX; it++) {
                hv[0] = ld_ll(rh + slot0); hv[1] = ld_ll(rh + slot1);
                uint32_t bad = 0;
                if (warp == 0) {
                    fv[0] = ld_ll(rh + wd + 8192); fv[1] = ld_ll(rh + wd);
                    bad = tag_bad(fv[0].w ^ tag, fv[1].w, tag);
                    fx = (g & 2) ? fv[0].y : fv[0].x; fh = (g & 2) ? fv[1].y : fv[1].x; fg = (g & 2) ? fv[0].z : fv[1].z;
                }
                if (it == 0) {
                    mbar_wait(BAR(B_WD), 0);
                    #pragma unroll
                    for (int i = 0; i < NDF; i++) DF_LOAD(i);
                }
                if (__all_sync(0xffffffffu, !ll_bad<1>(ll_bad<1>(bad, hv[0], tag), hv[1], tag))) break;
            }
            const uint32_t ha = sb + OFF_HSEL + (tid >> 3) * 128u + c * 16u + (g & 1) * 8u;
            sts64(ha, hv[0].x, hv[0].y); sts64(ha + 64, hv[1].x, hv[1].y);
            bar_sync(2 + (warp >> 1), 64);
            const uint32_t bk = (g & 1) ? b1 : b0;
            frow = ~bk & 2047u;
            const float sg = sigmoid_f(rbf(key2f((bk & ~2047u) | 1024u)));
            fs2 = pack2(sg, sg);
        }
        if (warp == 0) TS(37);
        uint4* yd = p.s->lly + (cst.x >> 8) * 512 + (warp * 8 + c) * 8 + g;
        const uint4* ys = p.s->lly + (tid >> 2) * 512 + b * 4 + c;
        uint16_t* od = (uint16_t*)p.out + (size_t)frow * 1024 + (b >> 1) * 16 + (b & 1) * 4 + c + 8 * (g >> 1);
        {
            float ag[2][4], au[2][4];
            #pragma unroll
            for (int i = 0; i < 4; i++) ag[0][i] = ag[1][i] = au[0][i] = au[1][i] = 0.f;
            const uint32_t ha = sb + OFF_HSEL + (warp >> 1) * 1024u + (lane & 7) * 16u;
            uint4 hn = lds128(ha), hm = lds128(ha + 128);
            #pragma unroll
            for (int i = 0; i < 8; i++) {
                const uint4 h = hn;
                hn = hm;
                if (i < 6) hm = lds128(ha + (i + 2) * 128u);
                mma16816(ag[0], gf[2 * i][0], gf[2 * i][1], gf[2 * i][2], gf[2 * i][3], h.x, h.y);
                mma16816(au[0], uf[2 * i][0], uf[2 * i][1], uf[2 * i][2], uf[2 * i][3], h.x, h.y);
                mma16816(ag[1], gf[2 * i + 1][0], gf[2 * i + 1][1], gf[2 * i + 1][2], gf[2 * i + 1][3], h.z, h.w);
                mma16816(au[1], uf[2 * i + 1][0], uf[2 * i + 1][1], uf[2 * i + 1][2], uf[2 * i + 1][3], h.z, h.w);
                if (NDF + 2 * i < 16) { DF_LOAD((NDF + 2 * i) & 15); DF_LOAD((NDF + 2 * i + 1) & 15); }
            }
            sts64(sb + OFF_RED + (warp >> 1) * 512u + (c & 1) * 256u + ((warp & 1) * 16 + (c >> 1) * 8 + g) * 8u,
                  f2u(sel4(c, ag[0][0], ag[0][1], ag[0][2], ag[0][3]) + sel4(c, ag[1][0], ag[1][1], ag[1][2], ag[1][3])),
                  f2u(sel4(c, au[0][0], au[0][1], au[0][2], au[0][3]) + sel4(c, au[1][0], au[1][1], au[1][2], au[1][3])));
        }
        yd = pin_ptr(yd); ys = pin_ptr(ys); od = pin_ptr(od); pin<1>(&fs2);
        bar_sync(1, 256);
        {
            const uint32_t ra = sb + OFF_RED + lane * 16u;
            const uint4 r0 = lds128(ra), r1 = lds128(ra + 512), r2 = lds128(ra + 1024), r3 = lds128(ra + 1536);
            #define F4(f) ((u2f(r0.f) + u2f(r1.f)) + (u2f(r2.f) + u2f(r3.f)))
            const uint32_t hid = hmul2(silu2(pack2(F4(x), F4(z))), pack2(F4(y), F4(w)));
            #undef F4
            if (warp == 0) TS(38);
            const int src = (g & 1) * 16 + c;
            const uint32_t b0 = __shfl_sync(0xffffffffu, hid, src), b1 = __shfl_sync(0xffffffffu, hid, src + 4), b2 = __shfl_sync(0xffffffffu, hid, src + 8), b3 = __shfl_sync(0xffffffffu, hid, src + 12);
            float y[8][4];
            #pragma unroll
            for (int i = 0; i < 8; i++) {
                y[i][0] = y[i][1] = y[i][2] = y[i][3] = 0.f;
                mma16816(y[i], df[2 * i][0], df[2 * i][1], df[2 * i][2], df[2 * i][3], b0, b1);
            }
            #pragma unroll
            for (int i = 0; i < 8; i++) mma16816(y[i], df[2 * i + 1][0], df[2 * i + 1][1], df[2 * i + 1][2], df[2 * i + 1][3], b2, b3);
            if (cst.x < 112 * 256) {
                #pragma unroll
                for (int h = 0; h < 2; h++) {
                    #define YS(e) sel4(c, y[4 * h][e], y[4 * h + 1][e], y[4 * h + 2][e], y[4 * h + 3][e])
                    st_ll4(yd + 32 * h, YS(0), YS(1), YS(2), YS(3), tag);
                    #undef YS
                }
            }
        }
        if (warp == 0) TS(39);
        if (warp < 7) {
            uint4 v[2];
            v[0].w = v[1].w = 0;
            spin_until(clk32() + YWAIT);
            #pragma unroll 1
            for (int it = 0; it < POLL_MAX; it++) {
                if ((v[0].w ^ tag) & 3) v[0] = ld_ll(ys);
                if ((v[1].w ^ tag) & 3) v[1] = ld_ll(ys + 56 * 512);
                if (__all_sync(0xffffffffu, !(tag_bad(v[0].w ^ tag, v[1].w, tag) & 3))) break;
            }
            float y0 = u2f(v[0].x) + u2f(v[1].x), y1 = u2f(v[0].y) + u2f(v[1].y), y2 = u2f(v[0].z) + u2f(v[1].z), y3 = u2f(v[0].w) + u2f(v[1].w);
            const bool g0 = g & 1, g1 = g & 2;
            const float k0 = (g0 ? y1 : y0) + shfl_x(g0 ? y0 : y1, 4), k1 = (g0 ? y3 : y2) + shfl_x(g0 ? y2 : y3, 4);
            const float y = (g1 ? k1 : k0) + shfl_x(g1 ? k0 : k1, 8);
            stsf(sb + OFF_RED2 + (lane & 15) * 64u + (lane >> 4) * 32u + warp * 4u, y);
            bar_sync(6, 224);
            if (tid < 16) {
                const uint32_t a = sb + OFF_RED2 + lane * 64u;
                const uint4 ya = lds128(a), yb = lds128(a + 16), yc = lds128(a + 32), ye = lds128(a + 48);
                const float s = (((u2f(ya.x) + u2f(ya.y)) + (u2f(ya.z) + u2f(ya.w))) + ((u2f(yb.x) + u2f(yb.y)) + u2f(yb.z)))
                              + (((u2f(yc.x) + u2f(yc.y)) + (u2f(yc.z) + u2f(yc.w))) + ((u2f(ye.x) + u2f(ye.y)) + u2f(ye.z)));
                const uint32_t o = hadd2(fx, hmul2(fg, hadd2(fh, hmul2(pack2(s, s), fs2))));
                *od = (c & 1) ? o >> 16 : o;
                if (b == 0 && tid == 0) p.s->done[0] = tag;
                TS(40);
            }
        }
    }
}

typedef CUresult (*EncodeFn)(CUtensorMap*, CUtensorMapDataType, cuuint32_t, void*, const cuuint64_t*, const cuuint64_t*, const cuuint32_t*,
                             const cuuint32_t*, CUtensorMapInterleave, CUtensorMapSwizzle, CUtensorMapL2promotion, CUtensorMapFloatOOBfill);

CUtensorMap make_map(EncodeFn enc, const void* ptr, uint64_t cols, uint64_t rows, uint32_t bc, uint32_t br, CUtensorMapSwizzle swz, CUtensorMapL2promotion promo) {
    CUtensorMap m;
    cuuint64_t dims[2] = {cols, rows}, strides[1] = {cols * 2};
    cuuint32_t box[2] = {bc, br}, es[2] = {1, 1};
    enc(&m, CU_TENSOR_MAP_DATA_TYPE_BFLOAT16, 2, const_cast<void*>(ptr), dims, strides, box, es, CU_TENSOR_MAP_INTERLEAVE_NONE, swz, promo,
        CU_TENSOR_MAP_FLOAT_OOB_FILL_NONE);
    return m;
}
CUtensorMap make_map4(EncodeFn enc, const void* ptr, uint32_t groups, uint64_t rows, uint32_t br, CUtensorMapL2promotion promo) {
    CUtensorMap m;
    cuuint64_t dims[4] = {64, rows, 16, groups}, strides[3] = {groups * 2048ull, 128, 2048};
    cuuint32_t box[4] = {64, br, 2, groups}, es[4] = {1, 1, 1, 1};
    enc(&m, CU_TENSOR_MAP_DATA_TYPE_BFLOAT16, 4, const_cast<void*>(ptr), dims, strides, box, es, CU_TENSOR_MAP_INTERLEAVE_NONE, CU_TENSOR_MAP_SWIZZLE_128B, promo,
        CU_TENSOR_MAP_FLOAT_OOB_FILL_NONE);
    return m;
}

}

extern "C" void kernel_launch(void* const* d_in, const int* in_sizes, int n_in, void* d_out, int out_size) {
    (void)in_sizes; (void)n_in; (void)out_size;
    void* fn = nullptr; cudaDriverEntryPointQueryResult qr;
    cudaGetDriverEntryPoint("cuTensorMapEncodeTiled", &fn, cudaEnableDefault, &qr);
    EncodeFn enc = (EncodeFn)fn;
    void* hs = nullptr;
    cudaGetSymbolAddress(&hs, g_scratch);
    int dev = 0, sms = 0;
    cudaGetDevice(&dev);
    cudaDeviceGetAttribute(&sms, cudaDevAttrMultiProcessorCount, dev);
    const CUtensorMapL2promotion P256 = CU_TENSOR_MAP_L2_PROMOTION_L2_256B, P128 = CU_TENSOR_MAP_L2_PROMOTION_L2_128B, P0 = CU_TENSOR_MAP_L2_PROMOTION_NONE;
    CUtensorMap tmW = make_map4(enc, d_in[1], 3, 1024, 32, P256);
    CUtensorMap tmWo = make_map4(enc, d_in[3], 1, 1024, 64, P256);
    CUtensorMap tmO = make_map4(enc, d_out, 1, 2048, 16, P0);
    CUtensorMap tmPhi = make_map(enc, d_in[2], 32, 1024, 32, 128, CU_TENSOR_MAP_SWIZZLE_64B, P128);
    CUtensorMap tmG = make_map(enc, d_in[6], 3584, 1024, 32, 128, CU_TENSOR_MAP_SWIZZLE_64B, P0);
    CUtensorMap tmU = make_map(enc, d_in[7], 3584, 1024, 32, 128, CU_TENSOR_MAP_SWIZZLE_64B, P0);
    CUtensorMap tmD = make_map(enc, d_in[8], 1024, 3584, 64, 32, CU_TENSOR_MAP_SWIZZLE_128B, P128);
    CUtensorMap tmX = make_map(enc, d_in[0], 1024, 2048, 64, 128, CU_TENSOR_MAP_SWIZZLE_128B, P128);
    CUtensorMap tmM = make_map(enc, d_in[10], 6144, 1024, 64, 256, CU_TENSOR_MAP_SWIZZLE_128B, MPROMO);
    Ptrs p;
    p.x = (const bf16*)d_in[0]; p.c = (const bf16*)d_in[9]; p.wmod = (const bf16*)d_in[10]; p.wr = (const bf16*)d_in[5];
    p.wg = (const bf16*)d_in[6]; p.wu = (const bf16*)d_in[7]; p.wd = (const bf16*)d_in[8]; p.out = (bf16*)d_out; p.s = (Scratch*)hs;
    p.wqkv = (const bf16*)d_in[1]; p.wo = (const bf16*)d_in[3];
    p.by_sm = sms == 132;
    for (int sm = 0; sm < 132; sm++) {
        const int tp = sm >> 1, u = tp - 32;
        const int gp = (GPERM >> (4 * (tp < 32 ? tp & 7 : tp < 60 ? 1 + u % 7 : 0))) & 7, sl = 2 * (tp < 32 ? tp >> 3 : tp < 60 ? 4 + u / 7 : tp - 58) + (sm & 1);
        const int b = (tp >> 1) == 30 ? sm + 8 : ((gp >> 1) * 4 + (sl & 3)) * 8 + (gp & 1) * 4 + (sl >> 2);
        const int f = FMODE == 0 ? (b < 112 ? b : 255) : FMODE == 1 ? (sl < 14 && b < 128 ? gp * 14 + sl : 255) : (sm < 112 ? sm : 255);
        p.role[sm] = (uint16_t)(b | f << 8);
    }
    cudaFuncSetAttribute(fused_kernel, cudaFuncAttributeMaxDynamicSharedMemorySize, SMEM_BYTES);
    fused_kernel<<<132, NTHREADS, SMEM_BYTES, cudaStreamPerThread>>>(p, tmM, tmX, tmW, tmWo, tmPhi, tmG, tmU, tmD, tmO);
}
```

```cpp
#include <cuda_runtime.h>
#include <cuda.h>
#include <cuda_bf16.h>
#include <stdint.h>

namespace {

typedef __nv_bfloat16 bf16;

#define NFREE 4
constexpr int NTHREADS = 512;
constexpr int POLL_MAX = 400000;

constexpr uint32_t OFF_R0   = 0;
constexpr uint32_t OFF_A    = 65536;
constexpr uint32_t OFF_B    = 114688;
constexpr uint32_t OFF_V    = 65536;
constexpr uint32_t OFF_PHI  = 98304;
constexpr uint32_t OFF_F2   = 65536;
constexpr uint32_t OFF_DB   = 131072;
constexpr uint32_t OFF_KL   = 196608;
constexpr uint32_t OFF_WPHI = 214016;
constexpr uint32_t OFF_KVT  = OFF_WPHI;
constexpr uint32_t OFF_Z    = 222208;
constexpr uint32_t OFF_TAB  = OFF_Z;
constexpr uint32_t OFF_ONES = 226304;
constexpr uint32_t OFF_BAR  = 227328;
constexpr uint32_t OFF_CST  = OFF_BAR + 640;
constexpr uint32_t OFF_T1   = OFF_ONES;
constexpr uint32_t OFF_T2   = OFF_CST + 64;
constexpr uint32_t OFF_T3   = OFF_T2 + 512;
constexpr uint32_t OFF_KEY  = OFF_T3 + 256;
constexpr uint32_t OFF_ST2  = OFF_KEY + 512;
constexpr uint32_t OFF_CHK  = OFF_KEY;
constexpr uint32_t OFF_ZS   = OFF_ST2;
constexpr uint32_t SMEM_BYTES = 232448;
constexpr uint32_t OFF_X1   = OFF_KL;
constexpr uint32_t OFF_OUT  = OFF_R0 + 32768;
constexpr uint32_t OFF_HSEL = OFF_WPHI;
constexpr uint32_t OFF_RED  = OFF_WPHI + 4096;
constexpr uint32_t OFF_RED2 = OFF_RED + 2048;
static_assert(OFF_ST2 + 2048 <= SMEM_BYTES, "layout");

enum {
    B_O1 = 0, B_UF = 1, B_UD = 2, B_WPHI = 3, B_FB = 4  , B_OST = 8, B_GF = 9, B_WD = 10, B_KVL = 11  , B_KZ = 13, B_LMF = 14, B_SEL = 15, B_XP = 16  , B_TAG = 24,
    B_FA = 25  , B_FD = 30  , B_CAND = 34,
    B_PE = 35  , B_KST = 37  , B_KVT = 41  , B_LMD = 43, B_PAR = 44,
    B_EA = 45  , B_EB = 48  , B_PF = 56  , B_OWN = 60  , B_QE = 62, B_STP = 63, B_KEYS = 64, B_SWP = 65, B_STS = 66, B_GE = 67, B_CS = B_GE + 1  ,
    B_ED = 70  ,
    B_RD = 75
};

struct Scratch {
    uint4 os[16 * 16 * 1024];
    uint4 kvacc[8 * 4 * 528];
    uint4 flk[3 * 128 * 2];
    uint4 llstat[2048];
    uint4 llm1[16 * 64];
    uint4 flo[3 * 128 * 2];
    uint4 llmod2[2 * 256];
    uint4 llg[2 * 4 * 256];
    uint4 llln2[16 * 8 * 128];
    uint4 llcand[16 * 2];
    uint4 llrowh[32 * 256];
    uint4 llrowx[32 * 256];
    uint4 lly[128 * 512];
    unsigned done[4];
};
__device__ __align__(1024) Scratch g_scratch;
#define GT(i) do {} while (0)
#define TS(i) do {} while (0)
#define TR(i) do {} while (0)

__device__ __forceinline__ uint32_t smem_u32(const void* p) { return (uint32_t)__cvta_generic_to_shared(p); }
__device__ __forceinline__ uint32_t clk32() { uint32_t c; asm volatile("mov.u32 %0, %%clock;" : "=r"(c) :: "memory"); return c; }
__device__ __forceinline__ void spin_until(uint32_t t) { while ((int)(clk32() - t) < 0) {} }
__device__ __forceinline__ void sleep_until(uint32_t t) { while ((int)(clk32() - t) < 0) __nanosleep(40); }
__device__ __forceinline__ void mbar_init_fence() { asm volatile("fence.mbarrier_init.release.cluster;" ::: "memory"); }
__device__ __forceinline__ void mbar_wait(uint32_t bar, uint32_t parity) {
    asm volatile("{\n.reg .pred P1;\nLAB_WAIT:\nmbarrier.try_wait.parity.shared::cta.b64 P1, [%0], %1;\n@!P1 bra LAB_WAIT;\n}" :: "r"(bar), "r"(parity) : "memory");
}
__device__ __forceinline__ uint64_t policy_evict_first() { uint64_t p; asm("createpolicy.fractional.L2::evict_first.b64 %0, 1.0;" : "=l"(p)); return p; }
#define ELECT "{\n.reg .pred e;\nelect.sync _|e, 0xffffffff;\n@e "
__device__ __forceinline__ void e_arrive(uint32_t bar) { asm volatile(ELECT "mbarrier.arrive.shared::cta.b64 _, [%0];\n}" :: "r"(bar) : "memory"); }
__device__ __forceinline__ void e_arrive_after(uint32_t bar, uint32_t v) {
    asm volatile("{\n.reg .pred e;\n.reg .b32 n;\npopc.b32 n, %1;\nshr.u32 n, n, 4;\nmul.lo.u32 n, n, n;\nshr.u32 n, n, 3;\nadd.u32 n, n, %0;\n"
        "elect.sync _|e, 0xffffffff;\n@e mbarrier.arrive.shared::cta.b64 _, [n];\n}" :: "r"(bar), "r"(v) : "memory");
}
__device__ __forceinline__ void e_arrive_tx(uint32_t bar, uint32_t bytes) { asm volatile(ELECT "mbarrier.arrive.expect_tx.shared::cta.b64 _, [%0], %1;\n}" :: "r"(bar), "r"(bytes) : "memory"); }
__device__ __forceinline__ void e_init(uint32_t bar, uint32_t cnt) { asm volatile(ELECT "mbarrier.init.shared::cta.b64 [%0], %1;\n}" :: "r"(bar), "r"(cnt) : "memory"); }
__device__ __forceinline__ void tma_load_ef(uint32_t dst, const CUtensorMap* tm, int c0, int c1, uint32_t bar) {
    asm volatile(ELECT "cp.async.bulk.tensor.2d.shared::cluster.global.mbarrier::complete_tx::bytes.L2::cache_hint [%0], [%1, {%3, %4}], [%2], %5;\n}"
        :: "r"(dst), "l"(tm), "r"(bar), "r"(c0), "r"(c1), "l"(policy_evict_first()) : "memory");
}
__device__ __forceinline__ void tma_load(uint32_t dst, const CUtensorMap* tm, int c0, int c1, uint32_t bar) {
    asm volatile(ELECT "cp.async.bulk.tensor.2d.shared::cluster.global.mbarrier::complete_tx::bytes [%0], [%1, {%3, %4}], [%2];\n}"
        :: "r"(dst), "l"(tm), "r"(bar), "r"(c0), "r"(c1) : "memory");
}
__device__ __forceinline__ void tma_load4(uint32_t dst, const CUtensorMap* tm, int row, int blk, uint32_t bar) {
    asm volatile(ELECT "cp.async.bulk.tensor.4d.shared::cluster.global.mbarrier::complete_tx::bytes [%0], [%1, {0, %3, %4, 0}], [%2];\n}"
        :: "r"(dst), "l"(tm), "r"(bar), "r"(row), "r"(blk) : "memory");
}
__device__ __forceinline__ void tma_store4(const CUtensorMap* tm, int row, int blk, uint32_t src) {
    asm volatile(ELECT "cp.async.bulk.tensor.4d.global.shared::cta.bulk_group [%0, {0, %2, %3, 0}], [%1];\n}" :: "l"(tm), "r"(src), "r"(row), "r"(blk) : "memory");
}
__device__ __forceinline__ void bulk_load(uint32_t dst, const void* src, uint32_t bytes, uint32_t bar) {
    asm volatile(ELECT "cp.async.bulk.shared::cluster.global.mbarrier::complete_tx::bytes [%0], [%1], %2, [%3];\n}" :: "r"(dst), "l"(src), "r"(bytes), "r"(bar) : "memory");
}
__device__ __forceinline__ void bulk_store(void* dst, uint32_t src, uint32_t bytes) {
    asm volatile(ELECT "cp.async.bulk.global.shared::cta.bulk_group [%0], [%1], %2;\n}" :: "l"(dst), "r"(src), "r"(bytes) : "memory");
}
__device__ __forceinline__ void bulk_reduce(void* dst, uint32_t src, uint32_t bytes) {
    asm volatile(ELECT "cp.reduce.async.bulk.global.shared::cta.bulk_group.add.f32 [%0], [%1], %2;\n}" :: "l"(dst), "r"(src), "r"(bytes) : "memory");
}
__device__ __forceinline__ void tma_prefetch(const CUtensorMap* tm, int c0, int c1) {
    asm volatile(ELECT "cp.async.bulk.prefetch.tensor.2d.L2.global [%0, {%1, %2}];\n}" :: "l"(tm), "r"(c0), "r"(c1) : "memory");
}
__device__ __forceinline__ void l2_prefetch(const void* p, uint32_t bytes) {
    asm volatile(ELECT "cp.async.bulk.prefetch.L2.global [%0], %1;\n}" :: "l"(p), "r"(bytes) : "memory");
}
__device__ __forceinline__ void bulk_wait_read() { asm volatile("cp.async.bulk.commit_group;\ncp.async.bulk.wait_group.read 0;" ::: "memory"); }
__device__ __forceinline__ void bulk_wait() { asm volatile("cp.async.bulk.commit_group;\ncp.async.bulk.wait_group 0;" ::: "memory"); }
__device__ __forceinline__ void tmap_prefetch(const CUtensorMap* tm) { asm volatile("prefetch.tensormap [%0];" :: "l"(tm) : "memory"); }
__device__ __forceinline__ void wg_fence() { asm volatile("wgmma.fence.sync.aligned;" ::: "memory"); }
__device__ __forceinline__ void wg_commit() { asm volatile("wgmma.commit_group.sync.aligned;" ::: "memory"); }
template<int N> __device__ __forceinline__ void wg_wait() { asm volatile("wgmma.wait_group.sync.aligned %0;" :: "n"(N) : "memory"); }
template<int N> __device__ __forceinline__ void acc_fence(float (&d)[N]) {
    #pragma unroll
    for (int i = 0; i < N; i++) asm volatile("" : "+f"(d[i]) :: "memory");
}
__device__ __forceinline__ uint32_t desc_lo(uint32_t addr, uint32_t lbo) { return (addr >> 4) | ((lbo >> 4) << 16); }
constexpr uint32_t H128 = 0x40000040u;
constexpr uint32_t H64 = 0x80000020u;
__device__ __forceinline__ void fence_async_smem() { asm volatile("fence.proxy.async.shared::cta;" ::: "memory"); }
__device__ __forceinline__ void bar_sync(int id, int n) { asm volatile("bar.sync %0, %1;" :: "r"(id), "r"(n) : "memory"); }
template<int R> __device__ __forceinline__ void reg_inc() { asm volatile("setmaxnreg.inc.sync.aligned.u32 %0;" :: "n"(R)); }
template<int R> __device__ __forceinline__ void reg_dec() { asm volatile("setmaxnreg.dec.sync.aligned.u32 %0;" :: "n"(R)); }

__device__ __forceinline__ void stsm4(uint32_t addr, uint32_t r0, uint32_t r1, uint32_t r2, uint32_t r3) {
    asm volatile("stmatrix.sync.aligned.m8n8.x4.shared.b16 [%0], {%1,%2,%3,%4};" :: "r"(addr), "r"(r0), "r"(r1), "r"(r2), "r"(r3) : "memory");
}
__device__ __forceinline__ void ldsm4(uint32_t* r, uint32_t addr) {
    asm volatile("ldmatrix.sync.aligned.m8n8.x4.shared.b16 {%0,%1,%2,%3}, [%4];" : "=r"(r[0]), "=r"(r[1]), "=r"(r[2]), "=r"(r[3]) : "r"(addr) : "memory");
}
__device__ __forceinline__ void ldsm4t(uint32_t* r, uint32_t addr) {
    asm volatile("ldmatrix.sync.aligned.m8n8.x4.trans.shared.b16 {%0,%1,%2,%3}, [%4];" : "=r"(r[0]), "=r"(r[1]), "=r"(r[2]), "=r"(r[3]) : "r"(addr) : "memory");
}
__device__ __forceinline__ void mma16816(float (&d)[4], uint32_t a0, uint32_t a1, uint32_t a2, uint32_t a3, uint32_t b0, uint32_t b1) {
    asm volatile("mma.sync.aligned.m16n8k16.row.col.f32.bf16.bf16.f32 {%0,%1,%2,%3}, {%4,%5,%6,%7}, {%8,%9}, {%0,%1,%2,%3};"
        : "+f"(d[0]), "+f"(d[1]), "+f"(d[2]), "+f"(d[3]) : "r"(a0), "r"(a1), "r"(a2), "r"(a3), "r"(b0), "r"(b1));
}
__device__ __forceinline__ uint32_t awake_zero() {
    uint32_t r;
    asm volatile("{\n.reg .f32 d<4>;\nmma.sync.aligned.m16n8k8.row.col.f32.bf16.bf16.f32 {d0,d1,d2,d3}, {%1,%1}, {%1}, {%2,%2,%2,%2};\nmov.b32 %0, d0;\n}" : "=r"(r) : "r"(0), "f"(0.f));
    return r;
}
__device__ __forceinline__ void mbar_wait_awake(uint32_t bar, uint32_t parity) {
    #pragma unroll 1
    for (int it = 0; it < POLL_MAX; it++) {
        uint32_t ok;
        asm volatile("{\n.reg .pred p;\nmbarrier.try_wait.parity.shared::cta.b64 p, [%1], %2;\nselp.u32 %0, 0, 1, p;\n}" : "=r"(ok) : "r"(bar), "r"(parity) : "memory");
        if (__all_sync(0xffffffffu, ok == 0)) break;
        it += awake_zero();
    }
}
__device__ __forceinline__ uint4 lds128(uint32_t a) { uint4 v; asm volatile("ld.shared.v4.b32 {%0,%1,%2,%3}, [%4];" : "=r"(v.x), "=r"(v.y), "=r"(v.z), "=r"(v.w) : "r"(a) : "memory"); return v; }
__device__ __forceinline__ uint32_t lds32(uint32_t a) { uint32_t v; asm volatile("ld.shared.b32 %0, [%1];" : "=r"(v) : "r"(a) : "memory"); return v; }
__device__ __forceinline__ uint2 lds64(uint32_t a) { uint2 v; asm volatile("ld.shared.v2.b32 {%0,%1}, [%2];" : "=r"(v.x), "=r"(v.y) : "r"(a) : "memory"); return v; }
__device__ __forceinline__ float ldsf(uint32_t a) { float v; asm volatile("ld.shared.f32 %0, [%1];" : "=f"(v) : "r"(a) : "memory"); return v; }
__device__ __forceinline__ void sts128(uint32_t a, uint4 v) { asm volatile("st.shared.v4.b32 [%0], {%1,%2,%3,%4};" :: "r"(a), "r"(v.x), "r"(v.y), "r"(v.z), "r"(v.w) : "memory"); }
__device__ __forceinline__ void sts64(uint32_t a, uint32_t x, uint32_t y) { asm volatile("st.shared.v2.b32 [%0], {%1,%2};" :: "r"(a), "r"(x), "r"(y) : "memory"); }
__device__ __forceinline__ void sts32(uint32_t a, uint32_t x) { asm volatile("st.shared.b32 [%0], %1;" :: "r"(a), "r"(x) : "memory"); }
__device__ __forceinline__ void stsf(uint32_t a, float x) { asm volatile("st.shared.f32 [%0], %1;" :: "r"(a), "f"(x) : "memory"); }
__device__ __forceinline__ float u2f(uint32_t v) { return __uint_as_float(v); }
__device__ __forceinline__ uint32_t f2u(float v) { return __float_as_uint(v); }

__device__ __forceinline__ uint32_t ldg32(const void* p) { uint32_t v; asm volatile("ld.global.nc.b32 %0, [%1];" : "=r"(v) : "l"(p)); return v; }
__device__ __forceinline__ void stg128(void* p, uint4 v) { asm volatile("st.global.v4.b32 [%0], {%1,%2,%3,%4};" :: "l"(p), "r"(v.x), "r"(v.y), "r"(v.z), "r"(v.w) : "memory"); }
__device__ __forceinline__ void stg_zero(void* p) { stg128(p, make_uint4(0, 0, 0, 0)); }
__device__ __forceinline__ void fence_gpu() { asm volatile("fence.release.gpu;" ::: "memory"); }
__device__ __forceinline__ void st_ll(uint4* p, uint32_t x, uint32_t y, uint32_t z, uint32_t w) {
    asm volatile("st.relaxed.gpu.global.v4.b32 [%0], {%1,%2,%3,%4};" :: "l"(p), "r"(x), "r"(y), "r"(z), "r"(w) : "memory");
}
__device__ __forceinline__ uint4 ld_ll(const uint4* p) {
    uint4 v;
    asm volatile("ld.relaxed.gpu.global.v4.b32 {%0,%1,%2,%3}, [%4];" : "=r"(v.x), "=r"(v.y), "=r"(v.z), "=r"(v.w) : "l"(p) : "memory");
    return v;
}
template<uint32_t LUT> __device__ __forceinline__ uint32_t lop3(uint32_t a, uint32_t b, uint32_t c) { uint32_t d; asm("lop3.b32 %0, %1, %2, %3, %4;" : "=r"(d) : "r"(a), "r"(b), "r"(c), "n"(LUT)); return d; }
__device__ __forceinline__ uint32_t tag_bad(uint32_t bad, uint32_t w, uint32_t tag) { return lop3<0xF6>(bad, w, tag); }
__device__ __forceinline__ void st_ll4(uint4* p, float a, float b, float c, float d, uint32_t tag) { st_ll(p, f2u(a), f2u(b), f2u(c), lop3<0xD8>(f2u(d), tag, 3u)); }
__device__ __forceinline__ unsigned ld_rlx(const void* p) { unsigned v; asm volatile("ld.relaxed.gpu.global.u32 %0, [%1];" : "=r"(v) : "l"(p) : "memory"); return v; }
__device__ __forceinline__ void st_flag(uint4* p, uint32_t tag, uint32_t v, int lane) { if (lane < 2) st_ll(p + lane, tag, v, tag, v); }
__device__ __forceinline__ uint2 ld_flag(const uint4* p) { uint2 v; asm volatile("ld.relaxed.gpu.global.v2.b32 {%0,%1}, [%2];" : "=r"(v.x), "=r"(v.y) : "l"(p) : "memory"); return v; }
__device__ __forceinline__ uint32_t poll_flags(const uint4* f, uint32_t tag) {
    uint2 v = make_uint2(0, 0);
    #pragma unroll 1
    for (int it = 0; it < POLL_MAX; it++) {
        if (v.x != tag) v = ld_flag(f);
        if (__all_sync(0xffffffffu, v.x == tag)) break;
    }
    return v.y;
}
template<int Z> __device__ __forceinline__ uint32_t ll_bad(uint32_t bad, const uint4& v, uint32_t tag) {
    bad = tag_bad(bad, v.w, tag);
    return Z && lop3<0x80>(v.x, v.y, v.z) == ~0u ? 1u : bad;
}
template<int N, int Z, uint32_t M = ~0u, int AW = 0> __device__ __forceinline__ void poll_words(uint4 (&v)[N], const uint4* p, int stride, uint32_t tag) {
    #pragma unroll 1
    for (int it = 0; it < POLL_MAX; it++) {
        uint32_t bad = 0;
        #pragma unroll
        for (int i = 0; i < N; i++) v[i] = ld_ll(p + i * stride);
        #pragma unroll
        for (int i = 0; i < N; i++) bad = ll_bad<Z>(bad, v[i], tag);
        if (__all_sync(0xffffffffu, !(bad & M))) break;
        if (AW) it += awake_zero();
    }
}
constexpr uint32_t ONE2 = 0x3F803F80u;
__device__ __forceinline__ uint32_t pack2(float lo, float hi) { uint32_t d; asm("cvt.rn.bf16x2.f32 %0, %1, %2;" : "=r"(d) : "f"(hi), "f"(lo)); return d; }
__device__ __forceinline__ float bf_lo(uint32_t v) { return u2f(v << 16); }
__device__ __forceinline__ float bf_hi(uint32_t v) { return u2f(v & 0xffff0000u); }
__device__ __forceinline__ float rbf(float x) { return bf_lo(pack2(x, 0.f)); }
__device__ __forceinline__ uint32_t hsub2(uint32_t a, uint32_t b) { uint32_t d; asm("sub.rn.bf16x2 %0, %1, %2;" : "=r"(d) : "r"(a), "r"(b)); return d; }
__device__ __forceinline__ uint32_t hadd2(uint32_t a, uint32_t b) { uint32_t d; asm("add.rn.bf16x2 %0, %1, %2;" : "=r"(d) : "r"(a), "r"(b)); return d; }
__device__ __forceinline__ uint32_t hmul2(uint32_t a, uint32_t b) { uint32_t d; asm("mul.rn.bf16x2 %0, %1, %2;" : "=r"(d) : "r"(a), "r"(b)); return d; }
__device__ __forceinline__ uint32_t hfma2(uint32_t a, uint32_t b, uint32_t c) { uint32_t d; asm("fma.rn.bf16x2 %0, %1, %2, %3;" : "=r"(d) : "r"(a), "r"(b), "r"(c)); return d; }
__device__ __forceinline__ uint32_t hmax2(uint32_t a, uint32_t b) { uint32_t d; asm("max.bf16x2 %0, %1, %2;" : "=r"(d) : "r"(a), "r"(b)); return d; }
__device__ __forceinline__ uint32_t hmin2(uint32_t a, uint32_t b) { uint32_t d; asm("min.bf16x2 %0, %1, %2;" : "=r"(d) : "r"(a), "r"(b)); return d; }
__device__ __forceinline__ float ex2(float x) { float y; asm("ex2.approx.ftz.f32 %0, %1;" : "=f"(y) : "f"(x)); return y; }
__device__ __forceinline__ float rcp(float x) { float y; asm("rcp.approx.ftz.f32 %0, %1;" : "=f"(y) : "f"(x)); return y; }
__device__ __forceinline__ float shfl_x(float v, int m) { return __shfl_xor_sync(0xffffffffu, v, m); }
__device__ __forceinline__ uint32_t hdiv2(uint32_t d, uint32_t rh, uint32_t rl) { return hfma2(d, rh, hmul2(d, rl)); }
__device__ __forceinline__ void split_rcp(float r, uint32_t& rh, uint32_t& rl) { rh = pack2(r, r); const float l = r - bf_lo(rh); rl = pack2(l, l); }
__device__ __forceinline__ uint32_t lnmod(uint32_t x, uint32_t m, uint32_t rh, uint32_t rl, uint32_t a, uint32_t s) { return hadd2(hmul2(hdiv2(hsub2(x, m), rh, rl), a), s); }
__device__ __forceinline__ void ln_final(float s1, float s2, uint32_t& m2, float& rinv) {
    const float mean = s1 * (1.0f / 1024.0f), var = fmaf(-mean, mean, s2 * (1.0f / 1024.0f));
    m2 = pack2(mean, mean);
    float sd;
    asm("sqrt.approx.ftz.f32 %0, %1;" : "=f"(sd) : "f"(rbf(rbf(fmaxf(var, 0.f)) + 1e-5f)));
    rinv = rcp(rbf(sd));
}
__device__ __forceinline__ float sigmoid_f(float x) { return rcp(1.0f + ex2(-1.4426950408889634f * x)); }
__device__ __forceinline__ uint32_t silu2(uint32_t v) { return pack2(bf_lo(v) * sigmoid_f(bf_lo(v)), bf_hi(v) * sigmoid_f(bf_hi(v))); }
__device__ __forceinline__ uint32_t f2key(float f) { uint32_t u = f2u(f); return (u & 0x80000000u) ? ~u : (u | 0x80000000u); }
__device__ __forceinline__ float key2f(uint32_t k) { return u2f((k & 0x80000000u) ? k ^ 0x80000000u : ~k); }
template<int N> __device__ __forceinline__ void top2(uint32_t (&k)[N], uint32_t& b0, uint32_t& b1) {
    uint32_t m = k[0];
    #pragma unroll
    for (int i = 1; i < N; i++) m = max(m, k[i]);
    b0 = __reduce_max_sync(0xffffffffu, m);
    m = 0;
    #pragma unroll
    for (int i = 0; i < N; i++) m = max(m, k[i] == b0 ? 0u : k[i]);
    b1 = __reduce_max_sync(0xffffffffu, m);
}
template<class T> __device__ __forceinline__ T sel4(int c, T a0, T a1, T a2, T a3) { return (c & 2) ? ((c & 1) ? a3 : a2) : ((c & 1) ? a1 : a0); }

__device__ __forceinline__ void fm_max(const float (&a)[16], uint32_t* p, uint32_t* mm) {
    #pragma unroll
    for (int i = 0; i < 8; i++) p[i] = pack2(a[2 * i], a[2 * i + 1]);
    #pragma unroll
    for (int h = 0; h < 2; h++) {
        const uint32_t mx = hmax2(hmax2(p[h], p[2 + h]), hmax2(p[4 + h], p[6 + h]));
        const uint32_t mn = hmin2(hmin2(p[h], p[2 + h]), hmin2(p[4 + h], p[6 + h])) ^ 0x80008000u;
        mm[h] = hmax2(__byte_perm(mx, mn, 0x5410), __byte_perm(mx, mn, 0x7632));
    }
    #pragma unroll
    for (int d = 1; d <= 2; d++) { mm[0] = hmax2(mm[0], __shfl_xor_sync(0xffffffffu, mm[0], d)); mm[1] = hmax2(mm[1], __shfl_xor_sync(0xffffffffu, mm[1], d)); }
}
constexpr float LOG2E = 1.4426950408889634f;
__device__ __forceinline__ void fm_pos(const uint32_t* p, const uint32_t* mm, float (&e)[32]) {
    #pragma unroll
    for (int h = 0; h < 2; h++) {
        const float cp = -bf_lo(mm[h]) * LOG2E;
        #pragma unroll
        for (int j = 0; j < 4; j++) {
            const float f0 = bf_lo(p[2 * j + h]), f1 = bf_hi(p[2 * j + h]);
            e[8 * h + 2 * j] = ex2(fmaf(f0, LOG2E, cp)); e[8 * h + 2 * j + 1] = ex2(fmaf(f1, LOG2E, cp));
            e[16 + 8 * h + 2 * j] = f0; e[16 + 8 * h + 2 * j + 1] = f1;
        }
    }
}
__device__ __forceinline__ void fm_neg(const uint32_t* mm, float nl, float (&e)[32]) {
    #pragma unroll
    for (int i = 16; i < 32; i++) e[i] = ex2(fmaf(e[i], -LOG2E, bf_hi(mm[(i >> 3) & 1]) * (i < 16 + NFREE ? -LOG2E : nl)));
}
__device__ __forceinline__ void fm_norm(const float (&e)[32], uint32_t* ph) {
    float s[4];
    #pragma unroll
    for (int k = 0; k < 4; k++) s[k] = ((e[8 * k] + e[8 * k + 1]) + (e[8 * k + 2] + e[8 * k + 3])) + ((e[8 * k + 4] + e[8 * k + 5]) + (e[8 * k + 6] + e[8 * k + 7]));
    #pragma unroll
    for (int k = 0; k < 4; k++) s[k] += shfl_x(s[k], 1);
    #pragma unroll
    for (int k = 0; k < 4; k++) s[k] = rcp(s[k] + shfl_x(s[k], 2));
    #pragma unroll
    for (int k = 0; k < 4; k++)
        #pragma unroll
        for (int j = 0; j < 4; j++) ph[8 * (k >> 1) + 2 * j + (k & 1)] = pack2(e[8 * k + 2 * j] * s[k], e[8 * k + 2 * j + 1] * s[k]);
}
template<class T> __device__ __forceinline__ T* pin_ptr(T* p) { asm volatile("" : "+l"(p) :: "memory"); return p; }
template<int N> __device__ __forceinline__ void pin(uint32_t* d) {
    #pragma unroll
    for (int i = 0; i < N; i++) asm volatile("" : "+r"(d[i]) :: "memory");
}

template<uint32_t BO, uint32_t BH> __device__ __forceinline__ void mma192_rs(float (&d)[96], const uint32_t* a, uint32_t blo) {
  asm volatile("{\n.reg .pred p;\n.reg .b32 ta, tb;\n.reg .b64 da, db;\nadd.u32 tb, %100, %101;\nmov.b64 db, {tb, %102};\nsetp.ne.b32 p, 1, 0;\n"
    "wgmma.mma_async.sync.aligned.m64n192k16.f32.bf16.bf16 {%0, %1, %2, %3, %4, %5, %6, %7, %8, %9, %10, %11, %12, %13, %14, %15, %16, %17, %18, %19, %20, %21, %22, %23, %24, %25, %26, %27, %28, %29, %30, %31, %32, %33, %34, %35, %36, %37, %38, %39, %40, %41, %42, %43, %44, %45, %46, %47, %48, %49, %50, %51, %52, %53, %54, %55, %56, %57, %58, %59, %60, %61, %62, %63, %64, %65, %66, %67, %68, %69, %70, %71, %72, %73, %74, %75, %76, %77, %78, %79, %80, %81, %82, %83, %84, %85, %86, %87, %88, %89, %90, %91, %92, %93, %94, %95}, {%96,%97,%98,%99}, db, p, 1, 1, 1;\n}\n"
    : "+f"(d[0]), "+f"(d[1]), "+f"(d[2]), "+f"(d[3]), "+f"(d[4]), "+f"(d[5]), "+f"(d[6]), "+f"(d[7]), "+f"(d[8]), "+f"(d[9]), "+f"(d[10]), "+f"(d[11]), "+f"(d[12]), "+f"(d[13]), "+f"(d[14]), "+f"(d[15]), "+f"(d[16]), "+f"(d[17]), "+f"(d[18]), "+f"(d[19]), "+f"(d[20]), "+f"(d[21]), "+f"(d[22]), "+f"(d[23]), "+f"(d[24]), "+f"(d[25]), "+f"(d[26]), "+f"(d[27]), "+f"(d[28]), "+f"(d[29]), "+f"(d[30]), "+f"(d[31]), "+f"(d[32]), "+f"(d[33]), "+f"(d[34]), "+f"(d[35]), "+f"(d[36]), "+f"(d[37]), "+f"(d[38]), "+f"(d[39]), "+f"(d[40]), "+f"(d[41]), "+f"(d[42]), "+f"(d[43]), "+f"(d[44]), "+f"(d[45]), "+f"(d[46]), "+f"(d[47]), "+f"(d[48]), "+f"(d[49]), "+f"(d[50]), "+f"(d[51]), "+f"(d[52]), "+f"(d[53]), "+f"(d[54]), "+f"(d[55]), "+f"(d[56]), "+f"(d[57]), "+f"(d[58]), "+f"(d[59]), "+f"(d[60]), "+f"(d[61]), "+f"(d[62]), "+f"(d[63]), "+f"(d[64]), "+f"(d[65]), "+f"(d[66]), "+f"(d[67]), "+f"(d[68]), "+f"(d[69]), "+f"(d[70]), "+f"(d[71]), "+f"(d[72]), "+f"(d[73]), "+f"(d[74]), "+f"(d[75]), "+f"(d[76]), "+f"(d[77]), "+f"(d[78]), "+f"(d[79]), "+f"(d[80]), "+f"(d[81]), "+f"(d[82]), "+f"(d[83]), "+f"(d[84]), "+f"(d[85]), "+f"(d[86]), "+f"(d[87]), "+f"(d[88]), "+f"(d[89]), "+f"(d[90]), "+f"(d[91]), "+f"(d[92]), "+f"(d[93]), "+f"(d[94]), "+f"(d[95])
    : "r"(a[0]), "r"(a[1]), "r"(a[2]), "r"(a[3]), "r"(blo), "n"(BO), "n"(BH));
}
template<uint32_t BO, uint32_t BH> __device__ __forceinline__ void mma192_rsp(float (&d)[96], const uint32_t* a, uint32_t blo, int sc) {
  asm volatile("{\n.reg .pred p;\n.reg .b32 ta, tb;\n.reg .b64 da, db;\nadd.u32 tb, %100, %101;\nmov.b64 db, {tb, %102};\nsetp.ne.b32 p, %103, 0;\n"
    "wgmma.mma_async.sync.aligned.m64n192k16.f32.bf16.bf16 {%0, %1, %2, %3, %4, %5, %6, %7, %8, %9, %10, %11, %12, %13, %14, %15, %16, %17, %18, %19, %20, %21, %22, %23, %24, %25, %26, %27, %28, %29, %30, %31, %32, %33, %34, %35, %36, %37, %38, %39, %40, %41, %42, %43, %44, %45, %46, %47, %48, %49, %50, %51, %52, %53, %54, %55, %56, %57, %58, %59, %60, %61, %62, %63, %64, %65, %66, %67, %68, %69, %70, %71, %72, %73, %74, %75, %76, %77, %78, %79, %80, %81, %82, %83, %84, %85, %86, %87, %88, %89, %90, %91, %92, %93, %94, %95}, {%96,%97,%98,%99}, db, p, 1, 1, 1;\n}\n"
    : "+f"(d[0]), "+f"(d[1]), "+f"(d[2]), "+f"(d[3]), "+f"(d[4]), "+f"(d[5]), "+f"(d[6]), "+f"(d[7]), "+f"(d[8]), "+f"(d[9]), "+f"(d[10]), "+f"(d[11]), "+f"(d[12]), "+f"(d[13]), "+f"(d[14]), "+f"(d[15]), "+f"(d[16]), "+f"(d[17]), "+f"(d[18]), "+f"(d[19]), "+f"(d[20]), "+f"(d[21]), "+f"(d[22]), "+f"(d[23]), "+f"(d[24]), "+f"(d[25]), "+f"(d[26]), "+f"(d[27]), "+f"(d[28]), "+f"(d[29]), "+f"(d[30]), "+f"(d[31]), "+f"(d[32]), "+f"(d[33]), "+f"(d[34]), "+f"(d[35]), "+f"(d[36]), "+f"(d[37]), "+f"(d[38]), "+f"(d[39]), "+f"(d[40]), "+f"(d[41]), "+f"(d[42]), "+f"(d[43]), "+f"(d[44]), "+f"(d[45]), "+f"(d[46]), "+f"(d[47]), "+f"(d[48]), "+f"(d[49]), "+f"(d[50]), "+f"(d[51]), "+f"(d[52]), "+f"(d[53]), "+f"(d[54]), "+f"(d[55]), "+f"(d[56]), "+f"(d[57]), "+f"(d[58]), "+f"(d[59]), "+f"(d[60]), "+f"(d[61]), "+f"(d[62]), "+f"(d[63]), "+f"(d[64]), "+f"(d[65]), "+f"(d[66]), "+f"(d[67]), "+f"(d[68]), "+f"(d[69]), "+f"(d[70]), "+f"(d[71]), "+f"(d[72]), "+f"(d[73]), "+f"(d[74]), "+f"(d[75]), "+f"(d[76]), "+f"(d[77]), "+f"(d[78]), "+f"(d[79]), "+f"(d[80]), "+f"(d[81]), "+f"(d[82]), "+f"(d[83]), "+f"(d[84]), "+f"(d[85]), "+f"(d[86]), "+f"(d[87]), "+f"(d[88]), "+f"(d[89]), "+f"(d[90]), "+f"(d[91]), "+f"(d[92]), "+f"(d[93]), "+f"(d[94]), "+f"(d[95])
    : "r"(a[0]), "r"(a[1]), "r"(a[2]), "r"(a[3]), "r"(blo), "n"(BO), "n"(BH), "r"(sc));
}
template<uint32_t BO, uint32_t BH> __device__ __forceinline__ void mma32_rs(float (&d)[16], const uint32_t* a, uint32_t blo) {
  asm volatile("{\n.reg .pred p;\n.reg .b32 ta, tb;\n.reg .b64 da, db;\nadd.u32 tb, %20, %21;\nmov.b64 db, {tb, %22};\nsetp.ne.b32 p, 1, 0;\n"
    "wgmma.mma_async.sync.aligned.m64n32k16.f32.bf16.bf16 {%0, %1, %2, %3, %4, %5, %6, %7, %8, %9, %10, %11, %12, %13, %14, %15}, {%16,%17,%18,%19}, db, p, 1, 1, 1;\n}\n"
    : "+f"(d[0]), "+f"(d[1]), "+f"(d[2]), "+f"(d[3]), "+f"(d[4]), "+f"(d[5]), "+f"(d[6]), "+f"(d[7]), "+f"(d[8]), "+f"(d[9]), "+f"(d[10]), "+f"(d[11]), "+f"(d[12]), "+f"(d[13]), "+f"(d[14]), "+f"(d[15])
    : "r"(a[0]), "r"(a[1]), "r"(a[2]), "r"(a[3]), "r"(blo), "n"(BO), "n"(BH));
}
template<uint32_t BO, uint32_t BH> __device__ __forceinline__ void mma32_rs0(float (&d)[16], const uint32_t* a, uint32_t blo) {
  asm volatile("{\n.reg .pred p;\n.reg .b32 ta, tb;\n.reg .b64 da, db;\nadd.u32 tb, %20, %21;\nmov.b64 db, {tb, %22};\nsetp.ne.b32 p, 0, 0;\n"
    "wgmma.mma_async.sync.aligned.m64n32k16.f32.bf16.bf16 {%0, %1, %2, %3, %4, %5, %6, %7, %8, %9, %10, %11, %12, %13, %14, %15}, {%16,%17,%18,%19}, db, p, 1, 1, 1;\n}\n"
    : "=f"(d[0]), "=f"(d[1]), "=f"(d[2]), "=f"(d[3]), "=f"(d[4]), "=f"(d[5]), "=f"(d[6]), "=f"(d[7]), "=f"(d[8]), "=f"(d[9]), "=f"(d[10]), "=f"(d[11]), "=f"(d[12]), "=f"(d[13]), "=f"(d[14]), "=f"(d[15])
    : "r"(a[0]), "r"(a[1]), "r"(a[2]), "r"(a[3]), "r"(blo), "n"(BO), "n"(BH));
}
template<uint32_t BO, uint32_t BH> __device__ __forceinline__ void mma40_rs(float (&d)[20], const uint32_t* a, uint32_t blo) {
  asm volatile("{\n.reg .pred p;\n.reg .b32 ta, tb;\n.reg .b64 da, db;\nadd.u32 tb, %24, %25;\nmov.b64 db, {tb, %26};\nsetp.ne.b32 p, 1, 0;\n"
    "wgmma.mma_async.sync.aligned.m64n40k16.f32.bf16.bf16 {%0, %1, %2, %3, %4, %5, %6, %7, %8, %9, %10, %11, %12, %13, %14, %15, %16, %17, %18, %19}, {%20,%21,%22,%23}, db, p, 1, 1, 1;\n}\n"
    : "+f"(d[0]), "+f"(d[1]), "+f"(d[2]), "+f"(d[3]), "+f"(d[4]), "+f"(d[5]), "+f"(d[6]), "+f"(d[7]), "+f"(d[8]), "+f"(d[9]), "+f"(d[10]), "+f"(d[11]), "+f"(d[12]), "+f"(d[13]), "+f"(d[14]), "+f"(d[15]), "+f"(d[16]), "+f"(d[17]), "+f"(d[18]), "+f"(d[19])
    : "r"(a[0]), "r"(a[1]), "r"(a[2]), "r"(a[3]), "r"(blo), "n"(BO), "n"(BH));
}
template<uint32_t BO, uint32_t BH> __device__ __forceinline__ void mma40_rs0(float (&d)[20], const uint32_t* a, uint32_t blo) {
  asm volatile("{\n.reg .pred p;\n.reg .b32 ta, tb;\n.reg .b64 da, db;\nadd.u32 tb, %24, %25;\nmov.b64 db, {tb, %26};\nsetp.ne.b32 p, 0, 0;\n"
    "wgmma.mma_async.sync.aligned.m64n40k16.f32.bf16.bf16 {%0, %1, %2, %3, %4, %5, %6, %7, %8, %9, %10, %11, %12, %13, %14, %15, %16, %17, %18, %19}, {%20,%21,%22,%23}, db, p, 1, 1, 1;\n}\n"
    : "=f"(d[0]), "=f"(d[1]), "=f"(d[2]), "=f"(d[3]), "=f"(d[4]), "=f"(d[5]), "=f"(d[6]), "=f"(d[7]), "=f"(d[8]), "=f"(d[9]), "=f"(d[10]), "=f"(d[11]), "=f"(d[12]), "=f"(d[13]), "=f"(d[14]), "=f"(d[15]), "=f"(d[16]), "=f"(d[17]), "=f"(d[18]), "=f"(d[19])
    : "r"(a[0]), "r"(a[1]), "r"(a[2]), "r"(a[3]), "r"(blo), "n"(BO), "n"(BH));
}
template<uint32_t AO, uint32_t AH, uint32_t BO, uint32_t BH> __device__ __forceinline__ void mma40_tt(float (&d)[20], uint32_t alo, uint32_t blo) {
  asm volatile("{\n.reg .pred p;\n.reg .b32 ta, tb;\n.reg .b64 da, db;\nadd.u32 ta, %20, %21;\nmov.b64 da, {ta, %22};\nadd.u32 tb, %23, %24;\nmov.b64 db, {tb, %25};\nsetp.ne.b32 p, 1, 0;\n"
    "wgmma.mma_async.sync.aligned.m64n40k16.f32.bf16.bf16 {%0, %1, %2, %3, %4, %5, %6, %7, %8, %9, %10, %11, %12, %13, %14, %15, %16, %17, %18, %19}, da, db, p, 1, 1, 1, 1;\n}\n"
    : "+f"(d[0]), "+f"(d[1]), "+f"(d[2]), "+f"(d[3]), "+f"(d[4]), "+f"(d[5]), "+f"(d[6]), "+f"(d[7]), "+f"(d[8]), "+f"(d[9]), "+f"(d[10]), "+f"(d[11]), "+f"(d[12]), "+f"(d[13]), "+f"(d[14]), "+f"(d[15]), "+f"(d[16]), "+f"(d[17]), "+f"(d[18]), "+f"(d[19])
    : "r"(alo), "n"(AO), "n"(AH), "r"(blo), "n"(BO), "n"(BH));
}
template<uint32_t AO, uint32_t AH, uint32_t BO, uint32_t BH> __device__ __forceinline__ void mma40_tt0(float (&d)[20], uint32_t alo, uint32_t blo) {
  asm volatile("{\n.reg .pred p;\n.reg .b32 ta, tb;\n.reg .b64 da, db;\nadd.u32 ta, %20, %21;\nmov.b64 da, {ta, %22};\nadd.u32 tb, %23, %24;\nmov.b64 db, {tb, %25};\nsetp.ne.b32 p, 0, 0;\n"
    "wgmma.mma_async.sync.aligned.m64n40k16.f32.bf16.bf16 {%0, %1, %2, %3, %4, %5, %6, %7, %8, %9, %10, %11, %12, %13, %14, %15, %16, %17, %18, %19}, da, db, p, 1, 1, 1, 1;\n}\n"
    : "=f"(d[0]), "=f"(d[1]), "=f"(d[2]), "=f"(d[3]), "=f"(d[4]), "=f"(d[5]), "=f"(d[6]), "=f"(d[7]), "=f"(d[8]), "=f"(d[9]), "=f"(d[10]), "=f"(d[11]), "=f"(d[12]), "=f"(d[13]), "=f"(d[14]), "=f"(d[15]), "=f"(d[16]), "=f"(d[17]), "=f"(d[18]), "=f"(d[19])
    : "r"(alo), "n"(AO), "n"(AH), "r"(blo), "n"(BO), "n"(BH));
}
template<uint32_t AO, uint32_t AH, uint32_t BO, uint32_t BH> __device__ __forceinline__ void mma8_tn(float (&d)[4], uint32_t alo, uint32_t blo) {
  asm volatile("{\n.reg .pred p;\n.reg .b32 ta, tb;\n.reg .b64 da, db;\nadd.u32 ta, %4, %5;\nmov.b64 da, {ta, %6};\nadd.u32 tb, %7, %8;\nmov.b64 db, {tb, %9};\nsetp.ne.b32 p, 1, 0;\n"
    "wgmma.mma_async.sync.aligned.m64n8k16.f32.bf16.bf16 {%0, %1, %2, %3}, da, db, p, 1, 1, 1, 0;\n}\n"
    : "+f"(d[0]), "+f"(d[1]), "+f"(d[2]), "+f"(d[3])
    : "r"(alo), "n"(AO), "n"(AH), "r"(blo), "n"(BO), "n"(BH));
}
template<uint32_t AO, uint32_t AH, uint32_t BO, uint32_t BH> __device__ __forceinline__ void mma8_tn0(float (&d)[4], uint32_t alo, uint32_t blo) {
  asm volatile("{\n.reg .pred p;\n.reg .b32 ta, tb;\n.reg .b64 da, db;\nadd.u32 ta, %4, %5;\nmov.b64 da, {ta, %6};\nadd.u32 tb, %7, %8;\nmov.b64 db, {tb, %9};\nsetp.ne.b32 p, 0, 0;\n"
    "wgmma.mma_async.sync.aligned.m64n8k16.f32.bf16.bf16 {%0, %1, %2, %3}, da, db, p, 1, 1, 1, 0;\n}\n"
    : "=f"(d[0]), "=f"(d[1]), "=f"(d[2]), "=f"(d[3])
    : "r"(alo), "n"(AO), "n"(AH), "r"(blo), "n"(BO), "n"(BH));
}
template<uint32_t AO, uint32_t AH, uint32_t BO, uint32_t BH> __device__ __forceinline__ void mma128_ss(float (&d)[64], uint32_t alo, uint32_t blo) {
  asm volatile("{\n.reg .pred p;\n.reg .b32 ta, tb;\n.reg .b64 da, db;\nadd.u32 ta, %64, %65;\nmov.b64 da, {ta, %66};\nadd.u32 tb, %67, %68;\nmov.b64 db, {tb, %69};\nsetp.ne.b32 p, 1, 0;\n"
    "wgmma.mma_async.sync.aligned.m64n128k16.f32.bf16.bf16 {%0, %1, %2, %3, %4, %5, %6, %7, %8, %9, %10, %11, %12, %13, %14, %15, %16, %17, %18, %19, %20, %21, %22, %23, %24, %25, %26, %27, %28, %29, %30, %31, %32, %33, %34, %35, %36, %37, %38, %39, %40, %41, %42, %43, %44, %45, %46, %47, %48, %49, %50, %51, %52, %53, %54, %55, %56, %57, %58, %59, %60, %61, %62, %63}, da, db, p, 1, 1, 0, 1;\n}\n"
    : "+f"(d[0]), "+f"(d[1]), "+f"(d[2]), "+f"(d[3]), "+f"(d[4]), "+f"(d[5]), "+f"(d[6]), "+f"(d[7]), "+f"(d[8]), "+f"(d[9]), "+f"(d[10]), "+f"(d[11]), "+f"(d[12]), "+f"(d[13]), "+f"(d[14]), "+f"(d[15]), "+f"(d[16]), "+f"(d[17]), "+f"(d[18]), "+f"(d[19]), "+f"(d[20]), "+f"(d[21]), "+f"(d[22]), "+f"(d[23]), "+f"(d[24]), "+f"(d[25]), "+f"(d[26]), "+f"(d[27]), "+f"(d[28]), "+f"(d[29]), "+f"(d[30]), "+f"(d[31]), "+f"(d[32]), "+f"(d[33]), "+f"(d[34]), "+f"(d[35]), "+f"(d[36]), "+f"(d[37]), "+f"(d[38]), "+f"(d[39]), "+f"(d[40]), "+f"(d[41]), "+f"(d[42]), "+f"(d[43]), "+f"(d[44]), "+f"(d[45]), "+f"(d[46]), "+f"(d[47]), "+f"(d[48]), "+f"(d[49]), "+f"(d[50]), "+f"(d[51]), "+f"(d[52]), "+f"(d[53]), "+f"(d[54]), "+f"(d[55]), "+f"(d[56]), "+f"(d[57]), "+f"(d[58]), "+f"(d[59]), "+f"(d[60]), "+f"(d[61]), "+f"(d[62]), "+f"(d[63])
    : "r"(alo), "n"(AO), "n"(AH), "r"(blo), "n"(BO), "n"(BH));
}
template<uint32_t AO, uint32_t AH, uint32_t BO, uint32_t BH> __device__ __forceinline__ void mma128_ss0(float (&d)[64], uint32_t alo, uint32_t blo) {
  asm volatile("{\n.reg .pred p;\n.reg .b32 ta, tb;\n.reg .b64 da, db;\nadd.u32 ta, %64, %65;\nmov.b64 da, {ta, %66};\nadd.u32 tb, %67, %68;\nmov.b64 db, {tb, %69};\nsetp.ne.b32 p, 0, 0;\n"
    "wgmma.mma_async.sync.aligned.m64n128k16.f32.bf16.bf16 {%0, %1, %2, %3, %4, %5, %6, %7, %8, %9, %10, %11, %12, %13, %14, %15, %16, %17, %18, %19, %20, %21, %22, %23, %24, %25, %26, %27, %28, %29, %30, %31, %32, %33, %34, %35, %36, %37, %38, %39, %40, %41, %42, %43, %44, %45, %46, %47, %48, %49, %50, %51, %52, %53, %54, %55, %56, %57, %58, %59, %60, %61, %62, %63}, da, db, p, 1, 1, 0, 1;\n}\n"
    : "=f"(d[0]), "=f"(d[1]), "=f"(d[2]), "=f"(d[3]), "=f"(d[4]), "=f"(d[5]), "=f"(d[6]), "=f"(d[7]), "=f"(d[8]), "=f"(d[9]), "=f"(d[10]), "=f"(d[11]), "=f"(d[12]), "=f"(d[13]), "=f"(d[14]), "=f"(d[15]), "=f"(d[16]), "=f"(d[17]), "=f"(d[18]), "=f"(d[19]), "=f"(d[20]), "=f"(d[21]), "=f"(d[22]), "=f"(d[23]), "=f"(d[24]), "=f"(d[25]), "=f"(d[26]), "=f"(d[27]), "=f"(d[28]), "=f"(d[29]), "=f"(d[30]), "=f"(d[31]), "=f"(d[32]), "=f"(d[33]), "=f"(d[34]), "=f"(d[35]), "=f"(d[36]), "=f"(d[37]), "=f"(d[38]), "=f"(d[39]), "=f"(d[40]), "=f"(d[41]), "=f"(d[42]), "=f"(d[43]), "=f"(d[44]), "=f"(d[45]), "=f"(d[46]), "=f"(d[47]), "=f"(d[48]), "=f"(d[49]), "=f"(d[50]), "=f"(d[51]), "=f"(d[52]), "=f"(d[53]), "=f"(d[54]), "=f"(d[55]), "=f"(d[56]), "=f"(d[57]), "=f"(d[58]), "=f"(d[59]), "=f"(d[60]), "=f"(d[61]), "=f"(d[62]), "=f"(d[63])
    : "r"(alo), "n"(AO), "n"(AH), "r"(blo), "n"(BO), "n"(BH));
}
template<uint32_t AO, uint32_t AH, uint32_t BO, uint32_t BH> __device__ __forceinline__ void mma128_ssp(float (&d)[64], uint32_t alo, uint32_t blo, int sc) {
  asm volatile("{\n.reg .pred p;\n.reg .b32 ta, tb;\n.reg .b64 da, db;\nadd.u32 ta, %64, %65;\nmov.b64 da, {ta, %66};\nadd.u32 tb, %67, %68;\nmov.b64 db, {tb, %69};\nsetp.ne.b32 p, %70, 0;\n"
    "wgmma.mma_async.sync.aligned.m64n128k16.f32.bf16.bf16 {%0, %1, %2, %3, %4, %5, %6, %7, %8, %9, %10, %11, %12, %13, %14, %15, %16, %17, %18, %19, %20, %21, %22, %23, %24, %25, %26, %27, %28, %29, %30, %31, %32, %33, %34, %35, %36, %37, %38, %39, %40, %41, %42, %43, %44, %45, %46, %47, %48, %49, %50, %51, %52, %53, %54, %55, %56, %57, %58, %59, %60, %61, %62, %63}, da, db, p, 1, 1, 0, 1;\n}\n"
    : "+f"(d[0]), "+f"(d[1]), "+f"(d[2]), "+f"(d[3]), "+f"(d[4]), "+f"(d[5]), "+f"(d[6]), "+f"(d[7]), "+f"(d[8]), "+f"(d[9]), "+f"(d[10]), "+f"(d[11]), "+f"(d[12]), "+f"(d[13]), "+f"(d[14]), "+f"(d[15]), "+f"(d[16]), "+f"(d[17]), "+f"(d[18]), "+f"(d[19]), "+f"(d[20]), "+f"(d[21]), "+f"(d[22]), "+f"(d[23]), "+f"(d[24]), "+f"(d[25]), "+f"(d[26]), "+f"(d[27]), "+f"(d[28]), "+f"(d[29]), "+f"(d[30]), "+f"(d[31]), "+f"(d[32]), "+f"(d[33]), "+f"(d[34]), "+f"(d[35]), "+f"(d[36]), "+f"(d[37]), "+f"(d[38]), "+f"(d[39]), "+f"(d[40]), "+f"(d[41]), "+f"(d[42]), "+f"(d[43]), "+f"(d[44]), "+f"(d[45]), "+f"(d[46]), "+f"(d[47]), "+f"(d[48]), "+f"(d[49]), "+f"(d[50]), "+f"(d[51]), "+f"(d[52]), "+f"(d[53]), "+f"(d[54]), "+f"(d[55]), "+f"(d[56]), "+f"(d[57]), "+f"(d[58]), "+f"(d[59]), "+f"(d[60]), "+f"(d[61]), "+f"(d[62]), "+f"(d[63])
    : "r"(alo), "n"(AO), "n"(AH), "r"(blo), "n"(BO), "n"(BH), "r"(sc));
}

#define XD 600
#define XSTEP 300
#define XPD 550
#define XPB 8192
#define SPG 5600
#define WL0 1800
#define WLS 350
#define NB0 2
#define WP1 2000
#define PF_START 5600
#define PFP 126
#define GPERM 0x76543210u
#define FMODE 2
#define NM0 3
#define PWAIT 600
#define AWAKE 1
#define WDW 3
#define WDGAP 300
#define YWAIT 500
#define CWAIT 500
#define NDF 8
#define RDV 1
#define MSTEP 1200
#define MSLP 1000
#define MPOLL 3200
#define LMP 8
#define FLO(q, cta) (p.s->flo + (q) * 256 + (cta) * 2)
#define HALFRED 0
#define WD0 10
#define CLR0 22000
#define UPGAP 250
#define OUTGAP 150
#define MPROMO P128
#define MLOAD tma_load_ef
struct Ptrs { const bf16 *x, *wmod, *c, *wr, *wqkv; int by_sm; Scratch* s; const bf16 *wg, *wu, *wd, *wo; bf16* out; uint16_t role[132]; };

#define BAR(i) (sb + OFF_BAR + 8u * (i))

__device__ __forceinline__ uint32_t get_tag(uint32_t sb) { mbar_wait(BAR(B_TAG), 0); const uint32_t d = __shfl_sync(0xffffffffu, lds32(sb + OFF_CST + 32), 0); return d + 1 + (d & 2); }
__device__ __forceinline__ int d_kb(int n, int hg) {
    if (n < 2) return 2 * hg + n;
    const int h = n >= 9, q = n - 2 - 7 * h;
    return 2 * (q + (q >= hg)) + h;
}

__global__ void __launch_bounds__(NTHREADS, 1)
fused_kernel(const Ptrs p, const __grid_constant__ CUtensorMap tmM, const __grid_constant__ CUtensorMap tmX, const __grid_constant__ CUtensorMap tmW,
             const __grid_constant__ CUtensorMap tmWo, const __grid_constant__ CUtensorMap tmPhi, const __grid_constant__ CUtensorMap tmG,
             const __grid_constant__ CUtensorMap tmU, const __grid_constant__ CUtensorMap tmD, const __grid_constant__ CUtensorMap tmO)
{
    extern __shared__ __align__(1024) uint8_t smem_raw[];
    const uint32_t sb = smem_u32(smem_raw);
    const uint32_t cstart = __shfl_sync(0xffffffffu, clk32(), 0);
    const int tid = threadIdx.x, lane = tid & 31, warp = __shfl_sync(0xffffffffu, tid >> 5, 0);
    if (blockIdx.x < 128) {
        if (warp == 8) asm volatile("prefetch.global.L2 [%0];" :: "l"(p.wmod + (size_t)(blockIdx.x * 8 + (lane >> 2)) * 6144 + (lane & 1) * 64 + (lane & 2) * 512));
        if (warp == 13 && (lane & 1) < NM0 - 2) asm volatile("prefetch.global.L2 [%0];" :: "l"(p.wmod + (size_t)(blockIdx.x * 8 + (lane >> 2)) * 6144 + 128 + (lane & 1) * 64 + (lane & 2) * 512));
        if (warp == 11) asm volatile("prefetch.global.L2 [%0];" :: "l"((lane < 16 ? p.c : p.wr) + (lane & 15) * 64));
        if (warp == 12) l2_prefetch(p.wqkv + (size_t)blockIdx.x * 1536, 3072);
        if (warp == 9) { spin_until(cstart + XPD); l2_prefetch(p.x + (size_t)blockIdx.x * 16384, XPB); }
    }
    if (warp == 10) { tmap_prefetch(&tmM); tmap_prefetch(&tmX); tmap_prefetch(&tmW); }
    #pragma unroll
    for (int i = 0; i < 5; i++) e_init(BAR(5 * warp + i), warp < 5 ? 1 : warp < 7 ? 2 : warp < 9 ? 4 : warp < 14 ? 8 : warp < 15 ? 12 : 1);
    mbar_init_fence();
    if (warp == B_TAG / 5) { e_arrive_tx(BAR(B_TAG), 16); bulk_load(sb + OFF_CST + 32, p.s->done, 16, BAR(B_TAG)); }
    uint32_t role;
    asm("mov.u32 %0, %%smid;" : "=r"(role));
    role = p.role[p.by_sm ? role : blockIdx.x];
    const int b = role & 255;
    if (b >= 128 && warp == 0) {
        #pragma unroll
        for (int i = 0; i < 2; i++) { e_arrive_tx(BAR(i), 32768); MLOAD(sb + i * 32768u, &tmM, (b & 1) * 1024, (b & 2) * 256 + i * 256, BAR(i)); }
    }
    __syncthreads();

    if (b >= 128) {
        const int sp = b & 3;
        if (warp == 8) {
            #pragma unroll 1
            for (int j = 2, st = 2, ph = 1; j < 64; j++) {
                if (j == 2 * NM0) spin_until(cstart + SPG);
                mbar_wait(BAR(B_EA + st), ph);
                e_arrive_tx(BAR(st), 32768);
                MLOAD(sb + st * 32768u, &tmM, j < 32 ? (sp & 1) * 1024 + (j >> 1) * 64 : 2560 + sp * 512 + (j >> 2) * 64, (j < 32 ? (sp & 2) + (j & 1) : j & 3) * 256, BAR(st));
                if (++st == 6) { st = 0; ph ^= 1; }
            }
        } else if (warp < 8) {
            const int g = lane >> 2, c = lane & 3;
            {
                const bf16* cp = p.c + (tid >> 3) * 32 + (tid & 1) * 16 + (tid & 6);
                const uint32_t c0 = ldg32(cp), c1 = ldg32(cp + 8);
                stg_zero(p.s->llm1 + (tid >> 4) * 64 + sp * 16 + (tid & 15));
                if (tid < 128) stg_zero(p.s->llmod2 + sp * 128 + tid);
                sts64(sb + 200704u + tid * 8, silu2(c0), silu2(c1));
                bar_sync(1, 256);
                TR(57);
            }
            const uint32_t wa = sb + (warp * 32 + (lane & 7) + (lane >> 4) * 8) * 128u + ((((lane >> 3) & 1) ^ (lane & 7)) << 4);
            float m[4][4];
            #pragma unroll
            for (int i = 0; i < 4; i++) m[i][0] = m[i][1] = m[i][2] = m[i][3] = 0.f;
            #pragma unroll 1
            for (int r = 0, st = 0, ph = 0; r < 32; r++) {
                const uint32_t sa = sb + 200704u + ((r < 16 ? sp >> 1 : r & 1) * 16 + warp) * 64 + c * 16;
                #pragma unroll
                for (int q = 0; q < 2; q++) {
                    const uint4 sv = lds128(sa + q * 512);
                    uint32_t f[8][4];
                    mbar_wait(BAR(st + q), ph);
                    if (r == 0 && warp == 0) TR(60 + q);
                    #pragma unroll
                    for (int i = 0; i < 8; i++) ldsm4t(f[i], (wa + (st + q) * 32768u + (i >> 2) * 2048u) ^ ((i & 3) << 5));
                    e_arrive_after(BAR(B_EA + st + q), (f[0][0] ^ f[1][0] ^ f[2][0]) ^ (f[3][0] ^ f[4][0] ^ f[5][0]) ^ (f[6][0] ^ f[7][0]));
                    #pragma unroll
                    for (int i = 0; i < 8; i++) mma16816(m[i & 3], f[i][0], f[i][1], f[i][2], f[i][3], (i & 4) ? sv.z : sv.x, (i & 4) ? sv.w : sv.y);
                }
                st += 2; if (st == 6) { st = 0; ph ^= 1; }
                if (r >= 16 && !(r & 1)) continue;
                const int n = r < 16 ? r : (r >> 1) + 8;
                const uint32_t a = sb + 196608u + (n & 1) * 2048u + warp * 256u + (c * 16 + (g >> 1) * 4 + (g & 1)) * 4u;
                mbar_wait(BAR(B_XP + (n & 1)), ~(n >> 1) & 1);
                stsf(a, sel4(c, m[0][0], m[1][0], m[2][0], m[3][0])); stsf(a + 8, sel4(c, m[0][2], m[1][2], m[2][2], m[3][2]));
                #pragma unroll
                for (int i = 0; i < 4; i++) m[i][0] = m[i][1] = m[i][2] = m[i][3] = 0.f;
                __syncwarp();
                e_arrive(BAR(B_PF + (n & 1)));
            }
        } else if (warp == 9) {
            const int c = lane & 3;
            const uint32_t tag = get_tag(sb);
            #pragma unroll 1
            for (int n = 0; n < 24; n++) {
                const bf16* wr = p.wr + (sp & 1) * 512 + (n & 7) * 64 + ((lane >> 2) & 3) * 16 + 2 * c;
                const uint32_t wr0 = ldg32(wr), wr1 = ldg32(wr + 8);
                const uint32_t ra = sb + 196608u + (n & 1) * 2048u + (lane >> 4) * 1024u + (lane & 15) * 16u;
                uint4* d = n < 16 ? p.s->llm1 + n * 64 + sp * 16 + lane : p.s->llmod2 + sp * 128 + (n & 7) * 16 + lane;
                mbar_wait(BAR(B_PF + (n & 1)), (n >> 1) & 1);
                const uint4 r0 = lds128(ra), r1 = lds128(ra + 256), r2 = lds128(ra + 512), r3 = lds128(ra + 768);
                e_arrive(BAR(B_XP + (n & 1)));
                #define F4(f) ((u2f(r0.f) + u2f(r1.f)) + (u2f(r2.f) + u2f(r3.f)))
                float x = F4(x), y = F4(y), z = F4(z), w = F4(w);
                #undef F4
                x += shfl_x(x, 16); y += shfl_x(y, 16); z += shfl_x(z, 16); w += shfl_x(w, 16);
                if (n < 16) {
                    if (lane < 16) st_ll4(d, x, y, z, w, tag);
                } else {
                    uint32_t lo = pack2(x, y), hi2 = pack2(z, w);
                    float e = fmaf(bf_lo(lo), bf_lo(wr0), bf_hi(lo) * bf_hi(wr0)) + fmaf(bf_lo(hi2), bf_lo(wr1), bf_hi(hi2) * bf_hi(wr1));
                    if (sp >= 2) {
                        lo = hadd2(lo, ONE2); hi2 = hadd2(hi2, ONE2);
                        const uint32_t q0 = hmul2(lo, wr0), q1 = hmul2(hi2, wr1);
                        e = (bf_lo(q0) + bf_hi(q0)) + (bf_lo(q1) + bf_hi(q1));
                    }
                    #pragma unroll 1
                    for (int k = 1; k < 16; k <<= 1) e += shfl_x(e, k);
                    if (lane < 16) st_ll(d, lo, hi2, f2u(e), tag);
                }
                TR(n);
            }
        }
    } else if (warp >= 12) {
        reg_dec<24>();
        const int rb = b >> 3, hg = b & 7, fs = role >> 8;
        const bool ffn = fs < 112;
        if (warp == 12) {
            #pragma unroll 1
            for (int j = 0, s = 0, ph = 1; j < 16; j++) {
                if (j < 2) mbar_wait(j ? BAR(B_STS) : BAR(B_STP), 0);
                mbar_wait(BAR(B_EA + s), ph);
                e_arrive_tx(BAR(B_FA + s), 16384); tma_load(sb + OFF_A + s * 16384u, &tmX, j * 64, rb * 128, BAR(B_FA + s));
                if (j == 0) TS(2);
                if (j == 1) GT(0);
                if (j == 6) GT(1);
                if (j == 11) GT(2);
                if (++s == 3) { s = 0; ph ^= 1; }
            }
            tmap_prefetch(&tmO);
            const uint32_t tag = get_tag(sb);
            e_arrive(BAR(B_FD)); e_arrive(BAR(B_FD + 1));
            const uint4* osrc = pin_ptr(p.s->os + (size_t)rb * 16 * 1024);
            #pragma unroll 1
            for (int q = 0; q < 3; q++) {
                mbar_wait(q < 2 ? BAR(B_KST + 1 + 2 * q) : BAR(B_OWN), 0);
                const uint32_t chk = poll_flags(q < 2 ? p.s->flk + (q + 1) * 256 + (hg * 16 + (lane & 15)) * 2 : FLO(0, rb * 8 + (lane & 7)), tag);
                if (q == 2) { sts32(sb + OFF_CHK + 64 + (lane & 7) * 8, chk); __syncwarp(); break; }
                e_arrive_tx(BAR(B_KVL + q), 16896); bulk_load(sb + (q ? OFF_PHI : OFF_KL), p.s->kvacc + hg * 2112 + q * 1056, 16896, BAR(B_KVL + q));
                TS(12 + q);
                if (!q) GT(4);
            }
            TS(3); GT(5);
            #pragma unroll
            for (int n = 2; n < 6; n++) {
                if (n >= 4) mbar_wait(BAR(B_ED + (n & 3)), 0); else if (n == 3) mbar_wait(BAR(B_OWN + 1), 0);
                e_arrive_tx(BAR(B_FD + (n & 3)), 16384);
                bulk_load(sb + (n == 5 ? OFF_X1 : OFF_R0 + (n & 3) * 16384u), osrc + (n - 2 >= hg ? n - 1 : n - 2) * 2048, 16384, BAR(B_FD + (n & 3)));
                TR(32 + n);
            }
            #pragma unroll 1
            for (int n = 6; n < 16; n++) {
                const uint32_t s = n & 3, fb = BAR(B_FD + s);
                const uint4* src = osrc + d_kb(n, hg) * 1024;
                if (n == 9) mbar_wait(BAR(B_O1), 0);
                mbar_wait(BAR(B_ED + s), ((n >> 2) - 1) & 1);
                e_arrive_tx(fb, 16384);
                bulk_load(sb + OFF_R0 + s * 16384u, src, 16384, fb);
                TR(32 + n);
            }
            e_arrive_tx(BAR(B_WPHI), 32768);
            mbar_wait(BAR(B_ED), 1);
            tma_load(sb + OFF_R0, &tmX, hg * 128, rb * 128, BAR(B_WPHI));
            tma_load(sb + OFF_X1, &tmX, hg * 128 + 64, rb * 128, BAR(B_WPHI));
            GT(6);
            mbar_wait(BAR(B_CAND), 0);
            GT(7);
            const uint2 lc = lds64(sb + OFF_CST + 16);
            const uint32_t w0 = __shfl_sync(0xffffffffu, lc.x >> 4, 0), w1 = __shfl_sync(0xffffffffu, lc.y >> 4, 0);
            mbar_wait(BAR(B_SWP), 0);
            fence_async_smem();
            #pragma unroll 1
            for (uint32_t w = 0; w < 8; w++)
                if (w != w0 && w != w1) { tma_store4(&tmO, rb * 128 + w * 16, hg * 2, sb + OFF_OUT + w * 4096u); spin_until(clk32() + OUTGAP); }
            mbar_wait(BAR(B_SEL), 0);
            const uint2 sel = lds64(sb + OFF_CST + 24);
            #pragma unroll 1
            for (uint32_t i = 0; i < (w0 == w1 ? 8u : 16u); i++) {
                const uint32_t w = i < 8 ? w0 : w1, r = (i & 7) * 2 + (lane >> 4), row = rb * 128 + w * 16 + r;
                const uint4 o = lds128(sb + OFF_OUT + w * 4096u + ((lane >> 3) & 1) * 2048u + r * 128u + (((lane ^ r) & 7) << 4));
                if (row != (~sel.x & 2047u) && row != (~sel.y & 2047u)) stg128(p.out + (size_t)row * 1024 + hg * 128 + (lane & 15) * 8, o);
            }
            bulk_wait_read();
        } else if (warp == 14) {
            const uint32_t fb = ffn ? 65536 : 0;
            e_arrive_tx(BAR(B_GF), fb); e_arrive_tx(BAR(B_UD), fb); e_arrive_tx(BAR(B_UF), fb); e_arrive_tx(BAR(B_WD), fb);
            uint32_t due = cstart + WP1;
            #pragma unroll 1
            for (int i = -2; i < 26; i++) {
                if (i >= 0) {
                    const bf16* a = i < 8 ? p.wg + (size_t)(i * 128 + b) * 3584 : i < 16 ? p.wu + (size_t)((i - 8) * 128 + b) * 3584
                                  : i < 18 ? p.wo + (size_t)(b * 2 + i - 16) * 4096 : p.wd + (size_t)(b * 8 + i - 18) * 3584;
                    sleep_until(due);
                    l2_prefetch(a, (i >> 1) == 8 ? 8192 : 7168);
                    due += 7 * PFP;
                }
                if (i == 1) { tmap_prefetch(&tmPhi); tmap_prefetch(&tmG); tmap_prefetch(&tmWo); tmap_prefetch(&tmU); tmap_prefetch(&tmD); mbar_wait(BAR(B_STS), 0); }
                if (ffn && (uint32_t)(i - 3) < 8u) tma_load_ef(sb + OFF_R0 + (i - 3) * 8192u, &tmG, fs * 32, (i - 3) * 128, BAR(B_GF));
                if (ffn && (uint32_t)(i - 11) < 8u) tma_load(sb + OFF_WPHI, &tmU, fs * 32, (i - 11) * 128, BAR(B_UD));
                if (i == 19) { mbar_wait(BAR(B_UD), 0); e_arrive_tx(BAR(B_WPHI), 8192); tma_load(sb + OFF_WPHI, &tmPhi, 0, hg * 128, BAR(B_WPHI)); }
                if (i == LMP + 2 * (b & 3) + (b >> 6)) tma_prefetch(&tmM, 2048 + (b >> 6) * 2048 + (b >> 2) * 64, (b & 3) * 256);
                if (i < 13) {
                    sleep_until(due);
                    l2_prefetch(p.wqkv + (size_t)((i + 3) * 128 + b) * 1536, 3072);
                    due += i == -2 ? PF_START - WP1 : 3 * PFP;
                }
            }
            if (lane < 4) stg_zero(FLO(lane >> 1, b) + (lane & 1));
            const uint32_t tag = get_tag(sb);
            #pragma unroll 1
            for (int q = 0; q < 2; q++) {
                mbar_wait(BAR(B_OWN + q), 0);
                if (q) mbar_wait(BAR(B_FD + 2), 0);
                bulk_store(p.s->os + ((size_t)b * 2 + q) * 1024, sb + OFF_R0 + q * 16384u, 16384);
                mbar_wait(BAR(B_CS + q), 0);
                uint32_t chk = __reduce_xor_sync(0xffffffffu, lane < 8 ? lds32(sb + OFF_CHK + q * 32 + lane * 4) : 0u);
                bulk_wait();
                __syncwarp();
                st_flag(FLO(q, b), tag, chk, lane);
                TS(7 + q);
            }
            e_arrive(BAR(B_OST));
            fence_gpu();
            __syncwarp();
            st_flag(FLO(2, b), tag, 0, lane);
        } else {
            uint4* fk = p.s->flk + (hg * 16 + rb) * 2;
            if (warp == 13) {
                #pragma unroll 1
                for (int i = 0; i < 32; i++) {
                    const uint32_t s = i & 3;
                    if (i < NB0) spin_until(cstart + WL0 + WLS * i); else if (i == NB0) mbar_wait(BAR(B_STS), 0);
                    mbar_wait(BAR(B_EB + s), ((i >> 2) - 1) & 1);
                    e_arrive_tx(BAR(B_FB + s), 24576); tma_load4(sb + OFF_B + s * 24576u, &tmW, i * 32, hg * 2, BAR(B_FB + s));
                    TR(64 + i);
                }
                mbar_wait(BAR(B_EB), 1); mbar_wait(BAR(B_EB + 1), 1);
                e_arrive_tx(BAR(B_LMF), 32768); tma_load_ef(sb + OFF_B, &tmM, 2048 + (b >> 6) * 2048 + (b >> 2) * 64, (b & 3) * 256, BAR(B_LMF));
                mbar_wait(BAR(B_LMD), 0);
                #pragma unroll 1
                for (int n = 0; n < 4; n++) {
                    e_arrive_tx(BAR(B_FD + n), 16384); tma_load4(sb + OFF_DB + n * 16384u, &tmWo, d_kb(n, hg) * 64, hg * 2, BAR(B_FD + n));
                }
            } else {
                sleep_until(cstart + CLR0);
                const uint32_t tag = get_tag(sb);
                #pragma unroll 1
                for (int i = lane; i < 132; i += 32) stg_zero(p.s->kvacc + hg * 2112 + rb * 132 + i);
                if (lane < 4) stg_zero(fk + 256 + (lane >> 1) * 256 + (lane & 1));
                fence_gpu();
                __syncwarp();
                st_flag(fk, tag, 0, lane);
                sleep_until(clk32() + 2000);
                poll_flags(p.s->flk + (hg * 16 + (lane & 15)) * 2, tag);
                mbar_wait(BAR(B_QE), 0);
                #pragma unroll 1
                for (int i = 0; i < 4; i++) {
                    stg_zero(p.s->llln2 + b * 128 + i * 32 + lane);
                    stg_zero(p.s->llrowh + (i >> 1) * 8192 + (rb * 2 + (i & 1)) * 256 + hg * 32 + lane);
                    #pragma unroll
                    for (int k = 0; k < 4; k++) stg_zero(p.s->lly + (fs & 127) * 512 + i * 128 + k * 32 + lane);
                }
                if (lane < 2 && hg == (rb & 7)) stg_zero(p.s->llcand + rb * 2 + lane);
                __syncwarp();
                e_arrive(BAR(B_KZ));
            }
            const int q = warp == 13;
            const uint32_t tag = get_tag(sb);
            mbar_wait(BAR(B_KZ), 0);
            #pragma unroll 1
            for (int h = 2 * q; h < 2 * q + 2; h++) {
                mbar_wait(BAR(B_KST + h), 0);
                if (HALFRED) spin_until(clk32() + HALFRED);
                uint4* acc = p.s->kvacc + (hg * 4 + h) * 528;
                bulk_reduce(acc + (HALFRED ? (rb & 1) * 256 : 0), sb + OFF_V + h * 8192u, HALFRED ? 4096 : 8192); bulk_reduce(acc + 512, sb + OFF_ZS + h * 256u, 256);
            }
            bulk_wait();
            if (q) e_arrive(BAR(B_KZ));
            TR(158 + q);
            fence_gpu();
            __syncwarp();
            st_flag(fk + 256 + q * 256, tag, 0, lane);
            TS(10 + q);
            if (q) {
                #pragma unroll 1
                for (int n = 4; n < 16; n++) {
                    const uint32_t s = n & 3;
                    mbar_wait(BAR(B_ED + s), ((n >> 2) - 1) & 1);
                    e_arrive_tx(BAR(B_FD + s), 16384);
                    tma_load4(sb + OFF_DB + s * 16384u, &tmWo, d_kb(n, hg) * 64, hg * 2, BAR(B_FD + s));
                    TR(96 + n);
                    if (ffn && (uint32_t)(n - WD0) < 4u) {
                        #pragma unroll
                        for (int k = 0; k < 2; k++) tma_load_ef(sb + OFF_F2 + (n - WD0) * 8192u + k * 4096u, &tmD, (n - WD0) * 256 + k * 128, fs * 32, BAR(B_WD));
                    }
                }
                if (ffn) {
                    mbar_wait(BAR(B_ED + WDW), 1);
                    #pragma unroll 1
                    for (int z = 0; z < 8; z++) { tma_load_ef(sb + OFF_DB + z * 4096u, &tmD, z * 128 + 64, fs * 32, BAR(B_WD)); sleep_until(clk32() + WDGAP); }
                }
            } else {
                if (ffn) {
                    mbar_wait(BAR(B_KZ), 1);
                    #pragma unroll 1
                    for (int i = 7; i < 15; i++) {
                        if (i == 12) mbar_wait(BAR(B_KVT + 1), 0);
                        tma_load_ef(sb + OFF_F2 + (i & 7) * 8192u, &tmU, fs * 32, (i & 7) * 128, BAR(B_UF));
                        sleep_until(clk32() + UPGAP);
                    }
                }
                mbar_wait(BAR(B_OST), 0);
                sts32(sb + OFF_CHK + 68 + (lane & 7) * 8, poll_flags(FLO(1, rb * 8 + (lane & 7)), tag));
                __syncwarp();
                e_arrive(BAR(B_O1));
                TS(4);
            }
        }
    } else if (warp >= 8) {
        reg_dec<24>();
        const int rb = b >> 3, hg = b & 7, w4 = warp & 3, g = lane >> 2, c = lane & 3, t = tid & 127;
        const uint32_t sv = silu2(ldg32(p.c + (b & 3) * 256 + 2 * t)), tag = get_tag(sb);
        if (w4 < 3) {
            spin_until(cstart + MPOLL + MSTEP * w4);
            #pragma unroll 1
            for (int j = w4, ph = 1; j < 16; j += 3, ph ^= 1) {
                uint4 w[2];
                poll_words<2, 0, 3>(w, p.s->llm1 + j * 64 + lane, 32, tag);
                uint32_t lo = pack2(u2f(w[0].x) + u2f(w[1].x), u2f(w[0].y) + u2f(w[1].y)), hi = pack2(u2f(w[0].z) + u2f(w[1].z), u2f(w[0].w) + u2f(w[1].w));
                if (lane >= 16) { lo = hadd2(lo, ONE2); hi = hadd2(hi, ONE2); }
                sts64(sb + OFF_TAB + j * 256 + (lane & 15) * 16 + (lane < 16 ? 8 : 0), lo, hi);
                __syncwarp();
                if (j == 0) TS(5);
                TR(16 + j);
                mbar_wait(BAR(B_EA + w4), ph);
                e_arrive(BAR(B_FA + w4));
                __nanosleep(MSLP);
            }
        }
        mbar_wait(BAR(B_QE), 0);
        if (warp == 8) GT(3);
        sts32(sb + OFF_KL + w4 * 1024u + lane * 4, sv);
        fence_async_smem();
        bar_sync(2, 128);
        reg_inc<56>();
        {
            float m0[4], m1[4];
            const uint32_t da = desc_lo(sb + OFF_B, 16), db = desc_lo(sb + OFF_KL, 16);
            mbar_wait(BAR(B_LMF), 0);
            wg_fence();
            #define LMS(f, i) f<(i) * 256, H128, ((i) >> 1) * 64 + ((i) & 1) * 4, H128>(m0, da, db); f<(i) * 256 + 128, H128, ((i) >> 1) * 64 + ((i) & 1) * 4 + 2, H128>(m1, da, db)
            LMS(mma8_tn0, 0); LMS(mma8_tn, 1); LMS(mma8_tn, 2); LMS(mma8_tn, 3); LMS(mma8_tn, 4); LMS(mma8_tn, 5); LMS(mma8_tn, 6); LMS(mma8_tn, 7);
            #undef LMS
            wg_commit();
            wg_wait<0>();
            acc_fence(m0); acc_fence(m1);
            e_arrive(BAR(B_LMD));
            const float v0 = m0[0] + m1[0], v1 = m0[2] + m1[2], u0 = shfl_x(v0, 4), u1 = shfl_x(v1, 4);
            if (!(lane & 7)) st_ll4(p.s->llg + (b >> 6) * 1024 + (b & 3) * 256 + ((b >> 2) & 15) * 16 + w4 * 4 + (lane >> 3), v0, u0, v1, u1, tag);
            if (warp == 8) TR(150);
        }
        #pragma unroll 1
        for (int h = 0; h < 4; h++) {
            float okv[20];
            const uint32_t vb = OFF_V + h * 8192u, dp = desc_lo(sb + OFF_PHI + (h & 1) * 16384u, 16), dv = desc_lo(sb + vb, OFF_ONES - vb);
            mbar_wait(BAR(B_PF + h), 0);
            fence_async_smem();
            wg_fence();
            #define KVS(i) mma40_tt<(i) * 128, H128, (i) * (64u - (64u << 16)), H64>(okv, dp, dv)
            mma40_tt0<0, H128, 0, H64>(okv, dp, dv); KVS(1); KVS(2); KVS(3); KVS(4); KVS(5); KVS(6); KVS(7);
            #undef KVS
            wg_commit();
            wg_wait<0>();
            acc_fence(okv);
            if (h < 2) e_arrive(BAR(B_PE + h));
            bar_sync(2, 128);
            #pragma unroll
            for (int k = 0; k < 4; k++) sts128(sb + vb + (k * 128 + t) * 16u, make_uint4(f2u(okv[4 * k]), f2u(okv[4 * k + 1]), f2u(okv[4 * k + 2]), f2u(okv[4 * k + 3])));
            if (c == 0) sts64(sb + OFF_ZS + h * 256u + (w4 * 8 + g) * 8u, f2u(okv[16]), f2u(okv[18]));
            fence_async_smem();
            __syncwarp();
            e_arrive(BAR(B_KST + h));
            if (warp == 8) TR(151 + h);
        }
        e_arrive(BAR(B_ED)); e_arrive(BAR(B_ED + 1));
        if (w4 == 0 || w4 == 3) {
            uint4 w[4];
            poll_words<4, 0, 3>(w, p.s->llg + (w4 & 1) * 1024 + hg * 32 + lane, 256, tag);
            #define F4(f) ((u2f(w[0].f) + u2f(w[1].f)) + (u2f(w[2].f) + u2f(w[3].f)))
            const uint32_t lo = pack2(F4(x), F4(y)), hi = pack2(F4(z), F4(w));
            #undef F4
            sts64(w4 ? sb + OFF_T3 + lane * 8 : sb + OFF_T1 + lane * 16, lo, hi);
            if (!w4) sts64(sb + OFF_T1 + 512 + lane * 16, lo, hi);
        }
        #pragma unroll 1
        for (int q = 0; q < 2; q++) {
            const uint32_t f = w4 * 16 + g, kl = sb + (q ? OFF_PHI : OFF_KL), ta = sb + (q ? OFF_KL : OFF_KVT) + f * 64u + ((g >> 1) << 4) + 4 * c;
            const uint32_t za = sb + OFF_Z + (f + 8 * (c & 1)) * 64u + (((2 * q) ^ (g >> 1)) << 4) + (c >> 1) * 8;
            mbar_wait(q ? BAR(B_KVT) : BAR(B_STP), q ^ 1);
            mbar_wait(BAR(B_KVL + q), 0);
            uint4 v[8]; float z[2];
            #pragma unroll
            for (int k = 0; k < 8; k++) v[k] = lds128(kl + (k >> 2) * 8448u + (k & 3) * 2048u + t * 16u);
            #pragma unroll
            for (int hh = 0; hh < 2; hh++) z[hh] = ldsf(kl + hh * 8448u + 8192u + (w4 * 8 + g) * 8u + (c & 1) * 4);
            #pragma unroll
            for (int k = 0; k < 8; k++) {
                sts32((ta ^ ((k & 3) << 4)) + (k >> 2) * 4096u, pack2(u2f(v[k].x), u2f(v[k].y))); sts32((ta ^ ((k & 3) << 4)) + (k >> 2) * 4096u + 512, pack2(u2f(v[k].z), u2f(v[k].w)));
            }
            #pragma unroll
            for (int hh = 0; hh < 2; hh++) { const uint32_t zz = pack2(z[hh], z[hh]); sts64(za ^ (hh << 4), zz, zz); }
            fence_async_smem();
            __syncwarp();
            e_arrive(BAR(B_KVT + q));
            if (warp == 8) TR(155 + q);
        }
        reg_dec<24>();
        if (w4 == 1 || w4 == 2) {
            const bf16* wr = p.wr + hg * 128 + g * 16 + 2 * c;
            const uint32_t wr0 = ldg32(wr), wr1 = ldg32(wr + 8);
            uint4 w[2];
            poll_words<2, 1>(w, p.s->llmod2 + (w4 - 1) * 256 + hg * 32 + lane, (lane & 15) * 16 - hg * 32 - lane, tag);
            sts64(sb + OFF_T2 + lane * 16 + (w4 & 1) * 8, w[0].x, w[0].y);
            if (w4 == 2) sts64(sb + OFF_T1 + 512 + lane * 16 + 8, hmul2(w[0].x, wr0), hmul2(w[0].y, wr1));
            float d = u2f(w[1].z);
            #pragma unroll 1
            for (int k = 1; k < 16; k <<= 1) d += shfl_x(d, k);
            stsf(sb + OFF_CST + 8 + (w4 & 1) * 4, d);
        }
        if (warp == 10) TS(6);
        {
            const uint32_t a = sb + w4 * 4096u + g * 128u + (((2 * c) ^ g) << 4) + (g >> 1) * 4;
            uint32_t x = 0;
            #pragma unroll 1
            for (int n = 2; n < 16; n++) {
                const uint32_t ta = a + (n == 5 ? OFF_X1 : OFF_R0 + (n & 3) * 16384u), ca = sb + OFF_CHK + 64 + d_kb(n, hg) * 4;
                mbar_wait(BAR(B_FD + (n & 3)), (n >> 2) & 1);
                const uint32_t v0 = lds32(ta), v1 = lds32(ta + 1024), v2 = lds32(ta + 2048), v3 = lds32(ta + 3072);
                x = __funnelshift_l(x, x, 1) ^ v0 ^ v1 ^ v2 ^ v3;
                e_arrive_after(BAR(B_ED + (n & 3)), x);
                if (t == 0) x ^= lds32(ca);
            }
            sts32(sb + OFF_CHK + 128 + w4 * 4, __reduce_xor_sync(0xffffffffu, x));
        }
        __syncwarp();
        e_arrive(BAR(B_PAR));
        if (w4 < 2) {
            mbar_wait(BAR(B_PAR), 0);
            const uint4 ta = lds128(sb + OFF_T2 + lane * 16);
            const uint2 gb = lds64(sb + OFF_T3 + lane * 8);
            uint4* d = pin_ptr(p.s->llrowh + (rb * 2 + w4) * 256 + hg * 32 + lane);
            mbar_wait(BAR(B_KEYS), 0);
            const uint4 kk = lds128(sb + OFF_KEY + lane * 16);
            uint32_t k[4] = {kk.x, kk.y, kk.z, kk.w}, b0, b1;
            top2<4>(k, b0, b1);
            const uint32_t cd = ~(w4 ? b1 : b0) & 127u;
            const uint32_t xa = sb + OFF_R0 + (g >> 2) * (OFF_X1 - OFF_R0) + cd * 128u + ((((g & 3) * 2) ^ (cd & 7)) << 4) + c * 4;
            const uint32_t x0 = lds32(xa), x1 = lds32(xa ^ 16);
            const uint4 st = lds128(sb + OFF_ST2 + cd * 16);
            st_ll(d, lnmod(x0, st.x, st.y, st.z, ta.x, ta.z), lnmod(x1, st.x, st.y, st.z, ta.y, ta.w), gb.x, tag);
            st_ll(d + 8192, x0, x1, gb.y, tag);
            sts32(sb + OFF_CST + 16 + w4 * 4, cd);
            __syncwarp();
            e_arrive(BAR(B_CAND));
            if (warp == 8) TS(9);
        } else if (w4 == 2) {
            uint4* cp = pin_ptr(p.s->llcand + lane);
            mbar_wait(BAR(B_KEYS), 0);
            if (hg == (rb & 7)) {
                const uint4 kk = lds128(sb + OFF_KEY + lane * 16);
                uint32_t k[4] = {kk.x, kk.y, kk.z, kk.w}, b0, b1;
                top2<4>(k, b0, b1);
                if ((lane >> 1) == rb) st_ll(cp, tag, (lane & 1) ? b1 : b0, tag, tag);
            } else spin_until(clk32() + CWAIT);
            uint32_t k[1] = {poll_flags(cp, tag)}, b0, b1;
            top2<1>(k, b0, b1);
            sts64(sb + OFF_CST + 24, b0, b1);
            __syncwarp();
            e_arrive(BAR(B_SEL));
        }
    } else {
        reg_inc<232>();
        float a0[96], a1[96];
        {
            const int g = lane >> 2, c = lane & 3;
            uint4* stp = p.s->llstat + b * 16 + warp * 2 + (lane >> 4);
            if (lane == 0 || lane == 18) stg_zero(stp);
            spin_until(cstart + XD + XSTEP * warp);
            e_arrive_tx(BAR(B_XP + warp), 4096);
            bulk_load(sb + OFF_R0 + warp * 4096u, p.x + (size_t)(b * 16 + 2 * warp) * 1024, 4096, BAR(B_XP + warp));
            const uint32_t tag = get_tag(sb);
            if (tid < 64) sts128(sb + OFF_ONES + tid * 16, make_uint4(ONE2, ONE2, ONE2, ONE2));
            if (tid == 64) { sts64(sb + OFF_CST, role, tag); stsf(sb + OFF_CST + 48, -LOG2E); }
            if (AWAKE & 1) mbar_wait_awake(BAR(B_XP + warp), 0); else mbar_wait(BAR(B_XP + warp), 0);
            e_arrive(BAR(B_STP));
            if (warp == 7) TS(14);
            float s[2][4], q0[2][4], q1[2][4];
            #pragma unroll
            for (int i = 0; i < 4; i++) s[0][i] = s[1][i] = q0[0][i] = q0[1][i] = q1[0][i] = q1[1][i] = 0.f;
            uint32_t xa[8][4], xb[8][4];
            const uint32_t la = sb + OFF_R0 + warp * 4096u + (lane & 7) * 16u;
            #pragma unroll
            for (int i = 0; i < 8; i++) {
                ldsm4(xa[i], la + ((lane >> 3) & 1) * 2048u + (lane >> 4) * 128u + i * 256u);
                ldsm4(xb[i], la + ((lane >> 3) & 1) * 128u + (lane >> 4) * 2048u + i * 256u);
            }
            #pragma unroll
            for (int i = 0; i < 8; i++) {
                mma16816(q0[i & 1], xa[i][0], xa[i][1], xa[i][2], xa[i][3], xb[i][0], xb[i][1]);
                mma16816(q1[i & 1], xa[i][0], xa[i][1], xa[i][2], xa[i][3], xb[i][2], xb[i][3]);
                mma16816(s[i & 1], xa[i][0], xa[i][1], xa[i][2], xa[i][3], ONE2, ONE2);
            }
            const float s0 = s[0][0] + s[1][0], s1 = s[0][2] + s[1][2];
            const float sq0 = (g & 1) ? q0[0][1] + q0[1][1] : q0[0][0] + q0[1][0], sq1 = (g & 1) ? q1[0][3] + q1[1][3] : q1[0][2] + q1[1][2];
            const bool up = lane >= 16;
            float sm = (up ? s1 : s0) + shfl_x(up ? s0 : s1, 18), sq = (up ? sq1 : sq0) + shfl_x(up ? sq0 : sq1, 18);
            sm += shfl_x(sm, 9); sq += shfl_x(sq, 9);
            sm += shfl_x(sm, 4); sq += shfl_x(sq, 4);
            uint32_t m2, rh, rl; float rinv;
            ln_final(sm, sq, m2, rinv);
            split_rcp(rinv, rh, rl);
            if (lane == 0 || lane == 18) st_ll(stp, m2, rh, rl, tag);
            if (warp == 7) TS(15);
            uint4 st[2];
            if (PWAIT) { mbar_wait(BAR(B_STP), 0); if (warp < 7) spin_until(clk32() + PWAIT); }
            #pragma unroll 1
            for (int it = 0; it < POLL_MAX; it++) {
                st[0] = ld_ll(p.s->llstat + (b >> 3) * 128 + warp * 16 + g); st[1] = ld_ll(p.s->llstat + (b >> 3) * 128 + warp * 16 + g + 8);
                const uint32_t o = RDV ? ld_rlx(&p.s->llstat[((b >> 5) * 4 + c) * 128 + warp * 16 + 15].w) : tag;
                if (__all_sync(0xffffffffu, !tag_bad(tag_bad(o ^ tag, st[0].w, tag), st[1].w, tag))) break;
                if (AWAKE & 1) it += awake_zero();
            }
            e_arrive(BAR(B_STS));
            if (warp == 0) TS(16);
            const uint32_t lrow = warp * 16 + (lane & 15);
            uint32_t aad = sb + OFF_A + lrow * 128u + (((lane >> 4) ^ (lrow & 7)) << 4);
            uint32_t tad = sb + OFF_TAB + c * 16, ab = BAR(B_FA), pa = 0;
            uint32_t f0[4], f1[4];
            #define PREP(f, q) do { \
                const uint4 t = lds128(tad + (q) * 64); \
                ldsm4(f, aad ^ ((q) << 5)); \
                f[0] = lnmod(f[0], st[0].x, st[0].y, st[0].z, t.x, t.z); f[1] = lnmod(f[1], st[1].x, st[1].y, st[1].z, t.x, t.z); \
                f[2] = lnmod(f[2], st[0].x, st[0].y, st[0].z, t.y, t.w); f[3] = lnmod(f[3], st[1].x, st[1].y, st[1].z, t.y, t.w); } while (0)
            #define MMA(f, off) do { wg_fence(); mma192_rs<(off), H128>(a0, f, blo); mma192_rs<(off) + 768, H128>(a1, f, blo); wg_commit(); wg_wait<1>(); } while (0)
            mbar_wait(ab, 0);
            PREP(f0, 0);
            if (RDV) mbar_wait(BAR(B_STS), 0);
            #pragma unroll 1
            for (int j = 0; j < 16; j++) {
                const uint32_t bb = BAR(B_FB) + (j & 1) * 16, blo = desc_lo(sb + OFF_B, 4096) + (j & 1) * 3072, pb = (j >> 1) & 1;
                mbar_wait(bb, pb);
                wg_fence(); mma192_rsp<0, H128>(a0, f0, blo, j); mma192_rsp<768, H128>(a1, f0, blo, j); wg_commit(); wg_wait<1>();
                if (j) e_arrive((bb ^ 16) + 8 * (B_EB - B_FB) + 8);
                PREP(f1, 1);
                MMA(f1, 128);
                PREP(f0, 2);
                mbar_wait(bb + 8, pb);
                MMA(f0, 1536);
                e_arrive(bb + 8 * (B_EB - B_FB));
                PREP(f1, 3);
                MMA(f1, 1536 + 128);
                e_arrive(ab + 8 * (B_EA - B_FA));
                ab += 8; aad += 16384; tad += 256;
                if (ab == BAR(B_FA + 3)) { ab -= 24; aad -= 49152; pa ^= 1; }
                if (j < 15) mbar_wait(ab, pa);
                PREP(f0, 0);
            }
            #undef PREP
            #undef MMA
        }
        int tid_o; asm volatile("mov.u32 %0, %%tid.x;" : "=r"(tid_o) :: "memory");
        const int tid = tid_o, lane = tid & 31, warp = __shfl_sync(0xffffffffu, tid >> 5, 0), wgi = warp >> 2, g = lane >> 2, c = lane & 3;
        const uint32_t srow = warp * 16 + (lane & 15);
        #define T128(t) (sb + (((t) >> 5) * 16 + ((t) & 15)) * 128u + (((((t) >> 4) & 1) ^ ((t) & 7)) << 4))
        const uint32_t pa = T128(tid);
        mbar_wait(BAR(B_WPHI), 0);
        mbar_wait(BAR(B_EA), 1);
        wg_wait<0>();
        acc_fence(a0); acc_fence(a1);
        e_arrive(BAR(B_QE));
        if (warp == 0) TS(18);
        uint32_t ph[4][16];
        {
            uint32_t f1[16], kq[32], pk[16], mm[4], mn[2];
            float ea[32], eb[32], p0[16], p1[16];
            const uint32_t dw = desc_lo(sb + OFF_WPHI, 16);
            #define PMMA(f, o) do { wg_fence(); mma32_rs0<(o), H64>(p0, f, dw); mma32_rs0<(o) + 128, H64>(p1, f + 8, dw); \
                mma32_rs<(o) + 64, H64>(p0, f + 4, dw); mma32_rs<(o) + 192, H64>(p1, f + 12, dw); wg_commit(); } while (0)
            #define PWAIT0() do { wg_wait<0>(); acc_fence(p0); acc_fence(p1); } while (0)
            #define V_OUT(lo) _Pragma("unroll") for (int i = lo; i < lo + 4; i++) { const int o = 32 + 8 * i; \
                stsm4(sb + OFF_V + (i >> 1) * 8192u + srow * 64u + (((2 * (i & 1) + (lane >> 4)) ^ ((srow >> 1) & 3)) << 4), \
                      pack2(a1[o], a1[o + 1]), pack2(a1[o + 2], a1[o + 3]), pack2(a1[o + 4], a1[o + 5]), pack2(a1[o + 6], a1[o + 7])); }
            V_OUT(0);
            #pragma unroll
            for (int i = 0; i < 16; i++) pk[i] = pack2(a0[64 + 2 * i], a0[65 + 2 * i]);
            PMMA(pk, 0);
            V_OUT(4);
            #undef V_OUT
            #pragma unroll
            for (int i = 0; i < 16; i++) f1[i] = pack2(a1[2 * i], a1[2 * i + 1]);
            #pragma unroll
            for (int i = 0; i < 32; i++) kq[i] = pack2(a0[2 * i], a0[2 * i + 1]);
            PWAIT0();
            reg_dec<216>();
            if (warp == 0) TS(19);
            #define PHI_OUT(h) do { if (u == 0) { \
                    mbar_wait((h) >= 2 ? BAR(B_PE + ((h) & 1)) : (h) ? BAR(B_LMD) : BAR(B_QE), 0);          \
                    _Pragma("unroll") for (int q = 0; q < 4; q++) stsm4((pa ^ (q << 5)) + OFF_PHI + ((h) & 1) * 16384u, ph[h][4 * q], ph[h][4 * q + 1], ph[h][4 * q + 2], ph[h][4 * q + 3]); \
                    __syncwarp(); \
                    e_arrive(BAR(B_PF + (h))); } } while (0)
            #define NL() ldsf(sb + OFF_CST + 48)
            #pragma unroll 1
            for (int u = 0; u < 2; u++) {
                fm_max(p0, pk, mm); fm_max(p1, pk + 8, mm + 2);
                PMMA(f1, 256);
                fm_pos(pk, mm, ea);
                acc_fence(ea);
                PWAIT0();
                if (u) e_arrive(BAR(B_STP));
                fm_neg(mm, NL(), ea); fm_pos(pk + 8, mm + 2, eb);
                fm_norm(ea, ph[0]); fm_max(p0, pk, mm);
                PHI_OUT(0);
                fm_neg(mm + 2, NL(), eb); fm_pos(pk, mm, ea);
                fm_norm(eb, ph[1]); fm_max(p1, pk + 8, mn);
                PHI_OUT(1);
                if (warp == 0) TS(21 + 2 * u);
                fm_neg(mm, NL(), ea); fm_pos(pk + 8, mn, eb);
                fm_norm(ea, ph[2]);
                PHI_OUT(2);
                PMMA(kq, 0);
                fm_neg(mn, NL(), eb);
                fm_norm(eb, ph[3]);
                PHI_OUT(3);
                PWAIT0();
                #pragma unroll
                for (int i = 0; i < 16; i++) f1[i] = kq[16 + i];
                if (warp == 0) TS(22 + 2 * u);
            }
            #undef NL
            #undef PHI_OUT
            #undef PWAIT0
            #undef PMMA
        }
        uint32_t gf[16][4], uf[16][4];
        const uint32_t fo = sb + (warp >> 1) * 2048u + ((lane & 7) + (lane >> 4) * 8) * 64u + (((2 * (warp & 1) + ((lane >> 3) & 1)) ^ ((lane >> 1) & 3)) << 4);
        #define F_LOAD(f, off, i) ldsm4t(f[i], fo + (off) + ((i) >> 1) * 8192u + ((i) & 1) * 1024u)
        #define G_LOAD(lo, n) _Pragma("unroll") for (int i = lo; i < lo + n; i++) F_LOAD(gf, OFF_R0, i)
        #define O_BLOCK(pp, ph0, ph1) do { \
            if ((AWAKE & 2) && !(pp)) mbar_wait_awake(BAR(B_KVT + (pp)), 0); else mbar_wait(BAR(B_KVT + (pp)), 0); \
            if (warp == 0) TS(25 + 3 * (pp)); \
            const uint32_t oa = T128(tid + (lds32(sb + OFF_CST) >> 16)); \
            float o0[20], o1[20]; \
            const uint32_t dk = (pp) ? desc_lo(sb + OFF_KL, OFF_Z + 32 - OFF_KL) : desc_lo(sb + OFF_KVT, OFF_Z - OFF_KVT); \
            constexpr uint32_t K1 = 256u - (255u << 16);          \
            wg_fence(); \
            mma40_rs0<0, H64>(o0, ph0, dk); mma40_rs0<K1, H64>(o1, ph1, dk); \
            mma40_rs<64, H64>(o0, ph0 + 4, dk); mma40_rs<K1 + 64, H64>(o1, ph1 + 4, dk); \
            mma40_rs<128, H64>(o0, ph0 + 8, dk); mma40_rs<K1 + 128, H64>(o1, ph1 + 8, dk); \
            mma40_rs<192, H64>(o0, ph0 + 12, dk); mma40_rs<K1 + 192, H64>(o1, ph1 + 12, dk); \
            wg_commit(); \
            wg_wait<0>(); \
            acc_fence(o0); acc_fence(o1); \
            if (pp) e_arrive(BAR(B_ED)); \
            if (warp == 0) TS(26 + 3 * (pp)); \
              \
            if (pp) { G_LOAD(12, 4); } \
            mbar_wait(BAR(B_GE + (pp)), 0);          \
            uint32_t chk = 0; \
            _Pragma("unroll") for (int hh = 0; hh < 2; hh++) { \
                const float (&o)[20] = hh ? o1 : o0; \
                uint32_t h0, l0, h1, l1; \
                split_rcp(rcp(rbf(rbf(o[16]) + 1e-6f)), h0, l0); split_rcp(rcp(rbf(rbf(o[18]) + 1e-6f)), h1, l1); \
                _Pragma("unroll") for (int q = 0; q < 2; q++) { \
                    const uint32_t r0 = hdiv2(pack2(o[8 * q], o[8 * q + 1]), h0, l0), r1 = hdiv2(pack2(o[8 * q + 2], o[8 * q + 3]), h1, l1); \
                    stsm4((oa ^ ((2 * hh + q) << 5)) + OFF_R0 + (pp) * 16384u, r0, r1, \
                          hdiv2(pack2(o[8 * q + 4], o[8 * q + 5]), h0, l0), hdiv2(pack2(o[8 * q + 6], o[8 * q + 7]), h1, l1)); \
                    chk ^= r0 ^ r1; \
                } \
            } \
            fence_async_smem(); \
            __syncwarp(); \
            e_arrive(BAR(B_OWN + (pp))); \
            sts32(sb + OFF_CHK + (pp) * 32 + warp * 4, __reduce_xor_sync(0xffffffffu, c == (g >> 1) ? chk : 0u)); \
            if (!(pp)) { G_LOAD(4, 8); fence_async_smem(); } \
            __syncwarp(); \
            e_arrive(BAR(B_CS + (pp))); \
            if (warp == 0) TS(27 + 3 * (pp)); \
        } while (0)
        float acc[64];
        const uint32_t da = desc_lo(sb + OFF_R0 + wgi * 8192u, 16), db = desc_lo(sb + OFF_DB, 8192);
        #define D_MMA(first, a, s) do { \
            wg_fence(); \
            first<(a), H128, (s) * 1024, H128>(acc, da, db); mma128_ss<(a) + 2, H128, (s) * 1024 + 128, H128>(acc, da, db); \
            mma128_ss<(a) + 4, H128, (s) * 1024 + 256, H128>(acc, da, db); mma128_ss<(a) + 6, H128, (s) * 1024 + 384, H128>(acc, da, db); \
            wg_commit(); } while (0)
        mbar_wait(BAR(B_GF), 0);
        G_LOAD(0, 4);
        e_arrive(BAR(B_GE));
        O_BLOCK(0, ph[0], ph[1]);
        mbar_wait(BAR(B_OWN), 0);
        mbar_wait(BAR(B_FD), 0);
        D_MMA(mma128_ss0, 0, 0);
        O_BLOCK(1, ph[2], ph[3]);
        reg_inc<232>();
        mbar_wait(BAR(B_OWN + 1), 0);
        #undef O_BLOCK
        #define D_STEP(n) do { \
            mbar_wait(BAR(B_FD + ((n) & 3)), ((n) >> 2) & 1); \
            if (warp == 0) TR(112 + (n)); \
            D_MMA(mma128_ss, (n) == 5 ? OFF_X1 / 16 : ((n) & 3) * 1024, (n) & 3); \
            if ((n) == 3) mbar_wait(BAR(B_UF), 0); \
            if ((n) >= 3 && (n) < 7) { F_LOAD(uf, OFF_F2, 2 * (((n) + 5) & 7)); F_LOAD(uf, OFF_F2, 2 * (((n) + 5) & 7) + 1); } \
            wg_wait<1>(); \
            if ((n) == 7) fence_async_smem();         \
            if ((n) > 2) e_arrive(BAR(B_ED + (((n) + 3) & 3))); } while (0)
        D_STEP(1);
        wg_wait<0>();
        e_arrive(BAR(B_ED + 1));
        D_STEP(2);
        if (warp == 0) TS(31);
        D_STEP(3); D_STEP(4); D_STEP(5); D_STEP(6); D_STEP(7); D_STEP(8); D_STEP(9); D_STEP(10); D_STEP(11); D_STEP(12); D_STEP(13); D_STEP(14); D_STEP(15);
        #undef D_STEP
        #undef D_MMA
        mbar_wait(BAR(B_PAR), 0);
        const uint4 mis = lds128(sb + OFF_CHK + 128);
        if (mis.x ^ mis.y ^ mis.z ^ mis.w) {
            const uint2 rt = lds64(sb + OFF_CST);
            const int rb = (rt.x >> 3) & 15;
            wg_wait<0>();
            poll_flags(FLO(2, rb * 8 + (lane & 7)), rt.y);
            #pragma unroll 1
            for (int kb = 0; kb < 16; kb++) {
                bar_sync(1, 256);
                if (warp == 0) {
                    e_arrive_tx(BAR(B_RD), 32768);
                    bulk_load(sb + OFF_R0 + 32768, p.s->os + (size_t)(rb * 16 + kb) * 1024, 16384, BAR(B_RD));
                    tma_load4(sb + OFF_DB + 32768, &tmWo, kb * 64, (rt.x & 7) * 2, BAR(B_RD));
                }
                mbar_wait(BAR(B_RD), kb & 1);
                wg_fence();
                mma128_ssp<2048, H128, 2048, H128>(acc, da, db, kb); mma128_ss<2050, H128, 2048 + 128, H128>(acc, da, db);
                mma128_ss<2052, H128, 2048 + 256, H128>(acc, da, db); mma128_ss<2054, H128, 2048 + 384, H128>(acc, da, db);
                wg_commit();
                wg_wait<0>();
            }
        }
        #define XADDR(i) ((xa ^ (((i) & 3) << 5)) + ((i) < 4 ? OFF_R0 : OFF_X1))
        const uint4 cst = lds128(sb + OFF_CST);
        const int b = cst.x & 255;
        const uint32_t tag = cst.y, xa = T128(tid + (cst.x >> 16));
        uint4 w[4];
        const uint32_t rl = warp * 16 + g + 8 * (c & 1);
        const uint4* ws = pin_ptr(p.s->llln2 + ((b & ~7) + (c >> 1) * 4) * 128 + rl);
        {
        {
            uint32_t x2[8][4];
            mbar_wait(BAR(B_WPHI), 1);
            #pragma unroll
            for (int i = 0; i < 8; i++) ldsm4(x2[i], XADDR(i));
            uint4* d = pin_ptr(p.s->llln2 + b * 128 + warp * 16 + g);
            const uint32_t ta = sb + OFF_T1 + (g & 1) * 512 + c * 16;
            uint4 t = lds128(ta), tn = lds128(ta + 64);
            wg_wait<0>();
            acc_fence(acc);
            e_arrive(BAR(B_ED + 3));
            if (warp == 0) TS(32);
            float sd[4] = {0.f, 0.f, 0.f, 0.f}, qa[4] = {0.f, 0.f, 0.f, 0.f}, qb[4] = {0.f, 0.f, 0.f, 0.f};
            #pragma unroll
            for (int i = 0; i < 8; i++) {
                x2[i][0] = hadd2(x2[i][0], hmul2(t.x, pack2(acc[8 * i], acc[8 * i + 1]))); x2[i][1] = hadd2(x2[i][1], hmul2(t.x, pack2(acc[8 * i + 2], acc[8 * i + 3])));
                x2[i][2] = hadd2(x2[i][2], hmul2(t.y, pack2(acc[8 * i + 4], acc[8 * i + 5]))); x2[i][3] = hadd2(x2[i][3], hmul2(t.y, pack2(acc[8 * i + 6], acc[8 * i + 7])));
                mma16816(sd, x2[i][0], x2[i][1], x2[i][2], x2[i][3], t.z, t.w);
                t = tn;
                if (i < 6) tn = lds128(ta + (i + 2) * 64);
                mma16816(qa, x2[i][0], x2[i][1], x2[i][2], x2[i][3], x2[i][0], x2[i][2]);
                mma16816(qb, x2[i][0], x2[i][1], x2[i][2], x2[i][3], x2[i][1], x2[i][3]);
            }
            if (c == (g >> 1)) {
                st_ll(d, f2u(sd[0]), f2u((g & 1) ? qa[1] : qa[0]), f2u(sd[1]), tag);
                st_ll(d + 8, f2u(sd[2]), f2u((g & 1) ? qb[3] : qb[2]), f2u(sd[3]), tag);
            }
            __syncwarp();
            #pragma unroll
            for (int i = 0; i < 4; i++) w[i] = ld_ll(ws + i * 128);
            if (warp == 0) TS(33);
            #pragma unroll
            for (int i = 0; i < 8; i++) stsm4(XADDR(i), x2[i][0], x2[i][1], x2[i][2], x2[i][3]);
        }
        uint4 t2[8]; uint2 t3[8];
        #pragma unroll
        for (int i = 0; i < 8; i++) { t2[i] = lds128(sb + OFF_T2 + i * 64 + c * 16); t3[i] = lds64(sb + OFF_T3 + i * 32 + c * 8); }
        mbar_wait(BAR(B_ED + 3), 1);
        {
            #pragma unroll 1
            for (int it = 0; it < POLL_MAX; it++) {
                if (__all_sync(0xffffffffu, !(tag_bad(w[0].w ^ tag, w[1].w, tag) | tag_bad(w[2].w ^ tag, w[3].w, tag)))) break;
                #pragma unroll
                for (int i = 0; i < 4; i++) if (w[i].w != tag) w[i] = ld_ll(ws + i * 128);
            }
            float s1 = (u2f(w[0].x) + u2f(w[1].x)) + (u2f(w[2].x) + u2f(w[3].x));
            float s2 = (u2f(w[0].y) + u2f(w[1].y)) + (u2f(w[2].y) + u2f(w[3].y));
            float dt = (u2f(w[0].z) + u2f(w[1].z)) + (u2f(w[2].z) + u2f(w[3].z));
            s1 += shfl_x(s1, 2); s2 += shfl_x(s2, 2); dt += shfl_x(dt, 2);
            uint32_t m2, rh, rl2; float rinv;
            ln_final(s1, s2, m2, rinv);
            const uint32_t key = (f2key(fmaf(fmaf(-bf_lo(m2), u2f(cst.z), dt), rinv, u2f(cst.w))) | 2047u) ^ ((b >> 3) * 128 + rl);
            split_rcp(rinv, rh, rl2);
            if (c < 2) { sts32(sb + OFF_KEY + rl * 4, key); sts128(sb + OFF_ST2 + rl * 16, make_uint4(m2, rh, rl2, 0)); }
            __syncwarp();
            e_arrive(BAR(B_KEYS));
        }
        if (warp == 0) TS(34);
        {
            const uint4 s0 = lds128(sb + OFF_ST2 + (warp * 16 + g) * 16), s1 = lds128(sb + OFF_ST2 + (warp * 16 + g + 8) * 16);
            uint32_t x2[8][4];
            #pragma unroll
            for (int i = 0; i < 8; i++) ldsm4(x2[i], XADDR(i));
            const uint32_t oa = xa + warp * 2048u;
            #pragma unroll
            for (int i = 0; i < 8; i++) {
                const uint4 t = t2[i]; const uint2 gb = t3[i];
                stsm4((oa ^ ((i & 3) << 5)) + OFF_OUT + (i >> 2) * 2048u,
                      hadd2(x2[i][0], hmul2(gb.x, lnmod(x2[i][0], s0.x, s0.y, s0.z, t.x, t.z))), hadd2(x2[i][1], hmul2(gb.x, lnmod(x2[i][1], s1.x, s1.y, s1.z, t.x, t.z))),
                      hadd2(x2[i][2], hmul2(gb.y, lnmod(x2[i][2], s0.x, s0.y, s0.z, t.y, t.w))), hadd2(x2[i][3], hmul2(gb.y, lnmod(x2[i][3], s1.x, s1.y, s1.z, t.y, t.w))));
            }
            __syncwarp();
            e_arrive(BAR(B_SWP));
        }
        }
        #undef XADDR
        if (warp == 0) TS(35);
        uint32_t fx = 0, fh = 0, fg = 0, fs2, frow;
        uint32_t df[16][4];
        const uint32_t dfo = sb + warp * 4096u + ((lane & 7) + (lane >> 4) * 8) * 128u + ((((lane >> 3) & 1) ^ (lane & 7)) << 4);
        #define DF_LOAD(i) ldsm4t(df[i], (dfo + ((i) < 8 ? OFF_F2 : OFF_DB) + ((i) & 1) * 2048u) ^ ((((i) >> 1) & 3) << 5))
        {
            const int wi = ((tid >> 3) & 7) * 32 + (tid >> 6) * 8 + (tid & 7);
            const uint4* rh = pin_ptr(p.s->llrowh + wi);
            #pragma unroll
            for (int i = 8; i < 16; i++) F_LOAD(uf, OFF_F2, i);
            mbar_wait(BAR(B_SEL) + ((AWAKE & 4) ? awake_zero() : 0), 0);
            const uint2 bb = lds64(sb + OFF_CST + 24);
            const uint32_t b0 = bb.x, b1 = bb.y;
            if (warp == 0) TS(36);
            const uint32_t o0 = (~b0 & 0x780u) * 4, o1 = (~b1 & 0x780u) * 4, slot0 = o0, slot1 = o1 + (o0 == o1 ? 256 : 0);
            const int wd = ((g & 1) ? slot1 : slot0) + b * 2 + (c >> 1) - wi;
            uint4 hv[2], fv[2];
            #pragma unroll 1
            for (int it = 0; it < POLL_MAX; it++) {
                hv[0] = ld_ll(rh + slot0); hv[1] = ld_ll(rh + slot1);
                uint32_t bad = 0;
                if (warp == 0) {
                    fv[0] = ld_ll(rh + wd + 8192); fv[1] = ld_ll(rh + wd);
                    bad = tag_bad(fv[0].w ^ tag, fv[1].w, tag);
                    fx = (g & 2) ? fv[0].y : fv[0].x; fh = (g & 2) ? fv[1].y : fv[1].x; fg = (g & 2) ? fv[0].z : fv[1].z;
                }
                if (it == 0) {
                    mbar_wait(BAR(B_WD), 0);
                    #pragma unroll
                    for (int i = 0; i < NDF; i++) DF_LOAD(i);
                }
                if (__all_sync(0xffffffffu, !ll_bad<1>(ll_bad<1>(bad, hv[0], tag), hv[1], tag))) break;
            }
            const uint32_t ha = sb + OFF_HSEL + (tid >> 3) * 128u + c * 16u + (g & 1) * 8u;
            sts64(ha, hv[0].x, hv[0].y); sts64(ha + 64, hv[1].x, hv[1].y);
            bar_sync(2 + (warp >> 1), 64);
            const uint32_t bk = (g & 1) ? b1 : b0;
            frow = ~bk & 2047u;
            const float sg = sigmoid_f(rbf(key2f((bk & ~2047u) | 1024u)));
            fs2 = pack2(sg, sg);
        }
        if (warp == 0) TS(37);
        uint4* yd = p.s->lly + (cst.x >> 8) * 512 + (warp * 8 + c) * 8 + g;
        const uint4* ys = p.s->lly + (tid >> 2) * 512 + b * 4 + c;
        uint16_t* od = (uint16_t*)p.out + (size_t)frow * 1024 + (b >> 1) * 16 + (b & 1) * 4 + c + 8 * (g >> 1);
        {
            float ag[2][4], au[2][4];
            #pragma unroll
            for (int i = 0; i < 4; i++) ag[0][i] = ag[1][i] = au[0][i] = au[1][i] = 0.f;
            const uint32_t ha = sb + OFF_HSEL + (warp >> 1) * 1024u + (lane & 7) * 16u;
            uint4 hn = lds128(ha), hm = lds128(ha + 128);
            #pragma unroll
            for (int i = 0; i < 8; i++) {
                const uint4 h = hn;
                hn = hm;
                if (i < 6) hm = lds128(ha + (i + 2) * 128u);
                mma16816(ag[0], gf[2 * i][0], gf[2 * i][1], gf[2 * i][2], gf[2 * i][3], h.x, h.y);
                mma16816(au[0], uf[2 * i][0], uf[2 * i][1], uf[2 * i][2], uf[2 * i][3], h.x, h.y);
                mma16816(ag[1], gf[2 * i + 1][0], gf[2 * i + 1][1], gf[2 * i + 1][2], gf[2 * i + 1][3], h.z, h.w);
                mma16816(au[1], uf[2 * i + 1][0], uf[2 * i + 1][1], uf[2 * i + 1][2], uf[2 * i + 1][3], h.z, h.w);
                if (NDF + 2 * i < 16) { DF_LOAD((NDF + 2 * i) & 15); DF_LOAD((NDF + 2 * i + 1) & 15); }
            }
            sts64(sb + OFF_RED + (warp >> 1) * 512u + (c & 1) * 256u + ((warp & 1) * 16 + (c >> 1) * 8 + g) * 8u,
                  f2u(sel4(c, ag[0][0], ag[0][1], ag[0][2], ag[0][3]) + sel4(c, ag[1][0], ag[1][1], ag[1][2], ag[1][3])),
                  f2u(sel4(c, au[0][0], au[0][1], au[0][2], au[0][3]) + sel4(c, au[1][0], au[1][1], au[1][2], au[1][3])));
        }
        yd = pin_ptr(yd); ys = pin_ptr(ys); od = pin_ptr(od); pin<1>(&fs2);
        bar_sync(1, 256);
        {
            const uint32_t ra = sb + OFF_RED + lane * 16u;
            const uint4 r0 = lds128(ra), r1 = lds128(ra + 512), r2 = lds128(ra + 1024), r3 = lds128(ra + 1536);
            #define F4(f) ((u2f(r0.f) + u2f(r1.f)) + (u2f(r2.f) + u2f(r3.f)))
            const uint32_t hid = hmul2(silu2(pack2(F4(x), F4(z))), pack2(F4(y), F4(w)));
            #undef F4
            if (warp == 0) TS(38);
            const int src = (g & 1) * 16 + c;
            const uint32_t b0 = __shfl_sync(0xffffffffu, hid, src), b1 = __shfl_sync(0xffffffffu, hid, src + 4), b2 = __shfl_sync(0xffffffffu, hid, src + 8), b3 = __shfl_sync(0xffffffffu, hid, src + 12);
            float y[8][4];
            #pragma unroll
            for (int i = 0; i < 8; i++) {
                y[i][0] = y[i][1] = y[i][2] = y[i][3] = 0.f;
                mma16816(y[i], df[2 * i][0], df[2 * i][1], df[2 * i][2], df[2 * i][3], b0, b1);
            }
            #pragma unroll
            for (int i = 0; i < 8; i++) mma16816(y[i], df[2 * i + 1][0], df[2 * i + 1][1], df[2 * i + 1][2], df[2 * i + 1][3], b2, b3);
            if (cst.x < 112 * 256) {
                #pragma unroll
                for (int h = 0; h < 2; h++) {
                    #define YS(e) sel4(c, y[4 * h][e], y[4 * h + 1][e], y[4 * h + 2][e], y[4 * h + 3][e])
                    st_ll4(yd + 32 * h, YS(0), YS(1), YS(2), YS(3), tag);
                    #undef YS
                }
            }
        }
        if (warp == 0) TS(39);
        if (warp < 7) {
            uint4 v[2];
            v[0].w = v[1].w = 0;
            spin_until(clk32() + YWAIT);
            #pragma unroll 1
            for (int it = 0; it < POLL_MAX; it++) {
                if ((v[0].w ^ tag) & 3) v[0] = ld_ll(ys);
                if ((v[1].w ^ tag) & 3) v[1] = ld_ll(ys + 56 * 512);
                if (__all_sync(0xffffffffu, !(tag_bad(v[0].w ^ tag, v[1].w, tag) & 3))) break;
            }
            float y0 = u2f(v[0].x) + u2f(v[1].x), y1 = u2f(v[0].y) + u2f(v[1].y), y2 = u2f(v[0].z) + u2f(v[1].z), y3 = u2f(v[0].w) + u2f(v[1].w);
            const bool g0 = g & 1, g1 = g & 2;
            const float k0 = (g0 ? y1 : y0) + shfl_x(g0 ? y0 : y1, 4), k1 = (g0 ? y3 : y2) + shfl_x(g0 ? y2 : y3, 4);
            const float y = (g1 ? k1 : k0) + shfl_x(g1 ? k0 : k1, 8);
            stsf(sb + OFF_RED2 + (lane & 15) * 64u + (lane >> 4) * 32u + warp * 4u, y);
            bar_sync(6, 224);
            if (tid < 16) {
                const uint32_t a = sb + OFF_RED2 + lane * 64u;
                const uint4 ya = lds128(a), yb = lds128(a + 16), yc = lds128(a + 32), ye = lds128(a + 48);
                const float s = (((u2f(ya.x) + u2f(ya.y)) + (u2f(ya.z) + u2f(ya.w))) + ((u2f(yb.x) + u2f(yb.y)) + u2f(yb.z)))
                              + (((u2f(yc.x) + u2f(yc.y)) + (u2f(yc.z) + u2f(yc.w))) + ((u2f(ye.x) + u2f(ye.y)) + u2f(ye.z)));
                const uint32_t o = hadd2(fx, hmul2(fg, hadd2(fh, hmul2(pack2(s, s), fs2))));
                *od = (c & 1) ? o >> 16 : o;
                if (b == 0 && tid == 0) p.s->done[0] = tag;
                TS(40);
            }
        }
    }
}

typedef CUresult (*EncodeFn)(CUtensorMap*, CUtensorMapDataType, cuuint32_t, void*, const cuuint64_t*, const cuuint64_t*, const cuuint32_t*,
                             const cuuint32_t*, CUtensorMapInterleave, CUtensorMapSwizzle, CUtensorMapL2promotion, CUtensorMapFloatOOBfill);

CUtensorMap make_map(EncodeFn enc, const void* ptr, uint64_t cols, uint64_t rows, uint32_t bc, uint32_t br, CUtensorMapSwizzle swz, CUtensorMapL2promotion promo) {
    CUtensorMap m;
    cuuint64_t dims[2] = {cols, rows}, strides[1] = {cols * 2};
    cuuint32_t box[2] = {bc, br}, es[2] = {1, 1};
    enc(&m, CU_TENSOR_MAP_DATA_TYPE_BFLOAT16, 2, const_cast<void*>(ptr), dims, strides, box, es, CU_TENSOR_MAP_INTERLEAVE_NONE, swz, promo,
        CU_TENSOR_MAP_FLOAT_OOB_FILL_NONE);
    return m;
}
CUtensorMap make_map4(EncodeFn enc, const void* ptr, uint32_t groups, uint64_t rows, uint32_t br, CUtensorMapL2promotion promo) {
    CUtensorMap m;
    cuuint64_t dims[4] = {64, rows, 16, groups}, strides[3] = {groups * 2048ull, 128, 2048};
    cuuint32_t box[4] = {64, br, 2, groups}, es[4] = {1, 1, 1, 1};
    enc(&m, CU_TENSOR_MAP_DATA_TYPE_BFLOAT16, 4, const_cast<void*>(ptr), dims, strides, box, es, CU_TENSOR_MAP_INTERLEAVE_NONE, CU_TENSOR_MAP_SWIZZLE_128B, promo,
        CU_TENSOR_MAP_FLOAT_OOB_FILL_NONE);
    return m;
}

}

extern "C" void kernel_launch(void* const* d_in, const int* in_sizes, int n_in, void* d_out, int out_size) {
    (void)in_sizes; (void)n_in; (void)out_size;
    void* fn = nullptr; cudaDriverEntryPointQueryResult qr;
    cudaGetDriverEntryPoint("cuTensorMapEncodeTiled", &fn, cudaEnableDefault, &qr);
    EncodeFn enc = (EncodeFn)fn;
    void* hs = nullptr;
    cudaGetSymbolAddress(&hs, g_scratch);
    int dev = 0, sms = 0;
    cudaGetDevice(&dev);
    cudaDeviceGetAttribute(&sms, cudaDevAttrMultiProcessorCount, dev);
    const CUtensorMapL2promotion P256 = CU_TENSOR_MAP_L2_PROMOTION_L2_256B, P128 = CU_TENSOR_MAP_L2_PROMOTION_L2_128B, P0 = CU_TENSOR_MAP_L2_PROMOTION_NONE;
    CUtensorMap tmW = make_map4(enc, d_in[1], 3, 1024, 32, P256);
    CUtensorMap tmWo = make_map4(enc, d_in[3], 1, 1024, 64, P256);
    CUtensorMap tmO = make_map4(enc, d_out, 1, 2048, 16, P0);
    CUtensorMap tmPhi = make_map(enc, d_in[2], 32, 1024, 32, 128, CU_TENSOR_MAP_SWIZZLE_64B, P128);
    CUtensorMap tmG = make_map(enc, d_in[6], 3584, 1024, 32, 128, CU_TENSOR_MAP_SWIZZLE_64B, P0);
    CUtensorMap tmU = make_map(enc, d_in[7], 3584, 1024, 32, 128, CU_TENSOR_MAP_SWIZZLE_64B, P0);
    CUtensorMap tmD = make_map(enc, d_in[8], 1024, 3584, 64, 32, CU_TENSOR_MAP_SWIZZLE_128B, P128);
    CUtensorMap tmX = make_map(enc, d_in[0], 1024, 2048, 64, 128, CU_TENSOR_MAP_SWIZZLE_128B, P128);
    CUtensorMap tmM = make_map(enc, d_in[10], 6144, 1024, 64, 256, CU_TENSOR_MAP_SWIZZLE_128B, MPROMO);
    Ptrs p;
    p.x = (const bf16*)d_in[0]; p.c = (const bf16*)d_in[9]; p.wmod = (const bf16*)d_in[10]; p.wr = (const bf16*)d_in[5];
    p.wg = (const bf16*)d_in[6]; p.wu = (const bf16*)d_in[7]; p.wd = (const bf16*)d_in[8]; p.out = (bf16*)d_out; p.s = (Scratch*)hs;
    p.wqkv = (const bf16*)d_in[1]; p.wo = (const bf16*)d_in[3];
    p.by_sm = sms == 132;
    for (int sm = 0; sm < 132; sm++) {
        const int tp = sm >> 1, u = tp - 32;
        const int gp = (GPERM >> (4 * (tp < 32 ? tp & 7 : tp < 60 ? 1 + u % 7 : 0))) & 7, sl = 2 * (tp < 32 ? tp >> 3 : tp < 60 ? 4 + u / 7 : tp - 58) + (sm & 1);
        const int b = (tp >> 1) == 30 ? sm + 8 : ((gp >> 1) * 4 + (sl & 3)) * 8 + (gp & 1) * 4 + (sl >> 2);
        const int f = FMODE == 0 ? (b < 112 ? b : 255) : FMODE == 1 ? (sl < 14 && b < 128 ? gp * 14 + sl : 255) : (sm < 112 ? sm : 255);
        p.role[sm] = (uint16_t)(b | f << 8);
    }
    cudaFuncSetAttribute(fused_kernel, cudaFuncAttributeMaxDynamicSharedMemorySize, SMEM_BYTES);
    fused_kernel<<<132, NTHREADS, SMEM_BYTES, cudaStreamPerThread>>>(p, tmM, tmX, tmW, tmWo, tmPhi, tmG, tmU, tmD, tmO);
}
```

```cpp
#include <cuda_runtime.h>
#include <cuda.h>
#include <cuda_bf16.h>
#include <stdint.h>

namespace {

typedef __nv_bfloat16 bf16;

#define NFREE 4
constexpr int NTHREADS = 512;
constexpr int POLL_MAX = 400000;

constexpr uint32_t OFF_R0   = 0;
constexpr uint32_t OFF_A    = 65536;
constexpr uint32_t OFF_B    = 114688;
constexpr uint32_t OFF_U1   = 65536;
constexpr uint32_t OFF_PHI  = 98304;
constexpr uint32_t OFF_F2   = OFF_PHI;
constexpr uint32_t OFF_DB   = 131072;
constexpr uint32_t OFF_V    = 163840;
constexpr uint32_t OFF_KL1  = OFF_V;
constexpr uint32_t OFF_KL   = 196608;
constexpr uint32_t OFF_WPHI = 214016;
constexpr uint32_t OFF_KVT  = OFF_WPHI;
constexpr uint32_t OFF_Z    = 222208;
constexpr uint32_t OFF_TAB  = OFF_Z;
constexpr uint32_t OFF_ONES = 226304;
constexpr uint32_t OFF_BAR  = 227328;
constexpr uint32_t OFF_CST  = OFF_BAR + 640;
constexpr uint32_t OFF_T1   = OFF_ONES;
constexpr uint32_t OFF_T2   = OFF_CST + 64;
constexpr uint32_t OFF_T3   = OFF_T2 + 512;
constexpr uint32_t OFF_KEY  = OFF_T3 + 256;
constexpr uint32_t OFF_ST2  = OFF_KEY + 512;
constexpr uint32_t OFF_CHK  = OFF_KEY;
constexpr uint32_t OFF_ZS   = OFF_ST2;
constexpr uint32_t SMEM_BYTES = 232448;
constexpr uint32_t OFF_X1   = OFF_KL;
constexpr uint32_t OFF_OUT  = OFF_R0 + 32768;
constexpr uint32_t OFF_HSEL = OFF_WPHI;
constexpr uint32_t OFF_RED  = OFF_WPHI + 4096;
constexpr uint32_t OFF_RED2 = OFF_RED + 2048;
static_assert(OFF_ST2 + 2048 <= SMEM_BYTES, "layout");

enum {
    B_O1 = 0, B_UF = 1, B_UD = 2, B_WPHI = 3, B_FB = 4  , B_OST = 8, B_GF = 9, B_WD = 10, B_KVL = 11  , B_KZ = 13, B_LMF = 14, B_SEL = 15, B_XP = 16  , B_TAG = 24,
    B_FA = 25  , B_FD = 30  , B_CAND = 34,
    B_KST = 37  , B_KVT = 41  , B_LMD = 43, B_PAR = 44,
    B_EA = 45  , B_EB = 48  , B_PF = 56  , B_OWN = 60  , B_QE = 62, B_STP = 63, B_KEYS = 64, B_SWP = 65, B_STS = 66, B_GE = 67, B_CS = B_GE + 1  ,
    B_ED = 70  ,
    B_RD = 75
};

struct Scratch {
    uint4 os[16 * 16 * 1024];
    uint4 kvacc[8 * 4 * 528];
    uint4 flk[3 * 128 * 2];
    uint4 llstat[2048];
    uint4 llm1[16 * 64];
    uint4 flo[3 * 128 * 2];
    uint4 llmod2[2 * 256];
    uint4 llg[2 * 4 * 256];
    uint4 llln2[16 * 8 * 128];
    uint4 llcand[16 * 2];
    uint4 llrowh[32 * 256];
    uint4 llrowx[32 * 256];
    uint4 lly[128 * 512];
    unsigned done[4];
};
__device__ __align__(1024) Scratch g_scratch;
#define GT(i) do {} while (0)
#define TS(i) do {} while (0)
#define TR(i) do {} while (0)

__device__ __forceinline__ uint32_t smem_u32(const void* p) { return (uint32_t)__cvta_generic_to_shared(p); }
__device__ __forceinline__ uint32_t clk32() { uint32_t c; asm volatile("mov.u32 %0, %%clock;" : "=r"(c) :: "memory"); return c; }
__device__ __forceinline__ void spin_until(uint32_t t) { while ((int)(clk32() - t) < 0) {} }
__device__ __forceinline__ void sleep_until(uint32_t t) { while ((int)(clk32() - t) < 0) __nanosleep(40); }
__device__ __forceinline__ void mbar_init_fence() { asm volatile("fence.mbarrier_init.release.cluster;" ::: "memory"); }
__device__ __forceinline__ void mbar_wait(uint32_t bar, uint32_t parity) {
    asm volatile("{\n.reg .pred P1;\nLAB_WAIT:\nmbarrier.try_wait.parity.shared::cta.b64 P1, [%0], %1;\n@!P1 bra LAB_WAIT;\n}" :: "r"(bar), "r"(parity) : "memory");
}
__device__ __forceinline__ uint64_t policy_evict_first() { uint64_t p; asm("createpolicy.fractional.L2::evict_first.b64 %0, 1.0;" : "=l"(p)); return p; }
#define ELECT "{\n.reg .pred e;\nelect.sync _|e, 0xffffffff;\n@e "
__device__ __forceinline__ void e_arrive(uint32_t bar) { asm volatile(ELECT "mbarrier.arrive.shared::cta.b64 _, [%0];\n}" :: "r"(bar) : "memory"); }
__device__ __forceinline__ void e_arrive_after(uint32_t bar, uint32_t v) {
    asm volatile("{\n.reg .pred e;\n.reg .b32 n;\npopc.b32 n, %1;\nshr.u32 n, n, 4;\nmul.lo.u32 n, n, n;\nshr.u32 n, n, 3;\nadd.u32 n, n, %0;\n"
        "elect.sync _|e, 0xffffffff;\n@e mbarrier.arrive.shared::cta.b64 _, [n];\n}" :: "r"(bar), "r"(v) : "memory");
}
__device__ __forceinline__ void e_arrive_tx(uint32_t bar, uint32_t bytes) { asm volatile(ELECT "mbarrier.arrive.expect_tx.shared::cta.b64 _, [%0], %1;\n}" :: "r"(bar), "r"(bytes) : "memory"); }
__device__ __forceinline__ void e_init(uint32_t bar, uint32_t cnt) { asm volatile(ELECT "mbarrier.init.shared::cta.b64 [%0], %1;\n}" :: "r"(bar), "r"(cnt) : "memory"); }
__device__ __forceinline__ void tma_load_ef(uint32_t dst, const CUtensorMap* tm, int c0, int c1, uint32_t bar) {
    asm volatile(ELECT "cp.async.bulk.tensor.2d.shared::cluster.global.mbarrier::complete_tx::bytes.L2::cache_hint [%0], [%1, {%3, %4}], [%2], %5;\n}"
        :: "r"(dst), "l"(tm), "r"(bar), "r"(c0), "r"(c1), "l"(policy_evict_first()) : "memory");
}
__device__ __forceinline__ void tma_load(uint32_t dst, const CUtensorMap* tm, int c0, int c1, uint32_t bar) {
    asm volatile(ELECT "cp.async.bulk.tensor.2d.shared::cluster.global.mbarrier::complete_tx::bytes [%0], [%1, {%3, %4}], [%2];\n}"
        :: "r"(dst), "l"(tm), "r"(bar), "r"(c0), "r"(c1) : "memory");
}
__device__ __forceinline__ void tma_load4(uint32_t dst, const CUtensorMap* tm, int row, int blk, uint32_t bar) {
    asm volatile(ELECT "cp.async.bulk.tensor.4d.shared::cluster.global.mbarrier::complete_tx::bytes [%0], [%1, {0, %3, %4, 0}], [%2];\n}"
        :: "r"(dst), "l"(tm), "r"(bar), "r"(row), "r"(blk) : "memory");
}
__device__ __forceinline__ void tma_store4(const CUtensorMap* tm, int row, int blk, uint32_t src) {
    asm volatile(ELECT "cp.async.bulk.tensor.4d.global.shared::cta.bulk_group [%0, {0, %2, %3, 0}], [%1];\n}" :: "l"(tm), "r"(src), "r"(row), "r"(blk) : "memory");
}
__device__ __forceinline__ void bulk_load(uint32_t dst, const void* src, uint32_t bytes, uint32_t bar) {
    asm volatile(ELECT "cp.async.bulk.shared::cluster.global.mbarrier::complete_tx::bytes [%0], [%1], %2, [%3];\n}" :: "r"(dst), "l"(src), "r"(bytes), "r"(bar) : "memory");
}
__device__ __forceinline__ void bulk_store(void* dst, uint32_t src, uint32_t bytes) {
    asm volatile(ELECT "cp.async.bulk.global.shared::cta.bulk_group [%0], [%1], %2;\n}" :: "l"(dst), "r"(src), "r"(bytes) : "memory");
}
__device__ __forceinline__ void bulk_reduce(void* dst, uint32_t src, uint32_t bytes) {
    asm volatile(ELECT "cp.reduce.async.bulk.global.shared::cta.bulk_group.add.f32 [%0], [%1], %2;\n}" :: "l"(dst), "r"(src), "r"(bytes) : "memory");
}
__device__ __forceinline__ void tma_prefetch(const CUtensorMap* tm, int c0, int c1) {
    asm volatile(ELECT "cp.async.bulk.prefetch.tensor.2d.L2.global [%0, {%1, %2}];\n}" :: "l"(tm), "r"(c0), "r"(c1) : "memory");
}
__device__ __forceinline__ void l2_prefetch(const void* p, uint32_t bytes) {
    asm volatile(ELECT "cp.async.bulk.prefetch.L2.global [%0], %1;\n}" :: "l"(p), "r"(bytes) : "memory");
}
__device__ __forceinline__ void bulk_wait_read() { asm volatile("cp.async.bulk.commit_group;\ncp.async.bulk.wait_group.read 0;" ::: "memory"); }
__device__ __forceinline__ void bulk_wait() { asm volatile("cp.async.bulk.commit_group;\ncp.async.bulk.wait_group 0;" ::: "memory"); }
__device__ __forceinline__ void tmap_prefetch(const CUtensorMap* tm) { asm volatile("prefetch.tensormap [%0];" :: "l"(tm) : "memory"); }
__device__ __forceinline__ void wg_fence() { asm volatile("wgmma.fence.sync.aligned;" ::: "memory"); }
__device__ __forceinline__ void wg_commit() { asm volatile("wgmma.commit_group.sync.aligned;" ::: "memory"); }
template<int N> __device__ __forceinline__ void wg_wait() { asm volatile("wgmma.wait_group.sync.aligned %0;" :: "n"(N) : "memory"); }
template<int N> __device__ __forceinline__ void acc_fence(float (&d)[N]) {
    #pragma unroll
    for (int i = 0; i < N; i++) asm volatile("" : "+f"(d[i]) :: "memory");
}
__device__ __forceinline__ uint32_t desc_lo(uint32_t addr, uint32_t lbo) { return (addr >> 4) | ((lbo >> 4) << 16); }
constexpr uint32_t H128 = 0x40000040u;
constexpr uint32_t H64 = 0x80000020u;
__device__ __forceinline__ void fence_async_smem() { asm volatile("fence.proxy.async.shared::cta;" ::: "memory"); }
__device__ __forceinline__ void bar_sync(int id, int n) { asm volatile("bar.sync %0, %1;" :: "r"(id), "r"(n) : "memory"); }
template<int R> __device__ __forceinline__ void reg_inc() { asm volatile("setmaxnreg.inc.sync.aligned.u32 %0;" :: "n"(R)); }
template<int R> __device__ __forceinline__ void reg_dec() { asm volatile("setmaxnreg.dec.sync.aligned.u32 %0;" :: "n"(R)); }

__device__ __forceinline__ void stsm4(uint32_t addr, uint32_t r0, uint32_t r1, uint32_t r2, uint32_t r3) {
    asm volatile("stmatrix.sync.aligned.m8n8.x4.shared.b16 [%0], {%1,%2,%3,%4};" :: "r"(addr), "r"(r0), "r"(r1), "r"(r2), "r"(r3) : "memory");
}
__device__ __forceinline__ void ldsm4(uint32_t* r, uint32_t addr) {
    asm volatile("ldmatrix.sync.aligned.m8n8.x4.shared.b16 {%0,%1,%2,%3}, [%4];" : "=r"(r[0]), "=r"(r[1]), "=r"(r[2]), "=r"(r[3]) : "r"(addr) : "memory");
}
__device__ __forceinline__ void ldsm4t(uint32_t* r, uint32_t addr) {
    asm volatile("ldmatrix.sync.aligned.m8n8.x4.trans.shared.b16 {%0,%1,%2,%3}, [%4];" : "=r"(r[0]), "=r"(r[1]), "=r"(r[2]), "=r"(r[3]) : "r"(addr) : "memory");
}
__device__ __forceinline__ void mma16816(float (&d)[4], uint32_t a0, uint32_t a1, uint32_t a2, uint32_t a3, uint32_t b0, uint32_t b1) {
    asm volatile("mma.sync.aligned.m16n8k16.row.col.f32.bf16.bf16.f32 {%0,%1,%2,%3}, {%4,%5,%6,%7}, {%8,%9}, {%0,%1,%2,%3};"
        : "+f"(d[0]), "+f"(d[1]), "+f"(d[2]), "+f"(d[3]) : "r"(a0), "r"(a1), "r"(a2), "r"(a3), "r"(b0), "r"(b1));
}
__device__ __forceinline__ uint32_t awake_zero() {
    uint32_t r;
    asm volatile("{\n.reg .f32 d<4>;\nmma.sync.aligned.m16n8k8.row.col.f32.bf16.bf16.f32 {d0,d1,d2,d3}, {%1,%1}, {%1}, {%2,%2,%2,%2};\nmov.b32 %0, d0;\n}" : "=r"(r) : "r"(0), "f"(0.f));
    return r;
}
__device__ __forceinline__ void mbar_wait_awake(uint32_t bar, uint32_t parity) {
    #pragma unroll 1
    for (int it = 0; it < POLL_MAX; it++) {
        uint32_t ok;
        asm volatile("{\n.reg .pred p;\nmbarrier.try_wait.parity.shared::cta.b64 p, [%1], %2;\nselp.u32 %0, 0, 1, p;\n}" : "=r"(ok) : "r"(bar), "r"(parity) : "memory");
        if (__all_sync(0xffffffffu, ok == 0)) break;
        it += awake_zero();
    }
}
__device__ __forceinline__ uint4 lds128(uint32_t a) { uint4 v; asm volatile("ld.shared.v4.b32 {%0,%1,%2,%3}, [%4];" : "=r"(v.x), "=r"(v.y), "=r"(v.z), "=r"(v.w) : "r"(a) : "memory"); return v; }
__device__ __forceinline__ uint32_t lds32(uint32_t a) { uint32_t v; asm volatile("ld.shared.b32 %0, [%1];" : "=r"(v) : "r"(a) : "memory"); return v; }
__device__ __forceinline__ uint2 lds64(uint32_t a) { uint2 v; asm volatile("ld.shared.v2.b32 {%0,%1}, [%2];" : "=r"(v.x), "=r"(v.y) : "r"(a) : "memory"); return v; }
__device__ __forceinline__ float ldsf(uint32_t a) { float v; asm volatile("ld.shared.f32 %0, [%1];" : "=f"(v) : "r"(a) : "memory"); return v; }
__device__ __forceinline__ void sts128(uint32_t a, uint4 v) { asm volatile("st.shared.v4.b32 [%0], {%1,%2,%3,%4};" :: "r"(a), "r"(v.x), "r"(v.y), "r"(v.z), "r"(v.w) : "memory"); }
__device__ __forceinline__ void sts64(uint32_t a, uint32_t x, uint32_t y) { asm volatile("st.shared.v2.b32 [%0], {%1,%2};" :: "r"(a), "r"(x), "r"(y) : "memory"); }
__device__ __forceinline__ void sts32(uint32_t a, uint32_t x) { asm volatile("st.shared.b32 [%0], %1;" :: "r"(a), "r"(x) : "memory"); }
__device__ __forceinline__ void stsf(uint32_t a, float x) { asm volatile("st.shared.f32 [%0], %1;" :: "r"(a), "f"(x) : "memory"); }
__device__ __forceinline__ float u2f(uint32_t v) { return __uint_as_float(v); }
__device__ __forceinline__ uint32_t f2u(float v) { return __float_as_uint(v); }

__device__ __forceinline__ uint32_t ldg32(const void* p) { uint32_t v; asm volatile("ld.global.nc.b32 %0, [%1];" : "=r"(v) : "l"(p)); return v; }
__device__ __forceinline__ void stg128(void* p, uint4 v) { asm volatile("st.global.v4.b32 [%0], {%1,%2,%3,%4};" :: "l"(p), "r"(v.x), "r"(v.y), "r"(v.z), "r"(v.w) : "memory"); }
__device__ __forceinline__ void stg_zero(void* p) { stg128(p, make_uint4(0, 0, 0, 0)); }
__device__ __forceinline__ void fence_gpu() { asm volatile("fence.release.gpu;" ::: "memory"); }
__device__ __forceinline__ void st_ll(uint4* p, uint32_t x, uint32_t y, uint32_t z, uint32_t w) {
    asm volatile("st.relaxed.gpu.global.v4.b32 [%0], {%1,%2,%3,%4};" :: "l"(p), "r"(x), "r"(y), "r"(z), "r"(w) : "memory");
}
__device__ __forceinline__ uint4 ld_ll(const uint4* p) {
    uint4 v;
    asm volatile("ld.relaxed.gpu.global.v4.b32 {%0,%1,%2,%3}, [%4];" : "=r"(v.x), "=r"(v.y), "=r"(v.z), "=r"(v.w) : "l"(p) : "memory");
    return v;
}
template<uint32_t LUT> __device__ __forceinline__ uint32_t lop3(uint32_t a, uint32_t b, uint32_t c) { uint32_t d; asm("lop3.b32 %0, %1, %2, %3, %4;" : "=r"(d) : "r"(a), "r"(b), "r"(c), "n"(LUT)); return d; }
__device__ __forceinline__ uint32_t tag_bad(uint32_t bad, uint32_t w, uint32_t tag) { return lop3<0xF6>(bad, w, tag); }
__device__ __forceinline__ void st_ll4(uint4* p, float a, float b, float c, float d, uint32_t tag) { st_ll(p, f2u(a), f2u(b), f2u(c), lop3<0xD8>(f2u(d), tag, 3u)); }
__device__ __forceinline__ unsigned ld_rlx(const void* p) { unsigned v; asm volatile("ld.relaxed.gpu.global.u32 %0, [%1];" : "=r"(v) : "l"(p) : "memory"); return v; }
__device__ __forceinline__ void st_flag(uint4* p, uint32_t tag, uint32_t v, int lane) { if (lane < 2) st_ll(p + lane, tag, v, tag, v); }
__device__ __forceinline__ uint2 ld_flag(const uint4* p) { uint2 v; asm volatile("ld.relaxed.gpu.global.v2.b32 {%0,%1}, [%2];" : "=r"(v.x), "=r"(v.y) : "l"(p) : "memory"); return v; }
__device__ __forceinline__ uint32_t poll_flags(const uint4* f, uint32_t tag) {
    uint2 v = make_uint2(0, 0);
    #pragma unroll 1
    for (int it = 0; it < POLL_MAX; it++) {
        if (v.x != tag) v = ld_flag(f);
        if (__all_sync(0xffffffffu, v.x == tag)) break;
    }
    return v.y;
}
template<int Z> __device__ __forceinline__ uint32_t ll_bad(uint32_t bad, const uint4& v, uint32_t tag) {
    bad = tag_bad(bad, v.w, tag);
    return Z && lop3<0x80>(v.x, v.y, v.z) == ~0u ? 1u : bad;
}
template<int N, int Z, uint32_t M = ~0u, int AW = 0> __device__ __forceinline__ void poll_words(uint4 (&v)[N], const uint4* p, int stride, uint32_t tag) {
    #pragma unroll 1
    for (int it = 0; it < POLL_MAX; it++) {
        uint32_t bad = 0;
        #pragma unroll
        for (int i = 0; i < N; i++) v[i] = ld_ll(p + i * stride);
        #pragma unroll
        for (int i = 0; i < N; i++) bad = ll_bad<Z>(bad, v[i], tag);
        if (__all_sync(0xffffffffu, !(bad & M))) break;
        if (AW) it += awake_zero();
    }
}
constexpr uint32_t ONE2 = 0x3F803F80u;
__device__ __forceinline__ uint32_t pack2(float lo, float hi) { uint32_t d; asm("cvt.rn.bf16x2.f32 %0, %1, %2;" : "=r"(d) : "f"(hi), "f"(lo)); return d; }
__device__ __forceinline__ float bf_lo(uint32_t v) { return u2f(v << 16); }
__device__ __forceinline__ float bf_hi(uint32_t v) { return u2f(v & 0xffff0000u); }
__device__ __forceinline__ float rbf(float x) { return bf_lo(pack2(x, 0.f)); }
__device__ __forceinline__ uint32_t hsub2(uint32_t a, uint32_t b) { uint32_t d; asm("sub.rn.bf16x2 %0, %1, %2;" : "=r"(d) : "r"(a), "r"(b)); return d; }
__device__ __forceinline__ uint32_t hadd2(uint32_t a, uint32_t b) { uint32_t d; asm("add.rn.bf16x2 %0, %1, %2;" : "=r"(d) : "r"(a), "r"(b)); return d; }
__device__ __forceinline__ uint32_t hmul2(uint32_t a, uint32_t b) { uint32_t d; asm("mul.rn.bf16x2 %0, %1, %2;" : "=r"(d) : "r"(a), "r"(b)); return d; }
__device__ __forceinline__ uint32_t hfma2(uint32_t a, uint32_t b, uint32_t c) { uint32_t d; asm("fma.rn.bf16x2 %0, %1, %2, %3;" : "=r"(d) : "r"(a), "r"(b), "r"(c)); return d; }
__device__ __forceinline__ uint32_t hmax2(uint32_t a, uint32_t b) { uint32_t d; asm("max.bf16x2 %0, %1, %2;" : "=r"(d) : "r"(a), "r"(b)); return d; }
__device__ __forceinline__ uint32_t hmin2(uint32_t a, uint32_t b) { uint32_t d; asm("min.bf16x2 %0, %1, %2;" : "=r"(d) : "r"(a), "r"(b)); return d; }
__device__ __forceinline__ float ex2(float x) { float y; asm("ex2.approx.ftz.f32 %0, %1;" : "=f"(y) : "f"(x)); return y; }
__device__ __forceinline__ float rcp(float x) { float y; asm("rcp.approx.ftz.f32 %0, %1;" : "=f"(y) : "f"(x)); return y; }
__device__ __forceinline__ float shfl_x(float v, int m) { return __shfl_xor_sync(0xffffffffu, v, m); }
__device__ __forceinline__ uint32_t hdiv2(uint32_t d, uint32_t rh, uint32_t rl) { return hfma2(d, rh, hmul2(d, rl)); }
__device__ __forceinline__ void split_rcp(float r, uint32_t& rh, uint32_t& rl) { rh = pack2(r, r); const float l = r - bf_lo(rh); rl = pack2(l, l); }
__device__ __forceinline__ uint32_t lnmod(uint32_t x, uint32_t m, uint32_t rh, uint32_t rl, uint32_t a, uint32_t s) { return hadd2(hmul2(hdiv2(hsub2(x, m), rh, rl), a), s); }
__device__ __forceinline__ void ln_final(float s1, float s2, uint32_t& m2, float& rinv) {
    const float mean = s1 * (1.0f / 1024.0f), var = fmaf(-mean, mean, s2 * (1.0f / 1024.0f));
    m2 = pack2(mean, mean);
    float sd;
    asm("sqrt.approx.ftz.f32 %0, %1;" : "=f"(sd) : "f"(rbf(rbf(fmaxf(var, 0.f)) + 1e-5f)));
    rinv = rcp(rbf(sd));
}
__device__ __forceinline__ float sigmoid_f(float x) { return rcp(1.0f + ex2(-1.4426950408889634f * x)); }
__device__ __forceinline__ uint32_t silu2(uint32_t v) { return pack2(bf_lo(v) * sigmoid_f(bf_lo(v)), bf_hi(v) * sigmoid_f(bf_hi(v))); }
__device__ __forceinline__ uint32_t f2key(float f) { uint32_t u = f2u(f); return (u & 0x80000000u) ? ~u : (u | 0x80000000u); }
__device__ __forceinline__ float key2f(uint32_t k) { return u2f((k & 0x80000000u) ? k ^ 0x80000000u : ~k); }
template<int N> __device__ __forceinline__ void top2(uint32_t (&k)[N], uint32_t& b0, uint32_t& b1) {
    uint32_t m = k[0];
    #pragma unroll
    for (int i = 1; i < N; i++) m = max(m, k[i]);
    b0 = __reduce_max_sync(0xffffffffu, m);
    m = 0;
    #pragma unroll
    for (int i = 0; i < N; i++) m = max(m, k[i] == b0 ? 0u : k[i]);
    b1 = __reduce_max_sync(0xffffffffu, m);
}
template<class T> __device__ __forceinline__ T sel4(int c, T a0, T a1, T a2, T a3) { return (c & 2) ? ((c & 1) ? a3 : a2) : ((c & 1) ? a1 : a0); }

__device__ __forceinline__ void fm_max(const float (&a)[16], uint32_t* p, uint32_t* mm) {
    #pragma unroll
    for (int i = 0; i < 8; i++) p[i] = pack2(a[2 * i], a[2 * i + 1]);
    #pragma unroll
    for (int h = 0; h < 2; h++) {
        const uint32_t mx = hmax2(hmax2(p[h], p[2 + h]), hmax2(p[4 + h], p[6 + h]));
        const uint32_t mn = hmin2(hmin2(p[h], p[2 + h]), hmin2(p[4 + h], p[6 + h])) ^ 0x80008000u;
        mm[h] = hmax2(__byte_perm(mx, mn, 0x5410), __byte_perm(mx, mn, 0x7632));
    }
    #pragma unroll
    for (int d = 1; d <= 2; d++) { mm[0] = hmax2(mm[0], __shfl_xor_sync(0xffffffffu, mm[0], d)); mm[1] = hmax2(mm[1], __shfl_xor_sync(0xffffffffu, mm[1], d)); }
}
constexpr float LOG2E = 1.4426950408889634f;
__device__ __forceinline__ void fm_pos(const uint32_t* p, const uint32_t* mm, float (&e)[32]) {
    #pragma unroll
    for (int h = 0; h < 2; h++) {
        const float cp = -bf_lo(mm[h]) * LOG2E;
        #pragma unroll
        for (int j = 0; j < 4; j++) {
            const float f0 = bf_lo(p[2 * j + h]), f1 = bf_hi(p[2 * j + h]);
            e[8 * h + 2 * j] = ex2(fmaf(f0, LOG2E, cp)); e[8 * h + 2 * j + 1] = ex2(fmaf(f1, LOG2E, cp));
            e[16 + 8 * h + 2 * j] = f0; e[16 + 8 * h + 2 * j + 1] = f1;
        }
    }
}
__device__ __forceinline__ void fm_neg(const uint32_t* mm, float nl, float (&e)[32]) {
    #pragma unroll
    for (int i = 16; i < 32; i++) e[i] = ex2(fmaf(e[i], -LOG2E, bf_hi(mm[(i >> 3) & 1]) * (i < 16 + NFREE ? -LOG2E : nl)));
}
__device__ __forceinline__ void fm_norm(const float (&e)[32], uint32_t* ph) {
    float s[4];
    #pragma unroll
    for (int k = 0; k < 4; k++) s[k] = ((e[8 * k] + e[8 * k + 1]) + (e[8 * k + 2] + e[8 * k + 3])) + ((e[8 * k + 4] + e[8 * k + 5]) + (e[8 * k + 6] + e[8 * k + 7]));
    #pragma unroll
    for (int k = 0; k < 4; k++) s[k] += shfl_x(s[k], 1);
    #pragma unroll
    for (int k = 0; k < 4; k++) s[k] = rcp(s[k] + shfl_x(s[k], 2));
    #pragma unroll
    for (int k = 0; k < 4; k++)
        #pragma unroll
        for (int j = 0; j < 4; j++) ph[8 * (k >> 1) + 2 * j + (k & 1)] = pack2(e[8 * k + 2 * j] * s[k], e[8 * k + 2 * j + 1] * s[k]);
}
template<class T> __device__ __forceinline__ T* pin_ptr(T* p) { asm volatile("" : "+l"(p) :: "memory"); return p; }
template<int N> __device__ __forceinline__ void pin(uint32_t* d) {
    #pragma unroll
    for (int i = 0; i < N; i++) asm volatile("" : "+r"(d[i]) :: "memory");
}

template<uint32_t BO, uint32_t BH> __device__ __forceinline__ void mma192_rs(float (&d)[96], const uint32_t* a, uint32_t blo) {
  asm volatile("{\n.reg .pred p;\n.reg .b32 ta, tb;\n.reg .b64 da, db;\nadd.u32 tb, %100, %101;\nmov.b64 db, {tb, %102};\nsetp.ne.b32 p, 1, 0;\n"
    "wgmma.mma_async.sync.aligned.m64n192k16.f32.bf16.bf16 {%0, %1, %2, %3, %4, %5, %6, %7, %8, %9, %10, %11, %12, %13, %14, %15, %16, %17, %18, %19, %20, %21, %22, %23, %24, %25, %26, %27, %28, %29, %30, %31, %32, %33, %34, %35, %36, %37, %38, %39, %40, %41, %42, %43, %44, %45, %46, %47, %48, %49, %50, %51, %52, %53, %54, %55, %56, %57, %58, %59, %60, %61, %62, %63, %64, %65, %66, %67, %68, %69, %70, %71, %72, %73, %74, %75, %76, %77, %78, %79, %80, %81, %82, %83, %84, %85, %86, %87, %88, %89, %90, %91, %92, %93, %94, %95}, {%96,%97,%98,%99}, db, p, 1, 1, 1;\n}\n"
    : "+f"(d[0]), "+f"(d[1]), "+f"(d[2]), "+f"(d[3]), "+f"(d[4]), "+f"(d[5]), "+f"(d[6]), "+f"(d[7]), "+f"(d[8]), "+f"(d[9]), "+f"(d[10]), "+f"(d[11]), "+f"(d[12]), "+f"(d[13]), "+f"(d[14]), "+f"(d[15]), "+f"(d[16]), "+f"(d[17]), "+f"(d[18]), "+f"(d[19]), "+f"(d[20]), "+f"(d[21]), "+f"(d[22]), "+f"(d[23]), "+f"(d[24]), "+f"(d[25]), "+f"(d[26]), "+f"(d[27]), "+f"(d[28]), "+f"(d[29]), "+f"(d[30]), "+f"(d[31]), "+f"(d[32]), "+f"(d[33]), "+f"(d[34]), "+f"(d[35]), "+f"(d[36]), "+f"(d[37]), "+f"(d[38]), "+f"(d[39]), "+f"(d[40]), "+f"(d[41]), "+f"(d[42]), "+f"(d[43]), "+f"(d[44]), "+f"(d[45]), "+f"(d[46]), "+f"(d[47]), "+f"(d[48]), "+f"(d[49]), "+f"(d[50]), "+f"(d[51]), "+f"(d[52]), "+f"(d[53]), "+f"(d[54]), "+f"(d[55]), "+f"(d[56]), "+f"(d[57]), "+f"(d[58]), "+f"(d[59]), "+f"(d[60]), "+f"(d[61]), "+f"(d[62]), "+f"(d[63]), "+f"(d[64]), "+f"(d[65]), "+f"(d[66]), "+f"(d[67]), "+f"(d[68]), "+f"(d[69]), "+f"(d[70]), "+f"(d[71]), "+f"(d[72]), "+f"(d[73]), "+f"(d[74]), "+f"(d[75]), "+f"(d[76]), "+f"(d[77]), "+f"(d[78]), "+f"(d[79]), "+f"(d[80]), "+f"(d[81]), "+f"(d[82]), "+f"(d[83]), "+f"(d[84]), "+f"(d[85]), "+f"(d[86]), "+f"(d[87]), "+f"(d[88]), "+f"(d[89]), "+f"(d[90]), "+f"(d[91]), "+f"(d[92]), "+f"(d[93]), "+f"(d[94]), "+f"(d[95])
    : "r"(a[0]), "r"(a[1]), "r"(a[2]), "r"(a[3]), "r"(blo), "n"(BO), "n"(BH));
}
template<uint32_t BO, uint32_t BH> __device__ __forceinline__ void mma192_rsp(float (&d)[96], const uint32_t* a, uint32_t blo, int sc) {
  asm volatile("{\n.reg .pred p;\n.reg .b32 ta, tb;\n.reg .b64 da, db;\nadd.u32 tb, %100, %101;\nmov.b64 db, {tb, %102};\nsetp.ne.b32 p, %103, 0;\n"
    "wgmma.mma_async.sync.aligned.m64n192k16.f32.bf16.bf16 {%0, %1, %2, %3, %4, %5, %6, %7, %8, %9, %10, %11, %12, %13, %14, %15, %16, %17, %18, %19, %20, %21, %22, %23, %24, %25, %26, %27, %28, %29, %30, %31, %32, %33, %34, %35, %36, %37, %38, %39, %40, %41, %42, %43, %44, %45, %46, %47, %48, %49, %50, %51, %52, %53, %54, %55, %56, %57, %58, %59, %60, %61, %62, %63, %64, %65, %66, %67, %68, %69, %70, %71, %72, %73, %74, %75, %76, %77, %78, %79, %80, %81, %82, %83, %84, %85, %86, %87, %88, %89, %90, %91, %92, %93, %94, %95}, {%96,%97,%98,%99}, db, p, 1, 1, 1;\n}\n"
    : "+f"(d[0]), "+f"(d[1]), "+f"(d[2]), "+f"(d[3]), "+f"(d[4]), "+f"(d[5]), "+f"(d[6]), "+f"(d[7]), "+f"(d[8]), "+f"(d[9]), "+f"(d[10]), "+f"(d[11]), "+f"(d[12]), "+f"(d[13]), "+f"(d[14]), "+f"(d[15]), "+f"(d[16]), "+f"(d[17]), "+f"(d[18]), "+f"(d[19]), "+f"(d[20]), "+f"(d[21]), "+f"(d[22]), "+f"(d[23]), "+f"(d[24]), "+f"(d[25]), "+f"(d[26]), "+f"(d[27]), "+f"(d[28]), "+f"(d[29]), "+f"(d[30]), "+f"(d[31]), "+f"(d[32]), "+f"(d[33]), "+f"(d[34]), "+f"(d[35]), "+f"(d[36]), "+f"(d[37]), "+f"(d[38]), "+f"(d[39]), "+f"(d[40]), "+f"(d[41]), "+f"(d[42]), "+f"(d[43]), "+f"(d[44]), "+f"(d[45]), "+f"(d[46]), "+f"(d[47]), "+f"(d[48]), "+f"(d[49]), "+f"(d[50]), "+f"(d[51]), "+f"(d[52]), "+f"(d[53]), "+f"(d[54]), "+f"(d[55]), "+f"(d[56]), "+f"(d[57]), "+f"(d[58]), "+f"(d[59]), "+f"(d[60]), "+f"(d[61]), "+f"(d[62]), "+f"(d[63]), "+f"(d[64]), "+f"(d[65]), "+f"(d[66]), "+f"(d[67]), "+f"(d[68]), "+f"(d[69]), "+f"(d[70]), "+f"(d[71]), "+f"(d[72]), "+f"(d[73]), "+f"(d[74]), "+f"(d[75]), "+f"(d[76]), "+f"(d[77]), "+f"(d[78]), "+f"(d[79]), "+f"(d[80]), "+f"(d[81]), "+f"(d[82]), "+f"(d[83]), "+f"(d[84]), "+f"(d[85]), "+f"(d[86]), "+f"(d[87]), "+f"(d[88]), "+f"(d[89]), "+f"(d[90]), "+f"(d[91]), "+f"(d[92]), "+f"(d[93]), "+f"(d[94]), "+f"(d[95])
    : "r"(a[0]), "r"(a[1]), "r"(a[2]), "r"(a[3]), "r"(blo), "n"(BO), "n"(BH), "r"(sc));
}
template<uint32_t BO, uint32_t BH> __device__ __forceinline__ void mma32_rs(float (&d)[16], const uint32_t* a, uint32_t blo) {
  asm volatile("{\n.reg .pred p;\n.reg .b32 ta, tb;\n.reg .b64 da, db;\nadd.u32 tb, %20, %21;\nmov.b64 db, {tb, %22};\nsetp.ne.b32 p, 1, 0;\n"
    "wgmma.mma_async.sync.aligned.m64n32k16.f32.bf16.bf16 {%0, %1, %2, %3, %4, %5, %6, %7, %8, %9, %10, %11, %12, %13, %14, %15}, {%16,%17,%18,%19}, db, p, 1, 1, 1;\n}\n"
    : "+f"(d[0]), "+f"(d[1]), "+f"(d[2]), "+f"(d[3]), "+f"(d[4]), "+f"(d[5]), "+f"(d[6]), "+f"(d[7]), "+f"(d[8]), "+f"(d[9]), "+f"(d[10]), "+f"(d[11]), "+f"(d[12]), "+f"(d[13]), "+f"(d[14]), "+f"(d[15])
    : "r"(a[0]), "r"(a[1]), "r"(a[2]), "r"(a[3]), "r"(blo), "n"(BO), "n"(BH));
}
template<uint32_t BO, uint32_t BH> __device__ __forceinline__ void mma32_rs0(float (&d)[16], const uint32_t* a, uint32_t blo) {
  asm volatile("{\n.reg .pred p;\n.reg .b32 ta, tb;\n.reg .b64 da, db;\nadd.u32 tb, %20, %21;\nmov.b64 db, {tb, %22};\nsetp.ne.b32 p, 0, 0;\n"
    "wgmma.mma_async.sync.aligned.m64n32k16.f32.bf16.bf16 {%0, %1, %2, %3, %4, %5, %6, %7, %8, %9, %10, %11, %12, %13, %14, %15}, {%16,%17,%18,%19}, db, p, 1, 1, 1;\n}\n"
    : "=f"(d[0]), "=f"(d[1]), "=f"(d[2]), "=f"(d[3]), "=f"(d[4]), "=f"(d[5]), "=f"(d[6]), "=f"(d[7]), "=f"(d[8]), "=f"(d[9]), "=f"(d[10]), "=f"(d[11]), "=f"(d[12]), "=f"(d[13]), "=f"(d[14]), "=f"(d[15])
    : "r"(a[0]), "r"(a[1]), "r"(a[2]), "r"(a[3]), "r"(blo), "n"(BO), "n"(BH));
}
template<uint32_t BO, uint32_t BH> __device__ __forceinline__ void mma40_rs(float (&d)[20], const uint32_t* a, uint32_t blo) {
  asm volatile("{\n.reg .pred p;\n.reg .b32 ta, tb;\n.reg .b64 da, db;\nadd.u32 tb, %24, %25;\nmov.b64 db, {tb, %26};\nsetp.ne.b32 p, 1, 0;\n"
    "wgmma.mma_async.sync.aligned.m64n40k16.f32.bf16.bf16 {%0, %1, %2, %3, %4, %5, %6, %7, %8, %9, %10, %11, %12, %13, %14, %15, %16, %17, %18, %19}, {%20,%21,%22,%23}, db, p, 1, 1, 1;\n}\n"
    : "+f"(d[0]), "+f"(d[1]), "+f"(d[2]), "+f"(d[3]), "+f"(d[4]), "+f"(d[5]), "+f"(d[6]), "+f"(d[7]), "+f"(d[8]), "+f"(d[9]), "+f"(d[10]), "+f"(d[11]), "+f"(d[12]), "+f"(d[13]), "+f"(d[14]), "+f"(d[15]), "+f"(d[16]), "+f"(d[17]), "+f"(d[18]), "+f"(d[19])
    : "r"(a[0]), "r"(a[1]), "r"(a[2]), "r"(a[3]), "r"(blo), "n"(BO), "n"(BH));
}
template<uint32_t BO, uint32_t BH> __device__ __forceinline__ void mma40_rs0(float (&d)[20], const uint32_t* a, uint32_t blo) {
  asm volatile("{\n.reg .pred p;\n.reg .b32 ta, tb;\n.reg .b64 da, db;\nadd.u32 tb, %24, %25;\nmov.b64 db, {tb, %26};\nsetp.ne.b32 p, 0, 0;\n"
    "wgmma.mma_async.sync.aligned.m64n40k16.f32.bf16.bf16 {%0, %1, %2, %3, %4, %5, %6, %7, %8, %9, %10, %11, %12, %13, %14, %15, %16, %17, %18, %19}, {%20,%21,%22,%23}, db, p, 1, 1, 1;\n}\n"
    : "=f"(d[0]), "=f"(d[1]), "=f"(d[2]), "=f"(d[3]), "=f"(d[4]), "=f"(d[5]), "=f"(d[6]), "=f"(d[7]), "=f"(d[8]), "=f"(d[9]), "=f"(d[10]), "=f"(d[11]), "=f"(d[12]), "=f"(d[13]), "=f"(d[14]), "=f"(d[15]), "=f"(d[16]), "=f"(d[17]), "=f"(d[18]), "=f"(d[19])
    : "r"(a[0]), "r"(a[1]), "r"(a[2]), "r"(a[3]), "r"(blo), "n"(BO), "n"(BH));
}
template<uint32_t AO, uint32_t AH, uint32_t BO, uint32_t BH> __device__ __forceinline__ void mma40_tt(float (&d)[20], uint32_t alo, uint32_t blo) {
  asm volatile("{\n.reg .pred p;\n.reg .b32 ta, tb;\n.reg .b64 da, db;\nadd.u32 ta, %20, %21;\nmov.b64 da, {ta, %22};\nadd.u32 tb, %23, %24;\nmov.b64 db, {tb, %25};\nsetp.ne.b32 p, 1, 0;\n"
    "wgmma.mma_async.sync.aligned.m64n40k16.f32.bf16.bf16 {%0, %1, %2, %3, %4, %5, %6, %7, %8, %9, %10, %11, %12, %13, %14, %15, %16, %17, %18, %19}, da, db, p, 1, 1, 1, 1;\n}\n"
    : "+f"(d[0]), "+f"(d[1]), "+f"(d[2]), "+f"(d[3]), "+f"(d[4]), "+f"(d[5]), "+f"(d[6]), "+f"(d[7]), "+f"(d[8]), "+f"(d[9]), "+f"(d[10]), "+f"(d[11]), "+f"(d[12]), "+f"(d[13]), "+f"(d[14]), "+f"(d[15]), "+f"(d[16]), "+f"(d[17]), "+f"(d[18]), "+f"(d[19])
    : "r"(alo), "n"(AO), "n"(AH), "r"(blo), "n"(BO), "n"(BH));
}
template<uint32_t AO, uint32_t AH, uint32_t BO, uint32_t BH> __device__ __forceinline__ void mma40_tt0(float (&d)[20], uint32_t alo, uint32_t blo) {
  asm volatile("{\n.reg .pred p;\n.reg .b32 ta, tb;\n.reg .b64 da, db;\nadd.u32 ta, %20, %21;\nmov.b64 da, {ta, %22};\nadd.u32 tb, %23, %24;\nmov.b64 db, {tb, %25};\nsetp.ne.b32 p, 0, 0;\n"
    "wgmma.mma_async.sync.aligned.m64n40k16.f32.bf16.bf16 {%0, %1, %2, %3, %4, %5, %6, %7, %8, %9, %10, %11, %12, %13, %14, %15, %16, %17, %18, %19}, da, db, p, 1, 1, 1, 1;\n}\n"
    : "=f"(d[0]), "=f"(d[1]), "=f"(d[2]), "=f"(d[3]), "=f"(d[4]), "=f"(d[5]), "=f"(d[6]), "=f"(d[7]), "=f"(d[8]), "=f"(d[9]), "=f"(d[10]), "=f"(d[11]), "=f"(d[12]), "=f"(d[13]), "=f"(d[14]), "=f"(d[15]), "=f"(d[16]), "=f"(d[17]), "=f"(d[18]), "=f"(d[19])
    : "r"(alo), "n"(AO), "n"(AH), "r"(blo), "n"(BO), "n"(BH));
}
template<uint32_t AO, uint32_t AH, uint32_t BO, uint32_t BH> __device__ __forceinline__ void mma8_tn(float (&d)[4], uint32_t alo, uint32_t blo) {
  asm volatile("{\n.reg .pred p;\n.reg .b32 ta, tb;\n.reg .b64 da, db;\nadd.u32 ta, %4, %5;\nmov.b64 da, {ta, %6};\nadd.u32 tb, %7, %8;\nmov.b64 db, {tb, %9};\nsetp.ne.b32 p, 1, 0;\n"
    "wgmma.mma_async.sync.aligned.m64n8k16.f32.bf16.bf16 {%0, %1, %2, %3}, da, db, p, 1, 1, 1, 0;\n}\n"
    : "+f"(d[0]), "+f"(d[1]), "+f"(d[2]), "+f"(d[3])
    : "r"(alo), "n"(AO), "n"(AH), "r"(blo), "n"(BO), "n"(BH));
}
template<uint32_t AO, uint32_t AH, uint32_t BO, uint32_t BH> __device__ __forceinline__ void mma8_tn0(float (&d)[4], uint32_t alo, uint32_t blo) {
  asm volatile("{\n.reg .pred p;\n.reg .b32 ta, tb;\n.reg .b64 da, db;\nadd.u32 ta, %4, %5;\nmov.b64 da, {ta, %6};\nadd.u32 tb, %7, %8;\nmov.b64 db, {tb, %9};\nsetp.ne.b32 p, 0, 0;\n"
    "wgmma.mma_async.sync.aligned.m64n8k16.f32.bf16.bf16 {%0, %1, %2, %3}, da, db, p, 1, 1, 1, 0;\n}\n"
    : "=f"(d[0]), "=f"(d[1]), "=f"(d[2]), "=f"(d[3])
    : "r"(alo), "n"(AO), "n"(AH), "r"(blo), "n"(BO), "n"(BH));
}
template<uint32_t AO, uint32_t AH, uint32_t BO, uint32_t BH> __device__ __forceinline__ void mma128_ss(float (&d)[64], uint32_t alo, uint32_t blo) {
  asm volatile("{\n.reg .pred p;\n.reg .b32 ta, tb;\n.reg .b64 da, db;\nadd.u32 ta, %64, %65;\nmov.b64 da, {ta, %66};\nadd.u32 tb, %67, %68;\nmov.b64 db, {tb, %69};\nsetp.ne.b32 p, 1, 0;\n"
    "wgmma.mma_async.sync.aligned.m64n128k16.f32.bf16.bf16 {%0, %1, %2, %3, %4, %5, %6, %7, %8, %9, %10, %11, %12, %13, %14, %15, %16, %17, %18, %19, %20, %21, %22, %23, %24, %25, %26, %27, %28, %29, %30, %31, %32, %33, %34, %35, %36, %37, %38, %39, %40, %41, %42, %43, %44, %45, %46, %47, %48, %49, %50, %51, %52, %53, %54, %55, %56, %57, %58, %59, %60, %61, %62, %63}, da, db, p, 1, 1, 0, 1;\n}\n"
    : "+f"(d[0]), "+f"(d[1]), "+f"(d[2]), "+f"(d[3]), "+f"(d[4]), "+f"(d[5]), "+f"(d[6]), "+f"(d[7]), "+f"(d[8]), "+f"(d[9]), "+f"(d[10]), "+f"(d[11]), "+f"(d[12]), "+f"(d[13]), "+f"(d[14]), "+f"(d[15]), "+f"(d[16]), "+f"(d[17]), "+f"(d[18]), "+f"(d[19]), "+f"(d[20]), "+f"(d[21]), "+f"(d[22]), "+f"(d[23]), "+f"(d[24]), "+f"(d[25]), "+f"(d[26]), "+f"(d[27]), "+f"(d[28]), "+f"(d[29]), "+f"(d[30]), "+f"(d[31]), "+f"(d[32]), "+f"(d[33]), "+f"(d[34]), "+f"(d[35]), "+f"(d[36]), "+f"(d[37]), "+f"(d[38]), "+f"(d[39]), "+f"(d[40]), "+f"(d[41]), "+f"(d[42]), "+f"(d[43]), "+f"(d[44]), "+f"(d[45]), "+f"(d[46]), "+f"(d[47]), "+f"(d[48]), "+f"(d[49]), "+f"(d[50]), "+f"(d[51]), "+f"(d[52]), "+f"(d[53]), "+f"(d[54]), "+f"(d[55]), "+f"(d[56]), "+f"(d[57]), "+f"(d[58]), "+f"(d[59]), "+f"(d[60]), "+f"(d[61]), "+f"(d[62]), "+f"(d[63])
    : "r"(alo), "n"(AO), "n"(AH), "r"(blo), "n"(BO), "n"(BH));
}
template<uint32_t AO, uint32_t AH, uint32_t BO, uint32_t BH> __device__ __forceinline__ void mma128_ss0(float (&d)[64], uint32_t alo, uint32_t blo) {
  asm volatile("{\n.reg .pred p;\n.reg .b32 ta, tb;\n.reg .b64 da, db;\nadd.u32 ta, %64, %65;\nmov.b64 da, {ta, %66};\nadd.u32 tb, %67, %68;\nmov.b64 db, {tb, %69};\nsetp.ne.b32 p, 0, 0;\n"
    "wgmma.mma_async.sync.aligned.m64n128k16.f32.bf16.bf16 {%0, %1, %2, %3, %4, %5, %6, %7, %8, %9, %10, %11, %12, %13, %14, %15, %16, %17, %18, %19, %20, %21, %22, %23, %24, %25, %26, %27, %28, %29, %30, %31, %32, %33, %34, %35, %36, %37, %38, %39, %40, %41, %42, %43, %44, %45, %46, %47, %48, %49, %50, %51, %52, %53, %54, %55, %56, %57, %58, %59, %60, %61, %62, %63}, da, db, p, 1, 1, 0, 1;\n}\n"
    : "=f"(d[0]), "=f"(d[1]), "=f"(d[2]), "=f"(d[3]), "=f"(d[4]), "=f"(d[5]), "=f"(d[6]), "=f"(d[7]), "=f"(d[8]), "=f"(d[9]), "=f"(d[10]), "=f"(d[11]), "=f"(d[12]), "=f"(d[13]), "=f"(d[14]), "=f"(d[15]), "=f"(d[16]), "=f"(d[17]), "=f"(d[18]), "=f"(d[19]), "=f"(d[20]), "=f"(d[21]), "=f"(d[22]), "=f"(d[23]), "=f"(d[24]), "=f"(d[25]), "=f"(d[26]), "=f"(d[27]), "=f"(d[28]), "=f"(d[29]), "=f"(d[30]), "=f"(d[31]), "=f"(d[32]), "=f"(d[33]), "=f"(d[34]), "=f"(d[35]), "=f"(d[36]), "=f"(d[37]), "=f"(d[38]), "=f"(d[39]), "=f"(d[40]), "=f"(d[41]), "=f"(d[42]), "=f"(d[43]), "=f"(d[44]), "=f"(d[45]), "=f"(d[46]), "=f"(d[47]), "=f"(d[48]), "=f"(d[49]), "=f"(d[50]), "=f"(d[51]), "=f"(d[52]), "=f"(d[53]), "=f"(d[54]), "=f"(d[55]), "=f"(d[56]), "=f"(d[57]), "=f"(d[58]), "=f"(d[59]), "=f"(d[60]), "=f"(d[61]), "=f"(d[62]), "=f"(d[63])
    : "r"(alo), "n"(AO), "n"(AH), "r"(blo), "n"(BO), "n"(BH));
}
template<uint32_t AO, uint32_t AH, uint32_t BO, uint32_t BH> __device__ __forceinline__ void mma128_ssp(float (&d)[64], uint32_t alo, uint32_t blo, int sc) {
  asm volatile("{\n.reg .pred p;\n.reg .b32 ta, tb;\n.reg .b64 da, db;\nadd.u32 ta, %64, %65;\nmov.b64 da, {ta, %66};\nadd.u32 tb, %67, %68;\nmov.b64 db, {tb, %69};\nsetp.ne.b32 p, %70, 0;\n"
    "wgmma.mma_async.sync.aligned.m64n128k16.f32.bf16.bf16 {%0, %1, %2, %3, %4, %5, %6, %7, %8, %9, %10, %11, %12, %13, %14, %15, %16, %17, %18, %19, %20, %21, %22, %23, %24, %25, %26, %27, %28, %29, %30, %31, %32, %33, %34, %35, %36, %37, %38, %39, %40, %41, %42, %43, %44, %45, %46, %47, %48, %49, %50, %51, %52, %53, %54, %55, %56, %57, %58, %59, %60, %61, %62, %63}, da, db, p, 1, 1, 0, 1;\n}\n"
    : "+f"(d[0]), "+f"(d[1]), "+f"(d[2]), "+f"(d[3]), "+f"(d[4]), "+f"(d[5]), "+f"(d[6]), "+f"(d[7]), "+f"(d[8]), "+f"(d[9]), "+f"(d[10]), "+f"(d[11]), "+f"(d[12]), "+f"(d[13]), "+f"(d[14]), "+f"(d[15]), "+f"(d[16]), "+f"(d[17]), "+f"(d[18]), "+f"(d[19]), "+f"(d[20]), "+f"(d[21]), "+f"(d[22]), "+f"(d[23]), "+f"(d[24]), "+f"(d[25]), "+f"(d[26]), "+f"(d[27]), "+f"(d[28]), "+f"(d[29]), "+f"(d[30]), "+f"(d[31]), "+f"(d[32]), "+f"(d[33]), "+f"(d[34]), "+f"(d[35]), "+f"(d[36]), "+f"(d[37]), "+f"(d[38]), "+f"(d[39]), "+f"(d[40]), "+f"(d[41]), "+f"(d[42]), "+f"(d[43]), "+f"(d[44]), "+f"(d[45]), "+f"(d[46]), "+f"(d[47]), "+f"(d[48]), "+f"(d[49]), "+f"(d[50]), "+f"(d[51]), "+f"(d[52]), "+f"(d[53]), "+f"(d[54]), "+f"(d[55]), "+f"(d[56]), "+f"(d[57]), "+f"(d[58]), "+f"(d[59]), "+f"(d[60]), "+f"(d[61]), "+f"(d[62]), "+f"(d[63])
    : "r"(alo), "n"(AO), "n"(AH), "r"(blo), "n"(BO), "n"(BH), "r"(sc));
}

#define XD 600
#define XSTEP 300
#define XPD 550
#define XPB 8192
#define SPG 5600
#define WL0 1800
#define WLS 350
#define NB0 2
#define WP1 2000
#define PF_START 5600
#define PFP 126
#define GPERM 0x76543210u
#define FMODE 2
#define NM0 3
#define PWAIT 600
#define AWAKE 1
#define WDW 3
#define WDGAP 150
#define YWAIT 500
#define CWAIT 500
#define NDF 8
#define RDV 1
#define MSTEP 1200
#define MSLP 1000
#define MPOLL 3200
#define LMP 8
#define FLO(q, cta) (p.s->flo + (q) * 256 + (cta) * 2)
#define NUD 4u
#define U1Q 0
#define UPS 4
#define WD0 (UPS + 5)
#define CLR0 22000
#define UPGAP 180
#define OUTGAP 150
#define MPROMO P128
#define MLOAD tma_load_ef
struct Ptrs { const bf16 *x, *wmod, *c, *wr, *wqkv; int by_sm; Scratch* s; const bf16 *wg, *wu, *wd, *wo; bf16* out; uint16_t role[132]; };

#define BAR(i) (sb + OFF_BAR + 8u * (i))

__device__ __forceinline__ uint32_t get_tag(uint32_t sb) { mbar_wait(BAR(B_TAG), 0); const uint32_t d = __shfl_sync(0xffffffffu, lds32(sb + OFF_CST + 32), 0); return d + 1 + (d & 2); }
__device__ __forceinline__ int d_kb(int n, int hg) {
    if (n < 2) return 2 * hg + n;
    const int h = n >= 9, q = n - 2 - 7 * h;
    return 2 * (q + (q >= hg)) + h;
}

__global__ void __launch_bounds__(NTHREADS, 1)
fused_kernel(const Ptrs p, const __grid_constant__ CUtensorMap tmM, const __grid_constant__ CUtensorMap tmX, const __grid_constant__ CUtensorMap tmW,
             const __grid_constant__ CUtensorMap tmWo, const __grid_constant__ CUtensorMap tmPhi, const __grid_constant__ CUtensorMap tmG,
             const __grid_constant__ CUtensorMap tmU, const __grid_constant__ CUtensorMap tmD, const __grid_constant__ CUtensorMap tmO)
{
    extern __shared__ __align__(1024) uint8_t smem_raw[];
    const uint32_t sb = smem_u32(smem_raw);
    const uint32_t cstart = __shfl_sync(0xffffffffu, clk32(), 0);
    const int tid = threadIdx.x, lane = tid & 31, warp = __shfl_sync(0xffffffffu, tid >> 5, 0);
    if (blockIdx.x < 128) {
        if (warp == 8) asm volatile("prefetch.global.L2 [%0];" :: "l"(p.wmod + (size_t)(blockIdx.x * 8 + (lane >> 2)) * 6144 + (lane & 1) * 64 + (lane & 2) * 512));
        if (warp == 13 && (lane & 1) < NM0 - 2) asm volatile("prefetch.global.L2 [%0];" :: "l"(p.wmod + (size_t)(blockIdx.x * 8 + (lane >> 2)) * 6144 + 128 + (lane & 1) * 64 + (lane & 2) * 512));
        if (warp == 11) asm volatile("prefetch.global.L2 [%0];" :: "l"((lane < 16 ? p.c : p.wr) + (lane & 15) * 64));
        if (warp == 12) l2_prefetch(p.wqkv + (size_t)blockIdx.x * 1536, 3072);
        if (warp == 9) { spin_until(cstart + XPD); l2_prefetch(p.x + (size_t)blockIdx.x * 16384, XPB); }
    }
    if (warp == 10) { tmap_prefetch(&tmM); tmap_prefetch(&tmX); tmap_prefetch(&tmW); }
    #pragma unroll
    for (int i = 0; i < 5; i++) e_init(BAR(5 * warp + i), warp < 5 ? 1 : warp < 7 ? 2 : warp < 9 ? 4 : warp < 14 ? 8 : warp < 15 ? 12 : 1);
    mbar_init_fence();
    if (warp == B_TAG / 5) { e_arrive_tx(BAR(B_TAG), 16); bulk_load(sb + OFF_CST + 32, p.s->done, 16, BAR(B_TAG)); }
    uint32_t role;
    asm("mov.u32 %0, %%smid;" : "=r"(role));
    role = p.role[p.by_sm ? role : blockIdx.x];
    const int b = role & 255;
    if (b >= 128 && warp == 0) {
        #pragma unroll
        for (int i = 0; i < 2; i++) { e_arrive_tx(BAR(i), 32768); MLOAD(sb + i * 32768u, &tmM, (b & 1) * 1024, (b & 2) * 256 + i * 256, BAR(i)); }
    }
    __syncthreads();

    if (b >= 128) {
        const int sp = b & 3;
        if (warp == 8) {
            #pragma unroll 1
            for (int j = 2, st = 2, ph = 1; j < 64; j++) {
                if (j == 2 * NM0) spin_until(cstart + SPG);
                mbar_wait(BAR(B_EA + st), ph);
                e_arrive_tx(BAR(st), 32768);
                MLOAD(sb + st * 32768u, &tmM, j < 32 ? (sp & 1) * 1024 + (j >> 1) * 64 : 2560 + sp * 512 + (j >> 2) * 64, (j < 32 ? (sp & 2) + (j & 1) : j & 3) * 256, BAR(st));
                if (++st == 6) { st = 0; ph ^= 1; }
            }
        } else if (warp < 8) {
            const int g = lane >> 2, c = lane & 3;
            {
                const bf16* cp = p.c + (tid >> 3) * 32 + (tid & 1) * 16 + (tid & 6);
                const uint32_t c0 = ldg32(cp), c1 = ldg32(cp + 8);
                stg_zero(p.s->llm1 + (tid >> 4) * 64 + sp * 16 + (tid & 15));
                if (tid < 128) stg_zero(p.s->llmod2 + sp * 128 + tid);
                sts64(sb + 200704u + tid * 8, silu2(c0), silu2(c1));
                bar_sync(1, 256);
                TR(57);
            }
            const uint32_t wa = sb + (warp * 32 + (lane & 7) + (lane >> 4) * 8) * 128u + ((((lane >> 3) & 1) ^ (lane & 7)) << 4);
            float m[4][4];
            #pragma unroll
            for (int i = 0; i < 4; i++) m[i][0] = m[i][1] = m[i][2] = m[i][3] = 0.f;
            #pragma unroll 1
            for (int r = 0, st = 0, ph = 0; r < 32; r++) {
                const uint32_t sa = sb + 200704u + ((r < 16 ? sp >> 1 : r & 1) * 16 + warp) * 64 + c * 16;
                #pragma unroll
                for (int q = 0; q < 2; q++) {
                    const uint4 sv = lds128(sa + q * 512);
                    uint32_t f[8][4];
                    mbar_wait(BAR(st + q), ph);
                    if (r == 0 && warp == 0) TR(60 + q);
                    #pragma unroll
                    for (int i = 0; i < 8; i++) ldsm4t(f[i], (wa + (st + q) * 32768u + (i >> 2) * 2048u) ^ ((i & 3) << 5));
                    e_arrive_after(BAR(B_EA + st + q), (f[0][0] ^ f[1][0] ^ f[2][0]) ^ (f[3][0] ^ f[4][0] ^ f[5][0]) ^ (f[6][0] ^ f[7][0]));
                    #pragma unroll
                    for (int i = 0; i < 8; i++) mma16816(m[i & 3], f[i][0], f[i][1], f[i][2], f[i][3], (i & 4) ? sv.z : sv.x, (i & 4) ? sv.w : sv.y);
                }
                st += 2; if (st == 6) { st = 0; ph ^= 1; }
                if (r >= 16 && !(r & 1)) continue;
                const int n = r < 16 ? r : (r >> 1) + 8;
                const uint32_t a = sb + 196608u + (n & 1) * 2048u + warp * 256u + (c * 16 + (g >> 1) * 4 + (g & 1)) * 4u;
                mbar_wait(BAR(B_XP + (n & 1)), ~(n >> 1) & 1);
                stsf(a, sel4(c, m[0][0], m[1][0], m[2][0], m[3][0])); stsf(a + 8, sel4(c, m[0][2], m[1][2], m[2][2], m[3][2]));
                #pragma unroll
                for (int i = 0; i < 4; i++) m[i][0] = m[i][1] = m[i][2] = m[i][3] = 0.f;
                __syncwarp();
                e_arrive(BAR(B_PF + (n & 1)));
            }
        } else if (warp == 9) {
            const int c = lane & 3;
            const uint32_t tag = get_tag(sb);
            #pragma unroll 1
            for (int n = 0; n < 24; n++) {
                const bf16* wr = p.wr + (sp & 1) * 512 + (n & 7) * 64 + ((lane >> 2) & 3) * 16 + 2 * c;
                const uint32_t wr0 = ldg32(wr), wr1 = ldg32(wr + 8);
                const uint32_t ra = sb + 196608u + (n & 1) * 2048u + (lane >> 4) * 1024u + (lane & 15) * 16u;
                uint4* d = n < 16 ? p.s->llm1 + n * 64 + sp * 16 + lane : p.s->llmod2 + sp * 128 + (n & 7) * 16 + lane;
                mbar_wait(BAR(B_PF + (n & 1)), (n >> 1) & 1);
                const uint4 r0 = lds128(ra), r1 = lds128(ra + 256), r2 = lds128(ra + 512), r3 = lds128(ra + 768);
                e_arrive(BAR(B_XP + (n & 1)));
                #define F4(f) ((u2f(r0.f) + u2f(r1.f)) + (u2f(r2.f) + u2f(r3.f)))
                float x = F4(x), y = F4(y), z = F4(z), w = F4(w);
                #undef F4
                x += shfl_x(x, 16); y += shfl_x(y, 16); z += shfl_x(z, 16); w += shfl_x(w, 16);
                if (n < 16) {
                    if (lane < 16) st_ll4(d, x, y, z, w, tag);
                } else {
                    uint32_t lo = pack2(x, y), hi2 = pack2(z, w);
                    float e = fmaf(bf_lo(lo), bf_lo(wr0), bf_hi(lo) * bf_hi(wr0)) + fmaf(bf_lo(hi2), bf_lo(wr1), bf_hi(hi2) * bf_hi(wr1));
                    if (sp >= 2) {
                        lo = hadd2(lo, ONE2); hi2 = hadd2(hi2, ONE2);
                        const uint32_t q0 = hmul2(lo, wr0), q1 = hmul2(hi2, wr1);
                        e = (bf_lo(q0) + bf_hi(q0)) + (bf_lo(q1) + bf_hi(q1));
                    }
                    #pragma unroll 1
                    for (int k = 1; k < 16; k <<= 1) e += shfl_x(e, k);
                    if (lane < 16) st_ll(d, lo, hi2, f2u(e), tag);
                }
                TR(n);
            }
        }
    } else if (warp >= 12) {
        reg_dec<24>();
        const int rb = b >> 3, hg = b & 7, fs = role >> 8;
        const bool ffn = fs < 112;
        if (warp == 12) {
            #pragma unroll 1
            for (int j = 0, s = 0, ph = 1; j < 16; j++) {
                if (j < 2) mbar_wait(j ? BAR(B_STS) : BAR(B_STP), 0);
                mbar_wait(BAR(B_EA + s), ph);
                e_arrive_tx(BAR(B_FA + s), 16384); tma_load(sb + OFF_A + s * 16384u, &tmX, j * 64, rb * 128, BAR(B_FA + s));
                if (j == 0) TS(2);
                if (j == 1) GT(0);
                if (j == 6) GT(1);
                if (j == 11) GT(2);
                if (++s == 3) { s = 0; ph ^= 1; }
            }
            if (ffn) {
                #pragma unroll 1
                for (int i = 3; i >= 0; i--) {
                    if (i & 1) mbar_wait(U1Q ? BAR(B_QE) : BAR(B_EA + (i >> 1)), !U1Q && i == 1);
                    tma_load_ef(sb + OFF_U1 + i * 8192u, &tmU, fs * 32, 512 + i * 128, BAR(B_UF));
                }
            }
            tmap_prefetch(&tmO);
            const uint32_t tag = get_tag(sb);
            e_arrive(BAR(B_FD)); e_arrive(BAR(B_FD + 1));
            const uint4* osrc = pin_ptr(p.s->os + (size_t)rb * 16 * 1024);
            #pragma unroll 1
            for (int q = 0; q < 3; q++) {
                mbar_wait(q < 2 ? BAR(B_KST + 1 + 2 * q) : BAR(B_OWN), 0);
                const uint32_t chk = poll_flags(q < 2 ? p.s->flk + (q + 1) * 256 + (hg * 16 + (lane & 15)) * 2 : FLO(0, rb * 8 + (lane & 7)), tag);
                if (q == 2) { sts32(sb + OFF_CHK + 64 + (lane & 7) * 8, chk); __syncwarp(); break; }
                e_arrive_tx(BAR(B_KVL + q), 16896); bulk_load(sb + (q ? OFF_KL1 : OFF_KL), p.s->kvacc + hg * 2112 + q * 1056, 16896, BAR(B_KVL + q));
                TS(12 + q);
                if (!q) GT(4);
            }
            TS(3); GT(5);
            #pragma unroll
            for (int n = 2; n < 6; n++) {
                if (n >= 4) mbar_wait(BAR(B_ED + (n & 3)), 0); else if (n == 3) mbar_wait(BAR(B_OWN + 1), 0);
                e_arrive_tx(BAR(B_FD + (n & 3)), 16384);
                bulk_load(sb + (n == 5 ? OFF_X1 : OFF_R0 + (n & 3) * 16384u), osrc + (n - 2 >= hg ? n - 1 : n - 2) * 2048, 16384, BAR(B_FD + (n & 3)));
                TR(32 + n);
            }
            #pragma unroll 1
            for (int n = 6; n < 16; n++) {
                const uint32_t s = n & 3, fb = BAR(B_FD + s);
                const uint4* src = osrc + d_kb(n, hg) * 1024;
                if (n == 9) mbar_wait(BAR(B_O1), 0);
                mbar_wait(BAR(B_ED + s), ((n >> 2) - 1) & 1);
                e_arrive_tx(fb, 16384);
                bulk_load(sb + OFF_R0 + s * 16384u, src, 16384, fb);
                TR(32 + n);
            }
            e_arrive_tx(BAR(B_WPHI), 32768);
            mbar_wait(BAR(B_ED), 1);
            tma_load(sb + OFF_R0, &tmX, hg * 128, rb * 128, BAR(B_WPHI));
            tma_load(sb + OFF_X1, &tmX, hg * 128 + 64, rb * 128, BAR(B_WPHI));
            GT(6);
            mbar_wait(BAR(B_CAND), 0);
            GT(7);
            const uint2 lc = lds64(sb + OFF_CST + 16);
            const uint32_t w0 = __shfl_sync(0xffffffffu, lc.x >> 4, 0), w1 = __shfl_sync(0xffffffffu, lc.y >> 4, 0);
            mbar_wait(BAR(B_SWP), 0);
            fence_async_smem();
            #pragma unroll 1
            for (uint32_t w = 0; w < 8; w++)
                if (w != w0 && w != w1) { tma_store4(&tmO, rb * 128 + w * 16, hg * 2, sb + OFF_OUT + w * 4096u); spin_until(clk32() + OUTGAP); }
            mbar_wait(BAR(B_SEL), 0);
            const uint2 sel = lds64(sb + OFF_CST + 24);
            #pragma unroll 1
            for (uint32_t i = 0; i < (w0 == w1 ? 8u : 16u); i++) {
                const uint32_t w = i < 8 ? w0 : w1, r = (i & 7) * 2 + (lane >> 4), row = rb * 128 + w * 16 + r;
                const uint4 o = lds128(sb + OFF_OUT + w * 4096u + ((lane >> 3) & 1) * 2048u + r * 128u + (((lane ^ r) & 7) << 4));
                if (row != (~sel.x & 2047u) && row != (~sel.y & 2047u)) stg128(p.out + (size_t)row * 1024 + hg * 128 + (lane & 15) * 8, o);
            }
            bulk_wait_read();
        } else if (warp == 14) {
            const uint32_t fb = ffn ? 65536 : 0;
            e_arrive_tx(BAR(B_GF), fb); e_arrive_tx(BAR(B_UD), ffn ? NUD * 8192 : 0); e_arrive_tx(BAR(B_UF), fb); e_arrive_tx(BAR(B_WD), fb);
            uint32_t due = cstart + WP1;
            #pragma unroll 1
            for (int i = -2; i < 26; i++) {
                if (i >= 0) {
                    const bf16* a = i < 8 ? p.wg + (size_t)(i * 128 + b) * 3584 : i < 16 ? p.wu + (size_t)((i - 8) * 128 + b) * 3584
                                  : i < 18 ? p.wo + (size_t)(b * 2 + i - 16) * 4096 : p.wd + (size_t)(b * 8 + i - 18) * 3584;
                    sleep_until(due);
                    l2_prefetch(a, (i >> 1) == 8 ? 8192 : 7168);
                    due += 7 * PFP;
                }
                if (i == 1) { tmap_prefetch(&tmPhi); tmap_prefetch(&tmG); tmap_prefetch(&tmWo); tmap_prefetch(&tmU); tmap_prefetch(&tmD); mbar_wait(BAR(B_STS), 0); }
                if (ffn && (uint32_t)(i - 3) < 8u) tma_load_ef(sb + OFF_R0 + (i - 3) * 8192u, &tmG, fs * 32, (i - 3) * 128, BAR(B_GF));
                if (ffn && (uint32_t)(i - 11) < NUD) tma_load(sb + OFF_WPHI, &tmU, fs * 32, (i - 11) * 128, BAR(B_UD));
                if (i == 19) { mbar_wait(BAR(B_UD), 0); e_arrive_tx(BAR(B_WPHI), 8192); tma_load(sb + OFF_WPHI, &tmPhi, 0, hg * 128, BAR(B_WPHI)); }
                if (i == LMP + 2 * (b & 3) + (b >> 6)) tma_prefetch(&tmM, 2048 + (b >> 6) * 2048 + (b >> 2) * 64, (b & 3) * 256);
                if (i < 13) {
                    sleep_until(due);
                    l2_prefetch(p.wqkv + (size_t)((i + 3) * 128 + b) * 1536, 3072);
                    due += i == -2 ? PF_START - WP1 : 3 * PFP;
                }
            }
            if (lane < 4) stg_zero(FLO(lane >> 1, b) + (lane & 1));
            const uint32_t tag = get_tag(sb);
            #pragma unroll 1
            for (int q = 0; q < 2; q++) {
                mbar_wait(BAR(B_OWN + q), 0);
                if (q) mbar_wait(BAR(B_FD + 2), 0);
                bulk_store(p.s->os + ((size_t)b * 2 + q) * 1024, sb + OFF_R0 + q * 16384u, 16384);
                mbar_wait(BAR(B_CS + q), 0);
                uint32_t chk = __reduce_xor_sync(0xffffffffu, lane < 8 ? lds32(sb + OFF_CHK + q * 32 + lane * 4) : 0u);
                bulk_wait();
                __syncwarp();
                st_flag(FLO(q, b), tag, chk, lane);
                TS(7 + q);
            }
            e_arrive(BAR(B_OST));
            fence_gpu();
            __syncwarp();
            st_flag(FLO(2, b), tag, 0, lane);
        } else {
            uint4* fk = p.s->flk + (hg * 16 + rb) * 2;
            if (warp == 13) {
                #pragma unroll 1
                for (int i = 0; i < 32; i++) {
                    const uint32_t s = i & 3;
                    if (i < NB0) spin_until(cstart + WL0 + WLS * i); else if (i == NB0) mbar_wait(BAR(B_STS), 0);
                    mbar_wait(BAR(B_EB + s), ((i >> 2) - 1) & 1);
                    e_arrive_tx(BAR(B_FB + s), 24576); tma_load4(sb + OFF_B + s * 24576u, &tmW, i * 32, hg * 2, BAR(B_FB + s));
                    TR(64 + i);
                }
                mbar_wait(BAR(B_EB), 1); mbar_wait(BAR(B_EB + 1), 1);
                e_arrive_tx(BAR(B_LMF), 32768); tma_load_ef(sb + OFF_DB, &tmM, 2048 + (b >> 6) * 2048 + (b >> 2) * 64, (b & 3) * 256, BAR(B_LMF));
            } else {
                sleep_until(cstart + CLR0);
                const uint32_t tag = get_tag(sb);
                #pragma unroll 1
                for (int i = lane; i < 132; i += 32) stg_zero(p.s->kvacc + hg * 2112 + rb * 132 + i);
                if (lane < 4) stg_zero(fk + 256 + (lane >> 1) * 256 + (lane & 1));
                fence_gpu();
                __syncwarp();
                st_flag(fk, tag, 0, lane);
                sleep_until(clk32() + 2000);
                poll_flags(p.s->flk + (hg * 16 + (lane & 15)) * 2, tag);
                mbar_wait(BAR(B_QE), 0);
                #pragma unroll 1
                for (int i = 0; i < 4; i++) {
                    stg_zero(p.s->llln2 + b * 128 + i * 32 + lane);
                    stg_zero(p.s->llrowh + (i >> 1) * 8192 + (rb * 2 + (i & 1)) * 256 + hg * 32 + lane);
                    #pragma unroll
                    for (int k = 0; k < 4; k++) stg_zero(p.s->lly + (fs & 127) * 512 + i * 128 + k * 32 + lane);
                }
                if (lane < 2 && hg == (rb & 7)) stg_zero(p.s->llcand + rb * 2 + lane);
                __syncwarp();
                e_arrive(BAR(B_KZ));
            }
            const int q = warp == 13;
            const uint32_t tag = get_tag(sb);
            mbar_wait(BAR(B_KZ), 0);
            #pragma unroll 1
            for (int h = 2 * q; h < 2 * q + 2; h++) {
                mbar_wait(BAR(B_KST + h), 0);
                uint4* acc = p.s->kvacc + (hg * 4 + h) * 528;
                bulk_reduce(acc, sb + (h ? OFF_V + (h - 1) * 8192u : OFF_KL), 8192); bulk_reduce(acc + 512, sb + OFF_ZS + h * 256u, 256);
            }
            bulk_wait();
            if (q) e_arrive(BAR(B_KZ));
            TR(158 + q);
            fence_gpu();
            __syncwarp();
            st_flag(fk + 256 + q * 256, tag, 0, lane);
            TS(10 + q);
            if (q) {
                #pragma unroll 1
                for (int n = 4; n < 16; n++) {
                    const uint32_t s = n & 3;
                    mbar_wait(BAR(B_ED + s), ((n >> 2) - 1) & 1);
                    e_arrive_tx(BAR(B_FD + s), 16384);
                    tma_load4(sb + OFF_DB + s * 16384u, &tmWo, d_kb(n, hg) * 64, hg * 2, BAR(B_FD + s));
                    TR(96 + n);
                    if (ffn && (uint32_t)(n - WD0) < 4u) {
                        #pragma unroll
                        for (int k = 0; k < 2; k++) tma_load_ef(sb + OFF_F2 + (n - WD0) * 8192u + k * 4096u, &tmD, (n - WD0) * 256 + k * 128, fs * 32, BAR(B_WD));
                    }
                }
                if (ffn) {
                    mbar_wait(BAR(B_ED + WDW), 1);
                    #pragma unroll 1
                    for (int z = 0; z < 8; z++) { tma_load_ef(sb + OFF_DB + z * 4096u, &tmD, z * 128 + 64, fs * 32, BAR(B_WD)); sleep_until(clk32() + WDGAP); }
                }
            } else {
                mbar_wait(BAR(B_LMD), 0);
                mbar_wait(BAR(B_KVL), 0);
                mbar_wait(BAR(B_KZ), 1);
                #pragma unroll 1
                for (int i = 0; i < 8; i++) {
                    const int n = i < 2 ? i : i < 6 ? i + 2 : i - 4;
                    if (i == 6) mbar_wait(BAR(B_KVT + 1), 0);
                    if (n < 4) { e_arrive_tx(BAR(B_FD + n), 16384); tma_load4(sb + OFF_DB + n * 16384u, &tmWo, d_kb(n, hg) * 64, hg * 2, BAR(B_FD + n)); }
                    else if (ffn) { tma_load_ef(sb + OFF_F2 + (7 - n) * 8192u, &tmU, fs * 32, (7 - n) * 128, BAR(B_UF)); sleep_until(clk32() + UPGAP); }
                }
                mbar_wait(BAR(B_OST), 0);
                sts32(sb + OFF_CHK + 68 + (lane & 7) * 8, poll_flags(FLO(1, rb * 8 + (lane & 7)), tag));
                __syncwarp();
                e_arrive(BAR(B_O1));
                TS(4);
            }
        }
    } else if (warp >= 8) {
        reg_dec<24>();
        const int rb = b >> 3, hg = b & 7, w4 = warp & 3, g = lane >> 2, c = lane & 3, t = tid & 127;
        const uint32_t sv = silu2(ldg32(p.c + (b & 3) * 256 + 2 * t)), tag = get_tag(sb);
        if (w4 < 3) {
            spin_until(cstart + MPOLL + MSTEP * w4);
            #pragma unroll 1
            for (int j = w4, ph = 1; j < 16; j += 3, ph ^= 1) {
                uint4 w[2];
                poll_words<2, 0, 3>(w, p.s->llm1 + j * 64 + lane, 32, tag);
                uint32_t lo = pack2(u2f(w[0].x) + u2f(w[1].x), u2f(w[0].y) + u2f(w[1].y)), hi = pack2(u2f(w[0].z) + u2f(w[1].z), u2f(w[0].w) + u2f(w[1].w));
                if (lane >= 16) { lo = hadd2(lo, ONE2); hi = hadd2(hi, ONE2); }
                sts64(sb + OFF_TAB + j * 256 + (lane & 15) * 16 + (lane < 16 ? 8 : 0), lo, hi);
                __syncwarp();
                if (j == 0) TS(5);
                TR(16 + j);
                mbar_wait(BAR(B_EA + w4), ph);
                e_arrive(BAR(B_FA + w4));
                __nanosleep(MSLP);
            }
        }
        mbar_wait(BAR(B_QE), 0);
        if (warp == 8) GT(3);
        sts32(sb + OFF_Z + w4 * 1024u + lane * 4, sv);
        reg_inc<56>();
        #pragma unroll 1
        for (int h = 0; h < 4; h++) {
            float okv[20];
            const uint32_t vb = OFF_V + h * 8192u, dp = desc_lo(sb + OFF_PHI + (h & 1) * 16384u, 16), dv = desc_lo(sb + vb, OFF_ONES - vb);
            const uint32_t xa = sb + (h ? vb - 8192u : OFF_KL) + t * 16u;
            if (h) mbar_wait(BAR(B_KST - 1 + h), 0);
            mbar_wait(BAR(B_PF + h), 0);
            fence_async_smem();
            wg_fence();
            #define KVS(i) mma40_tt<(i) * 128, H128, (i) * (64u - (64u << 16)), H64>(okv, dp, dv)
            mma40_tt0<0, H128, 0, H64>(okv, dp, dv); KVS(1); KVS(2); KVS(3); KVS(4); KVS(5); KVS(6); KVS(7);
            #undef KVS
            wg_commit();
            wg_wait<0>();
            acc_fence(okv);
            #pragma unroll
            for (int k = 0; k < 4; k++) sts128(xa + k * 2048u, make_uint4(f2u(okv[4 * k]), f2u(okv[4 * k + 1]), f2u(okv[4 * k + 2]), f2u(okv[4 * k + 3])));
            if (c == 0) sts64(sb + OFF_ZS + h * 256u + (w4 * 8 + g) * 8u, f2u(okv[16]), f2u(okv[18]));
            fence_async_smem();
            __syncwarp();
            e_arrive(BAR(B_KST + h));
            if (warp == 8) TR(151 + h);
        }
        {
            float m0[4], m1[4];
            const uint32_t da = desc_lo(sb + OFF_DB, 16), db = desc_lo(sb + OFF_Z, 16);
            mbar_wait(BAR(B_LMF), 0);
            wg_fence();
            #define LMS(f, i) f<(i) * 256, H128, ((i) >> 1) * 64 + ((i) & 1) * 4, H128>(m0, da, db); f<(i) * 256 + 128, H128, ((i) >> 1) * 64 + ((i) & 1) * 4 + 2, H128>(m1, da, db)
            LMS(mma8_tn0, 0); LMS(mma8_tn, 1); LMS(mma8_tn, 2); LMS(mma8_tn, 3); LMS(mma8_tn, 4); LMS(mma8_tn, 5); LMS(mma8_tn, 6); LMS(mma8_tn, 7);
            #undef LMS
            wg_commit();
            wg_wait<0>();
            acc_fence(m0); acc_fence(m1);
            e_arrive(BAR(B_LMD));
            const float v0 = m0[0] + m1[0], v1 = m0[2] + m1[2], u0 = shfl_x(v0, 4), u1 = shfl_x(v1, 4);
            if (!(lane & 7)) st_ll4(p.s->llg + (b >> 6) * 1024 + (b & 3) * 256 + ((b >> 2) & 15) * 16 + w4 * 4 + (lane >> 3), v0, u0, v1, u1, tag);
            if (warp == 8) TR(150);
        }
        e_arrive(BAR(B_ED)); e_arrive(BAR(B_ED + 1));
        mbar_wait(BAR(B_LMD), 0);
        #pragma unroll 1
        for (int q = 0; q < 2; q++) {
            const uint32_t f = w4 * 16 + g, kl = sb + (q ? OFF_KL1 : OFF_KL), ta = sb + (q ? OFF_KL : OFF_KVT) + f * 64u + ((g >> 1) << 4) + 4 * c;
            const uint32_t za = sb + OFF_Z + (f + 8 * (c & 1)) * 64u + (((2 * q) ^ (g >> 1)) << 4) + (c >> 1) * 8;
            mbar_wait(q ? BAR(B_KVT) : BAR(B_STP), q ^ 1);
            mbar_wait(BAR(B_KVL + q), 0);
            uint4 v[8]; float z[2];
            #pragma unroll
            for (int k = 0; k < 8; k++) v[k] = lds128(kl + (k >> 2) * 8448u + (k & 3) * 2048u + t * 16u);
            #pragma unroll
            for (int hh = 0; hh < 2; hh++) z[hh] = ldsf(kl + hh * 8448u + 8192u + (w4 * 8 + g) * 8u + (c & 1) * 4);
            #pragma unroll
            for (int k = 0; k < 8; k++) {
                sts32((ta ^ ((k & 3) << 4)) + (k >> 2) * 4096u, pack2(u2f(v[k].x), u2f(v[k].y))); sts32((ta ^ ((k & 3) << 4)) + (k >> 2) * 4096u + 512, pack2(u2f(v[k].z), u2f(v[k].w)));
            }
            #pragma unroll
            for (int hh = 0; hh < 2; hh++) { const uint32_t zz = pack2(z[hh], z[hh]); sts64(za ^ (hh << 4), zz, zz); }
            fence_async_smem();
            __syncwarp();
            e_arrive(BAR(B_KVT + q));
            if (warp == 8) TR(155 + q);
        }
        reg_dec<24>();
        if (w4 == 0 || w4 == 3) {
            float s[4] = {0.f, 0.f, 0.f, 0.f};
            #pragma unroll 1
            for (int k = 0; k < 2; k++) {
                uint4 w[2];
                poll_words<2, 0, 3>(w, p.s->llg + (w4 & 1) * 1024 + k * 512 + hg * 32 + lane, 256, tag);
                s[0] += u2f(w[0].x) + u2f(w[1].x); s[1] += u2f(w[0].y) + u2f(w[1].y); s[2] += u2f(w[0].z) + u2f(w[1].z); s[3] += u2f(w[0].w) + u2f(w[1].w);
            }
            const uint32_t lo = pack2(s[0], s[1]), hi = pack2(s[2], s[3]);
            sts64(w4 ? sb + OFF_T3 + lane * 8 : sb + OFF_T1 + lane * 16, lo, hi);
            if (!w4) sts64(sb + OFF_T1 + 512 + lane * 16, lo, hi);
        }
        if (w4 == 1 || w4 == 2) {
            const bf16* wr = p.wr + hg * 128 + g * 16 + 2 * c;
            const uint32_t wr0 = ldg32(wr), wr1 = ldg32(wr + 8);
            uint4 w[2];
            poll_words<2, 1>(w, p.s->llmod2 + (w4 - 1) * 256 + hg * 32 + lane, (lane & 15) * 16 - hg * 32 - lane, tag);
            sts64(sb + OFF_T2 + lane * 16 + (w4 & 1) * 8, w[0].x, w[0].y);
            if (w4 == 2) sts64(sb + OFF_T1 + 512 + lane * 16 + 8, hmul2(w[0].x, wr0), hmul2(w[0].y, wr1));
            float d = u2f(w[1].z);
            #pragma unroll 1
            for (int k = 1; k < 16; k <<= 1) d += shfl_x(d, k);
            stsf(sb + OFF_CST + 8 + (w4 & 1) * 4, d);
        }
        if (warp == 10) TS(6);
        {
            const uint32_t a = sb + w4 * 4096u + g * 128u + (((2 * c) ^ g) << 4) + (g >> 1) * 4;
            uint32_t x = 0;
            #pragma unroll 1
            for (int n = 2; n < 16; n++) {
                const uint32_t ta = a + (n == 5 ? OFF_X1 : OFF_R0 + (n & 3) * 16384u), ca = sb + OFF_CHK + 64 + d_kb(n, hg) * 4;
                mbar_wait(BAR(B_FD + (n & 3)), (n >> 2) & 1);
                const uint32_t v0 = lds32(ta), v1 = lds32(ta + 1024), v2 = lds32(ta + 2048), v3 = lds32(ta + 3072);
                x = __funnelshift_l(x, x, 1) ^ v0 ^ v1 ^ v2 ^ v3;
                e_arrive_after(BAR(B_ED + (n & 3)), x);
                if (t == 0) x ^= lds32(ca);
            }
            sts32(sb + OFF_CHK + 128 + w4 * 4, __reduce_xor_sync(0xffffffffu, x));
        }
        __syncwarp();
        e_arrive(BAR(B_PAR));
        if (w4 < 2) {
            mbar_wait(BAR(B_PAR), 0);
            const uint4 ta = lds128(sb + OFF_T2 + lane * 16);
            const uint2 gb = lds64(sb + OFF_T3 + lane * 8);
            uint4* d = pin_ptr(p.s->llrowh + (rb * 2 + w4) * 256 + hg * 32 + lane);
            mbar_wait(BAR(B_KEYS), 0);
            const uint4 kk = lds128(sb + OFF_KEY + lane * 16);
            uint32_t k[4] = {kk.x, kk.y, kk.z, kk.w}, b0, b1;
            top2<4>(k, b0, b1);
            const uint32_t cd = ~(w4 ? b1 : b0) & 127u;
            const uint32_t xa = sb + OFF_R0 + (g >> 2) * (OFF_X1 - OFF_R0) + cd * 128u + ((((g & 3) * 2) ^ (cd & 7)) << 4) + c * 4;
            const uint32_t x0 = lds32(xa), x1 = lds32(xa ^ 16);
            const uint4 st = lds128(sb + OFF_ST2 + cd * 16);
            st_ll(d, lnmod(x0, st.x, st.y, st.z, ta.x, ta.z), lnmod(x1, st.x, st.y, st.z, ta.y, ta.w), gb.x, tag);
            st_ll(d + 8192, x0, x1, gb.y, tag);
            sts32(sb + OFF_CST + 16 + w4 * 4, cd);
            __syncwarp();
            e_arrive(BAR(B_CAND));
            if (warp == 8) TS(9);
        } else if (w4 == 2) {
            uint4* cp = pin_ptr(p.s->llcand + lane);
            mbar_wait(BAR(B_KEYS), 0);
            if (hg == (rb & 7)) {
                const uint4 kk = lds128(sb + OFF_KEY + lane * 16);
                uint32_t k[4] = {kk.x, kk.y, kk.z, kk.w}, b0, b1;
                top2<4>(k, b0, b1);
                if ((lane >> 1) == rb) st_ll(cp, tag, (lane & 1) ? b1 : b0, tag, tag);
            } else spin_until(clk32() + CWAIT);
            uint32_t k[1] = {poll_flags(cp, tag)}, b0, b1;
            top2<1>(k, b0, b1);
            sts64(sb + OFF_CST + 24, b0, b1);
            __syncwarp();
            e_arrive(BAR(B_SEL));
        }
    } else {
        reg_inc<232>();
        float a0[96], a1[96];
        {
            const int g = lane >> 2, c = lane & 3;
            uint4* stp = p.s->llstat + b * 16 + warp * 2 + (lane >> 4);
            if (lane == 0 || lane == 18) stg_zero(stp);
            spin_until(cstart + XD + XSTEP * warp);
            e_arrive_tx(BAR(B_XP + warp), 4096);
            bulk_load(sb + OFF_R0 + warp * 4096u, p.x + (size_t)(b * 16 + 2 * warp) * 1024, 4096, BAR(B_XP + warp));
            const uint32_t tag = get_tag(sb);
            if (tid < 64) sts128(sb + OFF_ONES + tid * 16, make_uint4(ONE2, ONE2, ONE2, ONE2));
            if (tid == 64) { sts64(sb + OFF_CST, role, tag); stsf(sb + OFF_CST + 48, -LOG2E); }
            if (AWAKE & 1) mbar_wait_awake(BAR(B_XP + warp), 0); else mbar_wait(BAR(B_XP + warp), 0);
            e_arrive(BAR(B_STP));
            if (warp == 7) TS(14);
            float s[2][4], q0[2][4], q1[2][4];
            #pragma unroll
            for (int i = 0; i < 4; i++) s[0][i] = s[1][i] = q0[0][i] = q0[1][i] = q1[0][i] = q1[1][i] = 0.f;
            uint32_t xa[8][4], xb[8][4];
            const uint32_t la = sb + OFF_R0 + warp * 4096u + (lane & 7) * 16u;
            #pragma unroll
            for (int i = 0; i < 8; i++) {
                ldsm4(xa[i], la + ((lane >> 3) & 1) * 2048u + (lane >> 4) * 128u + i * 256u);
                ldsm4(xb[i], la + ((lane >> 3) & 1) * 128u + (lane >> 4) * 2048u + i * 256u);
            }
            #pragma unroll
            for (int i = 0; i < 8; i++) {
                mma16816(q0[i & 1], xa[i][0], xa[i][1], xa[i][2], xa[i][3], xb[i][0], xb[i][1]);
                mma16816(q1[i & 1], xa[i][0], xa[i][1], xa[i][2], xa[i][3], xb[i][2], xb[i][3]);
                mma16816(s[i & 1], xa[i][0], xa[i][1], xa[i][2], xa[i][3], ONE2, ONE2);
            }
            const float s0 = s[0][0] + s[1][0], s1 = s[0][2] + s[1][2];
            const float sq0 = (g & 1) ? q0[0][1] + q0[1][1] : q0[0][0] + q0[1][0], sq1 = (g & 1) ? q1[0][3] + q1[1][3] : q1[0][2] + q1[1][2];
            const bool up = lane >= 16;
            float sm = (up ? s1 : s0) + shfl_x(up ? s0 : s1, 18), sq = (up ? sq1 : sq0) + shfl_x(up ? sq0 : sq1, 18);
            sm += shfl_x(sm, 9); sq += shfl_x(sq, 9);
            sm += shfl_x(sm, 4); sq += shfl_x(sq, 4);
            uint32_t m2, rh, rl; float rinv;
            ln_final(sm, sq, m2, rinv);
            split_rcp(rinv, rh, rl);
            if (lane == 0 || lane == 18) st_ll(stp, m2, rh, rl, tag);
            if (warp == 7) TS(15);
            uint4 st[2];
            if (PWAIT) { mbar_wait(BAR(B_STP), 0); if (warp < 7) spin_until(clk32() + PWAIT); }
            #pragma unroll 1
            for (int it = 0; it < POLL_MAX; it++) {
                st[0] = ld_ll(p.s->llstat + (b >> 3) * 128 + warp * 16 + g); st[1] = ld_ll(p.s->llstat + (b >> 3) * 128 + warp * 16 + g + 8);
                const uint32_t o = RDV ? ld_rlx(&p.s->llstat[((b >> 5) * 4 + c) * 128 + warp * 16 + 15].w) : tag;
                if (__all_sync(0xffffffffu, !tag_bad(tag_bad(o ^ tag, st[0].w, tag), st[1].w, tag))) break;
                if (AWAKE & 1) it += awake_zero();
            }
            e_arrive(BAR(B_STS));
            if (warp == 0) TS(16);
            const uint32_t lrow = warp * 16 + (lane & 15);
            uint32_t aad = sb + OFF_A + lrow * 128u + (((lane >> 4) ^ (lrow & 7)) << 4);
            uint32_t tad = sb + OFF_TAB + c * 16, ab = BAR(B_FA), pa = 0;
            uint32_t f0[4], f1[4];
            #define PREP(f, q) do { \
                const uint4 t = lds128(tad + (q) * 64); \
                ldsm4(f, aad ^ ((q) << 5)); \
                f[0] = lnmod(f[0], st[0].x, st[0].y, st[0].z, t.x, t.z); f[1] = lnmod(f[1], st[1].x, st[1].y, st[1].z, t.x, t.z); \
                f[2] = lnmod(f[2], st[0].x, st[0].y, st[0].z, t.y, t.w); f[3] = lnmod(f[3], st[1].x, st[1].y, st[1].z, t.y, t.w); } while (0)
            #define MMA(f, off) do { wg_fence(); mma192_rs<(off), H128>(a0, f, blo); mma192_rs<(off) + 768, H128>(a1, f, blo); wg_commit(); wg_wait<1>(); } while (0)
            mbar_wait(ab, 0);
            PREP(f0, 0);
            if (RDV) mbar_wait(BAR(B_STS), 0);
            #pragma unroll 1
            for (int j = 0; j < 16; j++) {
                const uint32_t bb = BAR(B_FB) + (j & 1) * 16, blo = desc_lo(sb + OFF_B, 4096) + (j & 1) * 3072, pb = (j >> 1) & 1;
                mbar_wait(bb, pb);
                wg_fence(); mma192_rsp<0, H128>(a0, f0, blo, j); mma192_rsp<768, H128>(a1, f0, blo, j); wg_commit(); wg_wait<1>();
                if (j) e_arrive((bb ^ 16) + 8 * (B_EB - B_FB) + 8);
                PREP(f1, 1);
                MMA(f1, 128);
                PREP(f0, 2);
                mbar_wait(bb + 8, pb);
                MMA(f0, 1536);
                e_arrive(bb + 8 * (B_EB - B_FB));
                PREP(f1, 3);
                MMA(f1, 1536 + 128);
                e_arrive(ab + 8 * (B_EA - B_FA));
                ab += 8; aad += 16384; tad += 256;
                if (ab == BAR(B_FA + 3)) { ab -= 24; aad -= 49152; pa ^= 1; }
                if (j < 15) mbar_wait(ab, pa);
                PREP(f0, 0);
            }
            #undef PREP
            #undef MMA
        }
        int tid_o; asm volatile("mov.u32 %0, %%tid.x;" : "=r"(tid_o) :: "memory");
        const int tid = tid_o, lane = tid & 31, warp = __shfl_sync(0xffffffffu, tid >> 5, 0), wgi = warp >> 2, g = lane >> 2, c = lane & 3;
        const uint32_t srow = warp * 16 + (lane & 15);
        #define T128(t) (sb + (((t) >> 5) * 16 + ((t) & 15)) * 128u + (((((t) >> 4) & 1) ^ ((t) & 7)) << 4))
        const uint32_t pa = T128(tid);
        mbar_wait(BAR(B_WPHI), 0);
        mbar_wait(BAR(B_EB + 2), 1);
        wg_wait<0>();
        acc_fence(a0); acc_fence(a1);
        e_arrive(BAR(B_QE));
        if (warp == 0) TS(18);
        uint32_t ph[4][16];
        {
            uint32_t f1[16], kq[32], pk[16], mm[4], mn[2];
            float ea[32], eb[32], p0[16], p1[16];
            const uint32_t dw = desc_lo(sb + OFF_WPHI, 16);
            #define PMMA(f, o) do { wg_fence(); mma32_rs0<(o), H64>(p0, f, dw); mma32_rs0<(o) + 128, H64>(p1, f + 8, dw); \
                mma32_rs<(o) + 64, H64>(p0, f + 4, dw); mma32_rs<(o) + 192, H64>(p1, f + 12, dw); wg_commit(); } while (0)
            #define PWAIT0() do { wg_wait<0>(); acc_fence(p0); acc_fence(p1); } while (0)
            #define V_OUT(lo, n) _Pragma("unroll") for (int i = lo; i < lo + n; i++) { const int o = 32 + 8 * i; \
                stsm4(sb + OFF_V + (i >> 1) * 8192u + srow * 64u + (((2 * (i & 1) + (lane >> 4)) ^ ((srow >> 1) & 3)) << 4), \
                      pack2(a1[o], a1[o + 1]), pack2(a1[o + 2], a1[o + 3]), pack2(a1[o + 4], a1[o + 5]), pack2(a1[o + 6], a1[o + 7])); }
            V_OUT(0, 4);
            #pragma unroll
            for (int i = 0; i < 16; i++) pk[i] = pack2(a0[64 + 2 * i], a0[65 + 2 * i]);
            PMMA(pk, 0);
            V_OUT(4, 2);
            #pragma unroll
            for (int i = 0; i < 16; i++) f1[i] = pack2(a1[2 * i], a1[2 * i + 1]);
            #pragma unroll
            for (int i = 0; i < 32; i++) kq[i] = pack2(a0[2 * i], a0[2 * i + 1]);
            mbar_wait(BAR(B_QE), 0);
            V_OUT(6, 2);
            #undef V_OUT
            PWAIT0();
            reg_dec<216>();
            if (warp == 0) TS(19);
            #define PHI_OUT(h) do { if (u == 0) { \
                    if ((h) >= 2) mbar_wait(BAR(B_KST + ((h) & 1)), 0);          \
                    _Pragma("unroll") for (int q = 0; q < 4; q++) stsm4((pa ^ (q << 5)) + OFF_PHI + ((h) & 1) * 16384u, ph[h][4 * q], ph[h][4 * q + 1], ph[h][4 * q + 2], ph[h][4 * q + 3]); \
                    __syncwarp(); \
                    e_arrive(BAR(B_PF + (h))); } } while (0)
            #define NL() ldsf(sb + OFF_CST + 48)
            #pragma unroll 1
            for (int u = 0; u < 2; u++) {
                fm_max(p0, pk, mm); fm_max(p1, pk + 8, mm + 2);
                PMMA(f1, 256);
                fm_pos(pk, mm, ea);
                acc_fence(ea);
                PWAIT0();
                if (u) e_arrive(BAR(B_STP));
                fm_neg(mm, NL(), ea); fm_pos(pk + 8, mm + 2, eb);
                fm_norm(ea, ph[0]); fm_max(p0, pk, mm);
                PHI_OUT(0);
                fm_neg(mm + 2, NL(), eb); fm_pos(pk, mm, ea);
                fm_norm(eb, ph[1]); fm_max(p1, pk + 8, mn);
                PHI_OUT(1);
                if (warp == 0) TS(21 + 2 * u);
                fm_neg(mm, NL(), ea); fm_pos(pk + 8, mn, eb);
                fm_norm(ea, ph[2]);
                PHI_OUT(2);
                PMMA(kq, 0);
                fm_neg(mn, NL(), eb);
                fm_norm(eb, ph[3]);
                PHI_OUT(3);
                PWAIT0();
                #pragma unroll
                for (int i = 0; i < 16; i++) f1[i] = kq[16 + i];
                if (warp == 0) TS(22 + 2 * u);
            }
            #undef NL
            #undef PHI_OUT
            #undef PWAIT0
            #undef PMMA
        }
        uint32_t gf[16][4], uf[16][4];
        const uint32_t fo = sb + (warp >> 1) * 2048u + ((lane & 7) + (lane >> 4) * 8) * 64u + (((2 * (warp & 1) + ((lane >> 3) & 1)) ^ ((lane >> 1) & 3)) << 4);
        #define F_LOAD(f, off, i) ldsm4t(f[i], fo + (off) + ((i) >> 1) * 8192u + ((i) & 1) * 1024u)
        #define G_LOAD(lo, n) _Pragma("unroll") for (int i = lo; i < lo + n; i++) F_LOAD(gf, OFF_R0, i)
        #define O_BLOCK(pp, ph0, ph1) do { \
            if ((AWAKE & 2) && !(pp)) mbar_wait_awake(BAR(B_KVT + (pp)), 0); else mbar_wait(BAR(B_KVT + (pp)), 0); \
            if (warp == 0) TS(25 + 3 * (pp)); \
            const uint32_t oa = T128(tid + (lds32(sb + OFF_CST) >> 16)); \
            float o0[20], o1[20]; \
            const uint32_t dk = (pp) ? desc_lo(sb + OFF_KL, OFF_Z + 32 - OFF_KL) : desc_lo(sb + OFF_KVT, OFF_Z - OFF_KVT); \
            constexpr uint32_t K1 = 256u - (255u << 16);          \
            wg_fence(); \
            mma40_rs0<0, H64>(o0, ph0, dk); mma40_rs0<K1, H64>(o1, ph1, dk); \
            mma40_rs<64, H64>(o0, ph0 + 4, dk); mma40_rs<K1 + 64, H64>(o1, ph1 + 4, dk); \
            mma40_rs<128, H64>(o0, ph0 + 8, dk); mma40_rs<K1 + 128, H64>(o1, ph1 + 8, dk); \
            mma40_rs<192, H64>(o0, ph0 + 12, dk); mma40_rs<K1 + 192, H64>(o1, ph1 + 12, dk); \
            wg_commit(); \
            wg_wait<0>(); \
            acc_fence(o0); acc_fence(o1); \
            if (pp) e_arrive(BAR(B_ED)); \
            if (warp == 0) TS(26 + 3 * (pp)); \
              \
            if (pp) { G_LOAD(12, 4); } \
            mbar_wait(BAR(B_GE + (pp)), 0);          \
            uint32_t chk = 0; \
            _Pragma("unroll") for (int hh = 0; hh < 2; hh++) { \
                const float (&o)[20] = hh ? o1 : o0; \
                uint32_t h0, l0, h1, l1; \
                split_rcp(rcp(rbf(rbf(o[16]) + 1e-6f)), h0, l0); split_rcp(rcp(rbf(rbf(o[18]) + 1e-6f)), h1, l1); \
                _Pragma("unroll") for (int q = 0; q < 2; q++) { \
                    const uint32_t r0 = hdiv2(pack2(o[8 * q], o[8 * q + 1]), h0, l0), r1 = hdiv2(pack2(o[8 * q + 2], o[8 * q + 3]), h1, l1); \
                    stsm4((oa ^ ((2 * hh + q) << 5)) + OFF_R0 + (pp) * 16384u, r0, r1, \
                          hdiv2(pack2(o[8 * q + 4], o[8 * q + 5]), h0, l0), hdiv2(pack2(o[8 * q + 6], o[8 * q + 7]), h1, l1)); \
                    chk ^= r0 ^ r1; \
                } \
            } \
            fence_async_smem(); \
            __syncwarp(); \
            e_arrive(BAR(B_OWN + (pp))); \
            sts32(sb + OFF_CHK + (pp) * 32 + warp * 4, __reduce_xor_sync(0xffffffffu, c == (g >> 1) ? chk : 0u)); \
            if (!(pp)) { G_LOAD(4, 8); fence_async_smem(); } \
            __syncwarp(); \
            e_arrive(BAR(B_CS + (pp))); \
            if (warp == 0) TS(27 + 3 * (pp)); \
        } while (0)
        float acc[64];
        const uint32_t da = desc_lo(sb + OFF_R0 + wgi * 8192u, 16), db = desc_lo(sb + OFF_DB, 8192);
        #define D_MMA(first, a, s) do { \
            wg_fence(); \
            first<(a), H128, (s) * 1024, H128>(acc, da, db); mma128_ss<(a) + 2, H128, (s) * 1024 + 128, H128>(acc, da, db); \
            mma128_ss<(a) + 4, H128, (s) * 1024 + 256, H128>(acc, da, db); mma128_ss<(a) + 6, H128, (s) * 1024 + 384, H128>(acc, da, db); \
            wg_commit(); } while (0)
        mbar_wait(BAR(B_GF), 0);
        G_LOAD(0, 4);
        e_arrive(BAR(B_GE));
        O_BLOCK(0, ph[0], ph[1]);
        mbar_wait(BAR(B_OWN), 0);
        mbar_wait(BAR(B_FD), 0);
        D_MMA(mma128_ss0, 0, 0);
        O_BLOCK(1, ph[2], ph[3]);
        reg_inc<232>();
        mbar_wait(BAR(B_OWN + 1), 0);
        #undef O_BLOCK
        #define D_STEP(n) do { \
            mbar_wait(BAR(B_FD + ((n) & 3)), ((n) >> 2) & 1); \
            if (warp == 0) TR(112 + (n)); \
            D_MMA(mma128_ss, (n) == 5 ? OFF_X1 / 16 : ((n) & 3) * 1024, (n) & 3); \
            if ((n) == UPS) mbar_wait(BAR(B_UF), 0); \
            if ((n) >= UPS && (n) < UPS + 2) { _Pragma("unroll") for (int i = 0; i < 4; i++) F_LOAD(uf, OFF_F2, 4 * (((n) - UPS) & 1) + i); } \
            wg_wait<1>(); \
            if ((n) == UPS + 2) fence_async_smem();         \
            if ((n) > 2) e_arrive(BAR(B_ED + (((n) + 3) & 3))); } while (0)
        D_STEP(1);
        wg_wait<0>();
        e_arrive(BAR(B_ED + 1));
        D_STEP(2);
        if (warp == 0) TS(31);
        D_STEP(3); D_STEP(4); D_STEP(5); D_STEP(6); D_STEP(7); D_STEP(8); D_STEP(9); D_STEP(10); D_STEP(11); D_STEP(12); D_STEP(13); D_STEP(14); D_STEP(15);
        #undef D_STEP
        #undef D_MMA
        mbar_wait(BAR(B_PAR), 0);
        const uint4 mis = lds128(sb + OFF_CHK + 128);
        if (mis.x ^ mis.y ^ mis.z ^ mis.w) {
            const uint2 rt = lds64(sb + OFF_CST);
            const int rb = (rt.x >> 3) & 15;
            wg_wait<0>();
            poll_flags(FLO(2, rb * 8 + (lane & 7)), rt.y);
            #pragma unroll 1
            for (int kb = 0; kb < 16; kb++) {
                bar_sync(1, 256);
                if (warp == 0) {
                    e_arrive_tx(BAR(B_RD), 32768);
                    bulk_load(sb + OFF_R0 + 32768, p.s->os + (size_t)(rb * 16 + kb) * 1024, 16384, BAR(B_RD));
                    tma_load4(sb + OFF_DB + 32768, &tmWo, kb * 64, (rt.x & 7) * 2, BAR(B_RD));
                }
                mbar_wait(BAR(B_RD), kb & 1);
                wg_fence();
                mma128_ssp<2048, H128, 2048, H128>(acc, da, db, kb); mma128_ss<2050, H128, 2048 + 128, H128>(acc, da, db);
                mma128_ss<2052, H128, 2048 + 256, H128>(acc, da, db); mma128_ss<2054, H128, 2048 + 384, H128>(acc, da, db);
                wg_commit();
                wg_wait<0>();
            }
        }
        #define XADDR(i) ((xa ^ (((i) & 3) << 5)) + ((i) < 4 ? OFF_R0 : OFF_X1))
        const uint4 cst = lds128(sb + OFF_CST);
        const int b = cst.x & 255;
        const uint32_t tag = cst.y, xa = T128(tid + (cst.x >> 16));
        uint4 w[4];
        const uint32_t rl = warp * 16 + g + 8 * (c & 1);
        const uint4* ws = pin_ptr(p.s->llln2 + ((b & ~7) + (c >> 1) * 4) * 128 + rl);
        {
        {
            uint32_t x2[8][4];
            mbar_wait(BAR(B_WPHI), 1);
            #pragma unroll
            for (int i = 0; i < 8; i++) ldsm4(x2[i], XADDR(i));
            uint4* d = pin_ptr(p.s->llln2 + b * 128 + warp * 16 + g);
            const uint32_t ta = sb + OFF_T1 + (g & 1) * 512 + c * 16;
            uint4 t = lds128(ta), tn = lds128(ta + 64);
            wg_wait<0>();
            acc_fence(acc);
            e_arrive(BAR(B_ED + 3));
            if (warp == 0) TS(32);
            float sd[4] = {0.f, 0.f, 0.f, 0.f}, qa[4] = {0.f, 0.f, 0.f, 0.f}, qb[4] = {0.f, 0.f, 0.f, 0.f};
            #pragma unroll
            for (int i = 0; i < 8; i++) {
                x2[i][0] = hadd2(x2[i][0], hmul2(t.x, pack2(acc[8 * i], acc[8 * i + 1]))); x2[i][1] = hadd2(x2[i][1], hmul2(t.x, pack2(acc[8 * i + 2], acc[8 * i + 3])));
                x2[i][2] = hadd2(x2[i][2], hmul2(t.y, pack2(acc[8 * i + 4], acc[8 * i + 5]))); x2[i][3] = hadd2(x2[i][3], hmul2(t.y, pack2(acc[8 * i + 6], acc[8 * i + 7])));
                mma16816(sd, x2[i][0], x2[i][1], x2[i][2], x2[i][3], t.z, t.w);
                t = tn;
                if (i < 6) tn = lds128(ta + (i + 2) * 64);
                mma16816(qa, x2[i][0], x2[i][1], x2[i][2], x2[i][3], x2[i][0], x2[i][2]);
                mma16816(qb, x2[i][0], x2[i][1], x2[i][2], x2[i][3], x2[i][1], x2[i][3]);
            }
            if (c == (g >> 1)) {
                st_ll(d, f2u(sd[0]), f2u((g & 1) ? qa[1] : qa[0]), f2u(sd[1]), tag);
                st_ll(d + 8, f2u(sd[2]), f2u((g & 1) ? qb[3] : qb[2]), f2u(sd[3]), tag);
            }
            __syncwarp();
            #pragma unroll
            for (int i = 0; i < 4; i++) w[i] = ld_ll(ws + i * 128);
            if (warp == 0) TS(33);
            #pragma unroll
            for (int i = 0; i < 8; i++) stsm4(XADDR(i), x2[i][0], x2[i][1], x2[i][2], x2[i][3]);
        }
        uint4 t2[8]; uint2 t3[8];
        #pragma unroll
        for (int i = 0; i < 8; i++) { t2[i] = lds128(sb + OFF_T2 + i * 64 + c * 16); t3[i] = lds64(sb + OFF_T3 + i * 32 + c * 8); }
        mbar_wait(BAR(B_ED + 3), 1);
        {
            #pragma unroll 1
            for (int it = 0; it < POLL_MAX; it++) {
                if (__all_sync(0xffffffffu, !(tag_bad(w[0].w ^ tag, w[1].w, tag) | tag_bad(w[2].w ^ tag, w[3].w, tag)))) break;
                #pragma unroll
                for (int i = 0; i < 4; i++) if (w[i].w != tag) w[i] = ld_ll(ws + i * 128);
            }
            float s1 = (u2f(w[0].x) + u2f(w[1].x)) + (u2f(w[2].x) + u2f(w[3].x));
            float s2 = (u2f(w[0].y) + u2f(w[1].y)) + (u2f(w[2].y) + u2f(w[3].y));
            float dt = (u2f(w[0].z) + u2f(w[1].z)) + (u2f(w[2].z) + u2f(w[3].z));
            s1 += shfl_x(s1, 2); s2 += shfl_x(s2, 2); dt += shfl_x(dt, 2);
            uint32_t m2, rh, rl2; float rinv;
            ln_final(s1, s2, m2, rinv);
            const uint32_t key = (f2key(fmaf(fmaf(-bf_lo(m2), u2f(cst.z), dt), rinv, u2f(cst.w))) | 2047u) ^ ((b >> 3) * 128 + rl);
            split_rcp(rinv, rh, rl2);
            if (c < 2) { sts32(sb + OFF_KEY + rl * 4, key); sts128(sb + OFF_ST2 + rl * 16, make_uint4(m2, rh, rl2, 0)); }
            __syncwarp();
            e_arrive(BAR(B_KEYS));
        }
        if (warp == 0) TS(34);
        {
            const uint4 s0 = lds128(sb + OFF_ST2 + (warp * 16 + g) * 16), s1 = lds128(sb + OFF_ST2 + (warp * 16 + g + 8) * 16);
            uint32_t x2[8][4];
            #pragma unroll
            for (int i = 0; i < 8; i++) ldsm4(x2[i], XADDR(i));
            const uint32_t oa = xa + warp * 2048u;
            #pragma unroll
            for (int i = 0; i < 8; i++) {
                const uint4 t = t2[i]; const uint2 gb = t3[i];
                stsm4((oa ^ ((i & 3) << 5)) + OFF_OUT + (i >> 2) * 2048u,
                      hadd2(x2[i][0], hmul2(gb.x, lnmod(x2[i][0], s0.x, s0.y, s0.z, t.x, t.z))), hadd2(x2[i][1], hmul2(gb.x, lnmod(x2[i][1], s1.x, s1.y, s1.z, t.x, t.z))),
                      hadd2(x2[i][2], hmul2(gb.y, lnmod(x2[i][2], s0.x, s0.y, s0.z, t.y, t.w))), hadd2(x2[i][3], hmul2(gb.y, lnmod(x2[i][3], s1.x, s1.y, s1.z, t.y, t.w))));
            }
            __syncwarp();
            e_arrive(BAR(B_SWP));
        }
        }
        #undef XADDR
        if (warp == 0) TS(35);
        uint32_t fx = 0, fh = 0, fg = 0, fs2, frow;
        uint32_t df[16][4];
        const uint32_t dfo = sb + warp * 4096u + ((lane & 7) + (lane >> 4) * 8) * 128u + ((((lane >> 3) & 1) ^ (lane & 7)) << 4);
        #define DF_LOAD(i) ldsm4t(df[i], (dfo + ((i) < 8 ? OFF_F2 : OFF_DB) + ((i) & 1) * 2048u) ^ ((((i) >> 1) & 3) << 5))
        {
            const int wi = ((tid >> 3) & 7) * 32 + (tid >> 6) * 8 + (tid & 7);
            const uint4* rh = pin_ptr(p.s->llrowh + wi);
            #pragma unroll
            for (int i = 8; i < 16; i++) F_LOAD(uf, OFF_U1 - 32768, i);
            mbar_wait(BAR(B_SEL) + ((AWAKE & 4) ? awake_zero() : 0), 0);
            const uint2 bb = lds64(sb + OFF_CST + 24);
            const uint32_t b0 = bb.x, b1 = bb.y;
            if (warp == 0) TS(36);
            const uint32_t o0 = (~b0 & 0x780u) * 4, o1 = (~b1 & 0x780u) * 4, slot0 = o0, slot1 = o1 + (o0 == o1 ? 256 : 0);
            const int wd = ((g & 1) ? slot1 : slot0) + b * 2 + (c >> 1) - wi;
            uint4 hv[2], fv[2];
            #pragma unroll 1
            for (int it = 0; it < POLL_MAX; it++) {
                hv[0] = ld_ll(rh + slot0); hv[1] = ld_ll(rh + slot1);
                uint32_t bad = 0;
                if (warp == 0) {
                    fv[0] = ld_ll(rh + wd + 8192); fv[1] = ld_ll(rh + wd);
                    bad = tag_bad(fv[0].w ^ tag, fv[1].w, tag);
                    fx = (g & 2) ? fv[0].y : fv[0].x; fh = (g & 2) ? fv[1].y : fv[1].x; fg = (g & 2) ? fv[0].z : fv[1].z;
                }
                if (it == 0) {
                    mbar_wait(BAR(B_WD), 0);
                    #pragma unroll
                    for (int i = 0; i < NDF; i++) DF_LOAD(i);
                }
                if (__all_sync(0xffffffffu, !ll_bad<1>(ll_bad<1>(bad, hv[0], tag), hv[1], tag))) break;
            }
            const uint32_t ha = sb + OFF_HSEL + (tid >> 3) * 128u + c * 16u + (g & 1) * 8u;
            sts64(ha, hv[0].x, hv[0].y); sts64(ha + 64, hv[1].x, hv[1].y);
            bar_sync(2 + (warp >> 1), 64);
            const uint32_t bk = (g & 1) ? b1 : b0;
            frow = ~bk & 2047u;
            const float sg = sigmoid_f(rbf(key2f((bk & ~2047u) | 1024u)));
            fs2 = pack2(sg, sg);
        }
        if (warp == 0) TS(37);
        uint4* yd = p.s->lly + (cst.x >> 8) * 512 + (warp * 8 + c) * 8 + g;
        const uint4* ys = p.s->lly + (tid >> 2) * 512 + b * 4 + c;
        uint16_t* od = (uint16_t*)p.out + (size_t)frow * 1024 + (b >> 1) * 16 + (b & 1) * 4 + c + 8 * (g >> 1);
        {
            float ag[2][4], au[2][4];
            #pragma unroll
            for (int i = 0; i < 4; i++) ag[0][i] = ag[1][i] = au[0][i] = au[1][i] = 0.f;
            const uint32_t ha = sb + OFF_HSEL + (warp >> 1) * 1024u + (lane & 7) * 16u;
            uint4 hn = lds128(ha), hm = lds128(ha + 128);
            #pragma unroll
            for (int i = 0; i < 8; i++) {
                const uint4 h = hn;
                hn = hm;
                if (i < 6) hm = lds128(ha + (i + 2) * 128u);
                mma16816(ag[0], gf[2 * i][0], gf[2 * i][1], gf[2 * i][2], gf[2 * i][3], h.x, h.y);
                mma16816(au[0], uf[2 * i][0], uf[2 * i][1], uf[2 * i][2], uf[2 * i][3], h.x, h.y);
                mma16816(ag[1], gf[2 * i + 1][0], gf[2 * i + 1][1], gf[2 * i + 1][2], gf[2 * i + 1][3], h.z, h.w);
                mma16816(au[1], uf[2 * i + 1][0], uf[2 * i + 1][1], uf[2 * i + 1][2], uf[2 * i + 1][3], h.z, h.w);
                if (NDF + 2 * i < 16) { DF_LOAD((NDF + 2 * i) & 15); DF_LOAD((NDF + 2 * i + 1) & 15); }
            }
            sts64(sb + OFF_RED + (warp >> 1) * 512u + (c & 1) * 256u + ((warp & 1) * 16 + (c >> 1) * 8 + g) * 8u,
                  f2u(sel4(c, ag[0][0], ag[0][1], ag[0][2], ag[0][3]) + sel4(c, ag[1][0], ag[1][1], ag[1][2], ag[1][3])),
                  f2u(sel4(c, au[0][0], au[0][1], au[0][2], au[0][3]) + sel4(c, au[1][0], au[1][1], au[1][2], au[1][3])));
        }
        yd = pin_ptr(yd); ys = pin_ptr(ys); od = pin_ptr(od); pin<1>(&fs2);
        bar_sync(1, 256);
        {
            const uint32_t ra = sb + OFF_RED + lane * 16u;
            const uint4 r0 = lds128(ra), r1 = lds128(ra + 512), r2 = lds128(ra + 1024), r3 = lds128(ra + 1536);
            #define F4(f) ((u2f(r0.f) + u2f(r1.f)) + (u2f(r2.f) + u2f(r3.f)))
            const uint32_t hid = hmul2(silu2(pack2(F4(x), F4(z))), pack2(F4(y), F4(w)));
            #undef F4
            if (warp == 0) TS(38);
            const int src = (g & 1) * 16 + c;
            const uint32_t b0 = __shfl_sync(0xffffffffu, hid, src), b1 = __shfl_sync(0xffffffffu, hid, src + 4), b2 = __shfl_sync(0xffffffffu, hid, src + 8), b3 = __shfl_sync(0xffffffffu, hid, src + 12);
            float y[8][4];
            #pragma unroll
            for (int i = 0; i < 8; i++) {
                y[i][0] = y[i][1] = y[i][2] = y[i][3] = 0.f;
                mma16816(y[i], df[2 * i][0], df[2 * i][1], df[2 * i][2], df[2 * i][3], b0, b1);
            }
            #pragma unroll
            for (int i = 0; i < 8; i++) mma16816(y[i], df[2 * i + 1][0], df[2 * i + 1][1], df[2 * i + 1][2], df[2 * i + 1][3], b2, b3);
            if (cst.x < 112 * 256) {
                #pragma unroll
                for (int h = 0; h < 2; h++) {
                    #define YS(e) sel4(c, y[4 * h][e], y[4 * h + 1][e], y[4 * h + 2][e], y[4 * h + 3][e])
                    st_ll4(yd + 32 * h, YS(0), YS(1), YS(2), YS(3), tag);
                    #undef YS
                }
            }
        }
        if (warp == 0) TS(39);
        if (warp < 7) {
            uint4 v[2];
            v[0].w = v[1].w = 0;
            spin_until(clk32() + YWAIT);
            #pragma unroll 1
            for (int it = 0; it < POLL_MAX; it++) {
                if ((v[0].w ^ tag) & 3) v[0] = ld_ll(ys);
                if ((v[1].w ^ tag) & 3) v[1] = ld_ll(ys + 56 * 512);
                if (__all_sync(0xffffffffu, !(tag_bad(v[0].w ^ tag, v[1].w, tag) & 3))) break;
            }
            float y0 = u2f(v[0].x) + u2f(v[1].x), y1 = u2f(v[0].y) + u2f(v[1].y), y2 = u2f(v[0].z) + u2f(v[1].z), y3 = u2f(v[0].w) + u2f(v[1].w);
            const bool g0 = g & 1, g1 = g & 2;
            const float k0 = (g0 ? y1 : y0) + shfl_x(g0 ? y0 : y1, 4), k1 = (g0 ? y3 : y2) + shfl_x(g0 ? y2 : y3, 4);
            const float y = (g1 ? k1 : k0) + shfl_x(g1 ? k0 : k1, 8);
            stsf(sb + OFF_RED2 + (lane & 15) * 64u + (lane >> 4) * 32u + warp * 4u, y);
            bar_sync(6, 224);
            if (tid < 16) {
                const uint32_t a = sb + OFF_RED2 + lane * 64u;
                const uint4 ya = lds128(a), yb = lds128(a + 16), yc = lds128(a + 32), ye = lds128(a + 48);
                const float s = (((u2f(ya.x) + u2f(ya.y)) + (u2f(ya.z) + u2f(ya.w))) + ((u2f(yb.x) + u2f(yb.y)) + u2f(yb.z)))
                              + (((u2f(yc.x) + u2f(yc.y)) + (u2f(yc.z) + u2f(yc.w))) + ((u2f(ye.x) + u2f(ye.y)) + u2f(ye.z)));
                const uint32_t o = hadd2(fx, hmul2(fg, hadd2(fh, hmul2(pack2(s, s), fs2))));
                *od = (c & 1) ? o >> 16 : o;
                if (b == 0 && tid == 0) p.s->done[0] = tag;
                TS(40);
            }
        }
    }
}

typedef CUresult (*EncodeFn)(CUtensorMap*, CUtensorMapDataType, cuuint32_t, void*, const cuuint64_t*, const cuuint64_t*, const cuuint32_t*,
                             const cuuint32_t*, CUtensorMapInterleave, CUtensorMapSwizzle, CUtensorMapL2promotion, CUtensorMapFloatOOBfill);

CUtensorMap make_map(EncodeFn enc, const void* ptr, uint64_t cols, uint64_t rows, uint32_t bc, uint32_t br, CUtensorMapSwizzle swz, CUtensorMapL2promotion promo) {
    CUtensorMap m;
    cuuint64_t dims[2] = {cols, rows}, strides[1] = {cols * 2};
    cuuint32_t box[2] = {bc, br}, es[2] = {1, 1};
    enc(&m, CU_TENSOR_MAP_DATA_TYPE_BFLOAT16, 2, const_cast<void*>(ptr), dims, strides, box, es, CU_TENSOR_MAP_INTERLEAVE_NONE, swz, promo,
        CU_TENSOR_MAP_FLOAT_OOB_FILL_NONE);
    return m;
}
CUtensorMap make_map4(EncodeFn enc, const void* ptr, uint32_t groups, uint64_t rows, uint32_t br, CUtensorMapL2promotion promo) {
    CUtensorMap m;
    cuuint64_t dims[4] = {64, rows, 16, groups}, strides[3] = {groups * 2048ull, 128, 2048};
    cuuint32_t box[4] = {64, br, 2, groups}, es[4] = {1, 1, 1, 1};
    enc(&m, CU_TENSOR_MAP_DATA_TYPE_BFLOAT16, 4, const_cast<void*>(ptr), dims, strides, box, es, CU_TENSOR_MAP_INTERLEAVE_NONE, CU_TENSOR_MAP_SWIZZLE_128B, promo,
        CU_TENSOR_MAP_FLOAT_OOB_FILL_NONE);
    return m;
}

}

extern "C" void kernel_launch(void* const* d_in, const int* in_sizes, int n_in, void* d_out, int out_size) {
    (void)in_sizes; (void)n_in; (void)out_size;
    void* fn = nullptr; cudaDriverEntryPointQueryResult qr;
    cudaGetDriverEntryPoint("cuTensorMapEncodeTiled", &fn, cudaEnableDefault, &qr);
    EncodeFn enc = (EncodeFn)fn;
    void* hs = nullptr;
    cudaGetSymbolAddress(&hs, g_scratch);
    int dev = 0, sms = 0;
    cudaGetDevice(&dev);
    cudaDeviceGetAttribute(&sms, cudaDevAttrMultiProcessorCount, dev);
    const CUtensorMapL2promotion P256 = CU_TENSOR_MAP_L2_PROMOTION_L2_256B, P128 = CU_TENSOR_MAP_L2_PROMOTION_L2_128B, P0 = CU_TENSOR_MAP_L2_PROMOTION_NONE;
    CUtensorMap tmW = make_map4(enc, d_in[1], 3, 1024, 32, P256);
    CUtensorMap tmWo = make_map4(enc, d_in[3], 1, 1024, 64, P256);
    CUtensorMap tmO = make_map4(enc, d_out, 1, 2048, 16, P0);
    CUtensorMap tmPhi = make_map(enc, d_in[2], 32, 1024, 32, 128, CU_TENSOR_MAP_SWIZZLE_64B, P128);
    CUtensorMap tmG = make_map(enc, d_in[6], 3584, 1024, 32, 128, CU_TENSOR_MAP_SWIZZLE_64B, P0);
    CUtensorMap tmU = make_map(enc, d_in[7], 3584, 1024, 32, 128, CU_TENSOR_MAP_SWIZZLE_64B, P0);
    CUtensorMap tmD = make_map(enc, d_in[8], 1024, 3584, 64, 32, CU_TENSOR_MAP_SWIZZLE_128B, P128);
    CUtensorMap tmX = make_map(enc, d_in[0], 1024, 2048, 64, 128, CU_TENSOR_MAP_SWIZZLE_128B, P128);
    CUtensorMap tmM = make_map(enc, d_in[10], 6144, 1024, 64, 256, CU_TENSOR_MAP_SWIZZLE_128B, MPROMO);
    Ptrs p;
    p.x = (const bf16*)d_in[0]; p.c = (const bf16*)d_in[9]; p.wmod = (const bf16*)d_in[10]; p.wr = (const bf16*)d_in[5];
    p.wg = (const bf16*)d_in[6]; p.wu = (const bf16*)d_in[7]; p.wd = (const bf16*)d_in[8]; p.out = (bf16*)d_out; p.s = (Scratch*)hs;
    p.wqkv = (const bf16*)d_in[1]; p.wo = (const bf16*)d_in[3];
    p.by_sm = sms == 132;
    for (int sm = 0; sm < 132; sm++) {
        const int tp = sm >> 1, u = tp - 32;
        const int gp = (GPERM >> (4 * (tp < 32 ? tp & 7 : tp < 60 ? 1 + u % 7 : 0))) & 7, sl = 2 * (tp < 32 ? tp >> 3 : tp < 60 ? 4 + u / 7 : tp - 58) + (sm & 1);
        const int b = (tp >> 1) == 30 ? sm + 8 : ((gp >> 1) * 4 + (sl & 3)) * 8 + (gp & 1) * 4 + (sl >> 2);
        const int f = FMODE == 0 ? (b < 112 ? b : 255) : FMODE == 1 ? (sl < 14 && b < 128 ? gp * 14 + sl : 255) : (sm < 112 ? sm : 255);
        p.role[sm] = (uint16_t)(b | f << 8);
    }
    cudaFuncSetAttribute(fused_kernel, cudaFuncAttributeMaxDynamicSharedMemorySize, SMEM_BYTES);
    fused_kernel<<<132, NTHREADS, SMEM_BYTES, cudaStreamPerThread>>>(p, tmM, tmX, tmW, tmWo, tmPhi, tmG, tmU, tmD, tmO);
}
```

```cpp
#include <cuda_runtime.h>
#include <cuda.h>
#include <cuda_bf16.h>
#include <stdint.h>

namespace {

typedef __nv_bfloat16 bf16;

#define NFREE 4
constexpr int NTHREADS = 512;
constexpr int POLL_MAX = 400000;

constexpr uint32_t OFF_R0   = 0;
constexpr uint32_t OFF_A    = 65536;
constexpr uint32_t OFF_B    = 114688;
constexpr uint32_t OFF_U1   = 65536;
constexpr uint32_t OFF_PHI  = 98304;
constexpr uint32_t OFF_F2   = OFF_PHI;
constexpr uint32_t OFF_DB   = 131072;
constexpr uint32_t OFF_V    = 163840;
constexpr uint32_t OFF_KL1  = OFF_V;
constexpr uint32_t OFF_KL   = 196608;
constexpr uint32_t OFF_WPHI = 214016;
constexpr uint32_t OFF_KVT  = OFF_WPHI;
constexpr uint32_t OFF_Z    = 222208;
constexpr uint32_t OFF_TAB  = OFF_Z;
constexpr uint32_t OFF_ONES = 226304;
constexpr uint32_t OFF_BAR  = 227328;
constexpr uint32_t OFF_CST  = OFF_BAR + 640;
constexpr uint32_t OFF_T1   = OFF_ONES;
constexpr uint32_t OFF_T2   = OFF_CST + 64;
constexpr uint32_t OFF_T3   = OFF_T2 + 512;
constexpr uint32_t OFF_KEY  = OFF_T3 + 256;
constexpr uint32_t OFF_ST2  = OFF_KEY + 512;
constexpr uint32_t OFF_CHK  = OFF_KEY;
constexpr uint32_t OFF_ZS   = OFF_ST2;
constexpr uint32_t SMEM_BYTES = 232448;
constexpr uint32_t OFF_X1   = OFF_KL;
constexpr uint32_t OFF_OUT  = OFF_R0 + 32768;
constexpr uint32_t OFF_HSEL = OFF_WPHI;
constexpr uint32_t OFF_RED  = OFF_WPHI + 4096;
constexpr uint32_t OFF_RED2 = OFF_RED + 2048;
static_assert(OFF_ST2 + 2048 <= SMEM_BYTES, "layout");

enum {
    B_O1 = 0, B_UF = 1, B_UD = 2, B_WPHI = 3, B_FB = 4  , B_OST = 8, B_GF = 9, B_WD = 10, B_KVL = 11  , B_KZ = 13, B_LMF = 14, B_SEL = 15, B_XP = 16  , B_TAG = 24,
    B_FA = 25  , B_FD = 30  , B_CAND = 34,
    B_KST = 37  , B_KVT = 41  , B_LMD = 43, B_PAR = 44,
    B_EA = 45  , B_EB = 48  , B_PF = 56  , B_OWN = 60  , B_QE = 62, B_STP = 63, B_KEYS = 64, B_SWP = 65, B_STS = 66, B_GE = 67, B_CS = B_GE + 1  ,
    B_ED = 70  ,
    B_RD = 75
};

struct Scratch {
    uint4 os[16 * 16 * 1024];
    uint4 kvacc[8 * 4 * 528];
    uint4 flk[3 * 128 * 2];
    uint4 llstat[2048];
    uint4 llm1[16 * 64];
    uint4 flo[3 * 128 * 2];
    uint4 llmod2[2 * 256];
    uint4 llg[2 * 4 * 256];
    uint4 llln2[16 * 8 * 128];
    uint4 llcand[16 * 2];
    uint4 llrowh[32 * 256];
    uint4 llrowx[32 * 256];
    uint4 lly[128 * 512];
    unsigned done[4];
};
__device__ __align__(1024) Scratch g_scratch;
#define GT(i) do {} while (0)
#define TS(i) do {} while (0)
#define TR(i) do {} while (0)

__device__ __forceinline__ uint32_t smem_u32(const void* p) { return (uint32_t)__cvta_generic_to_shared(p); }
__device__ __forceinline__ uint32_t clk32() { uint32_t c; asm volatile("mov.u32 %0, %%clock;" : "=r"(c) :: "memory"); return c; }
__device__ __forceinline__ void spin_until(uint32_t t) { while ((int)(clk32() - t) < 0) {} }
__device__ __forceinline__ void sleep_until(uint32_t t) { while ((int)(clk32() - t) < 0) __nanosleep(40); }
__device__ __forceinline__ void mbar_init_fence() { asm volatile("fence.mbarrier_init.release.cluster;" ::: "memory"); }
__device__ __forceinline__ void mbar_wait(uint32_t bar, uint32_t parity) {
    asm volatile("{\n.reg .pred P1;\nLAB_WAIT:\nmbarrier.try_wait.parity.shared::cta.b64 P1, [%0], %1;\n@!P1 bra LAB_WAIT;\n}" :: "r"(bar), "r"(parity) : "memory");
}
__device__ __forceinline__ uint64_t policy_evict_first() { uint64_t p; asm("createpolicy.fractional.L2::evict_first.b64 %0, 1.0;" : "=l"(p)); return p; }
#define ELECT "{\n.reg .pred e;\nelect.sync _|e, 0xffffffff;\n@e "
__device__ __forceinline__ void e_arrive(uint32_t bar) { asm volatile(ELECT "mbarrier.arrive.shared::cta.b64 _, [%0];\n}" :: "r"(bar) : "memory"); }
__device__ __forceinline__ void e_arrive_after(uint32_t bar, uint32_t v) {
    asm volatile("{\n.reg .pred e;\n.reg .b32 n;\npopc.b32 n, %1;\nshr.u32 n, n, 4;\nmul.lo.u32 n, n, n;\nshr.u32 n, n, 3;\nadd.u32 n, n, %0;\n"
        "elect.sync _|e, 0xffffffff;\n@e mbarrier.arrive.shared::cta.b64 _, [n];\n}" :: "r"(bar), "r"(v) : "memory");
}
__device__ __forceinline__ void e_arrive_tx(uint32_t bar, uint32_t bytes) { asm volatile(ELECT "mbarrier.arrive.expect_tx.shared::cta.b64 _, [%0], %1;\n}" :: "r"(bar), "r"(bytes) : "memory"); }
__device__ __forceinline__ void e_init(uint32_t bar, uint32_t cnt) { asm volatile(ELECT "mbarrier.init.shared::cta.b64 [%0], %1;\n}" :: "r"(bar), "r"(cnt) : "memory"); }
__device__ __forceinline__ void tma_load_ef(uint32_t dst, const CUtensorMap* tm, int c0, int c1, uint32_t bar) {
    asm volatile(ELECT "cp.async.bulk.tensor.2d.shared::cluster.global.mbarrier::complete_tx::bytes.L2::cache_hint [%0], [%1, {%3, %4}], [%2], %5;\n}"
        :: "r"(dst), "l"(tm), "r"(bar), "r"(c0), "r"(c1), "l"(policy_evict_first()) : "memory");
}
__device__ __forceinline__ void tma_load(uint32_t dst, const CUtensorMap* tm, int c0, int c1, uint32_t bar) {
    asm volatile(ELECT "cp.async.bulk.tensor.2d.shared::cluster.global.mbarrier::complete_tx::bytes [%0], [%1, {%3, %4}], [%2];\n}"
        :: "r"(dst), "l"(tm), "r"(bar), "r"(c0), "r"(c1) : "memory");
}
__device__ __forceinline__ void tma_load4(uint32_t dst, const CUtensorMap* tm, int row, int blk, uint32_t bar) {
    asm volatile(ELECT "cp.async.bulk.tensor.4d.shared::cluster.global.mbarrier::complete_tx::bytes [%0], [%1, {0, %3, %4, 0}], [%2];\n}"
        :: "r"(dst), "l"(tm), "r"(bar), "r"(row), "r"(blk) : "memory");
}
__device__ __forceinline__ void tma_store4(const CUtensorMap* tm, int row, int blk, uint32_t src) {
    asm volatile(ELECT "cp.async.bulk.tensor.4d.global.shared::cta.bulk_group [%0, {0, %2, %3, 0}], [%1];\n}" :: "l"(tm), "r"(src), "r"(row), "r"(blk) : "memory");
}
__device__ __forceinline__ void bulk_load(uint32_t dst, const void* src, uint32_t bytes, uint32_t bar) {
    asm volatile(ELECT "cp.async.bulk.shared::cluster.global.mbarrier::complete_tx::bytes [%0], [%1], %2, [%3];\n}" :: "r"(dst), "l"(src), "r"(bytes), "r"(bar) : "memory");
}
__device__ __forceinline__ void bulk_store(void* dst, uint32_t src, uint32_t bytes) {
    asm volatile(ELECT "cp.async.bulk.global.shared::cta.bulk_group [%0], [%1], %2;\n}" :: "l"(dst), "r"(src), "r"(bytes) : "memory");
}
__device__ __forceinline__ void bulk_reduce(void* dst, uint32_t src, uint32_t bytes) {
    asm volatile(ELECT "cp.reduce.async.bulk.global.shared::cta.bulk_group.add.f32 [%0], [%1], %2;\n}" :: "l"(dst), "r"(src), "r"(bytes) : "memory");
}
__device__ __forceinline__ void tma_prefetch(const CUtensorMap* tm, int c0, int c1) {
    asm volatile(ELECT "cp.async.bulk.prefetch.tensor.2d.L2.global [%0, {%1, %2}];\n}" :: "l"(tm), "r"(c0), "r"(c1) : "memory");
}
__device__ __forceinline__ void l2_prefetch(const void* p, uint32_t bytes) {
    asm volatile(ELECT "cp.async.bulk.prefetch.L2.global [%0], %1;\n}" :: "l"(p), "r"(bytes) : "memory");
}
__device__ __forceinline__ void bulk_wait_read() { asm volatile("cp.async.bulk.commit_group;\ncp.async.bulk.wait_group.read 0;" ::: "memory"); }
__device__ __forceinline__ void bulk_wait() { asm volatile("cp.async.bulk.commit_group;\ncp.async.bulk.wait_group 0;" ::: "memory"); }
__device__ __forceinline__ void tmap_prefetch(const CUtensorMap* tm) { asm volatile("prefetch.tensormap [%0];" :: "l"(tm) : "memory"); }
__device__ __forceinline__ void wg_fence() { asm volatile("wgmma.fence.sync.aligned;" ::: "memory"); }
__device__ __forceinline__ void wg_commit() { asm volatile("wgmma.commit_group.sync.aligned;" ::: "memory"); }
template<int N> __device__ __forceinline__ void wg_wait() { asm volatile("wgmma.wait_group.sync.aligned %0;" :: "n"(N) : "memory"); }
template<int N> __device__ __forceinline__ void acc_fence(float (&d)[N]) {
    #pragma unroll
    for (int i = 0; i < N; i++) asm volatile("" : "+f"(d[i]) :: "memory");
}
__device__ __forceinline__ uint32_t desc_lo(uint32_t addr, uint32_t lbo) { return (addr >> 4) | ((lbo >> 4) << 16); }
constexpr uint32_t H128 = 0x40000040u;
constexpr uint32_t H64 = 0x80000020u;
__device__ __forceinline__ void fence_async_smem() { asm volatile("fence.proxy.async.shared::cta;" ::: "memory"); }
__device__ __forceinline__ void bar_sync(int id, int n) { asm volatile("bar.sync %0, %1;" :: "r"(id), "r"(n) : "memory"); }
template<int R> __device__ __forceinline__ void reg_inc() { asm volatile("setmaxnreg.inc.sync.aligned.u32 %0;" :: "n"(R)); }
template<int R> __device__ __forceinline__ void reg_dec() { asm volatile("setmaxnreg.dec.sync.aligned.u32 %0;" :: "n"(R)); }

__device__ __forceinline__ void stsm4(uint32_t addr, uint32_t r0, uint32_t r1, uint32_t r2, uint32_t r3) {
    asm volatile("stmatrix.sync.aligned.m8n8.x4.shared.b16 [%0], {%1,%2,%3,%4};" :: "r"(addr), "r"(r0), "r"(r1), "r"(r2), "r"(r3) : "memory");
}
__device__ __forceinline__ void ldsm4(uint32_t* r, uint32_t addr) {
    asm volatile("ldmatrix.sync.aligned.m8n8.x4.shared.b16 {%0,%1,%2,%3}, [%4];" : "=r"(r[0]), "=r"(r[1]), "=r"(r[2]), "=r"(r[3]) : "r"(addr) : "memory");
}
__device__ __forceinline__ void ldsm4t(uint32_t* r, uint32_t addr) {
    asm volatile("ldmatrix.sync.aligned.m8n8.x4.trans.shared.b16 {%0,%1,%2,%3}, [%4];" : "=r"(r[0]), "=r"(r[1]), "=r"(r[2]), "=r"(r[3]) : "r"(addr) : "memory");
}
__device__ __forceinline__ void mma16816(float (&d)[4], uint32_t a0, uint32_t a1, uint32_t a2, uint32_t a3, uint32_t b0, uint32_t b1) {
    asm volatile("mma.sync.aligned.m16n8k16.row.col.f32.bf16.bf16.f32 {%0,%1,%2,%3}, {%4,%5,%6,%7}, {%8,%9}, {%0,%1,%2,%3};"
        : "+f"(d[0]), "+f"(d[1]), "+f"(d[2]), "+f"(d[3]) : "r"(a0), "r"(a1), "r"(a2), "r"(a3), "r"(b0), "r"(b1));
}
__device__ __forceinline__ uint32_t awake_zero() {
    uint32_t r;
    asm volatile("{\n.reg .f32 d<4>;\nmma.sync.aligned.m16n8k8.row.col.f32.bf16.bf16.f32 {d0,d1,d2,d3}, {%1,%1}, {%1}, {%2,%2,%2,%2};\nmov.b32 %0, d0;\n}" : "=r"(r) : "r"(0), "f"(0.f));
    return r;
}
__device__ __forceinline__ void mbar_wait_awake(uint32_t bar, uint32_t parity) {
    #pragma unroll 1
    for (int it = 0; it < POLL_MAX; it++) {
        uint32_t ok;
        asm volatile("{\n.reg .pred p;\nmbarrier.try_wait.parity.shared::cta.b64 p, [%1], %2;\nselp.u32 %0, 0, 1, p;\n}" : "=r"(ok) : "r"(bar), "r"(parity) : "memory");
        if (__all_sync(0xffffffffu, ok == 0)) break;
        it += awake_zero();
    }
}
__device__ __forceinline__ uint4 lds128(uint32_t a) { uint4 v; asm volatile("ld.shared.v4.b32 {%0,%1,%2,%3}, [%4];" : "=r"(v.x), "=r"(v.y), "=r"(v.z), "=r"(v.w) : "r"(a) : "memory"); return v; }
__device__ __forceinline__ uint32_t lds32(uint32_t a) { uint32_t v; asm volatile("ld.shared.b32 %0, [%1];" : "=r"(v) : "r"(a) : "memory"); return v; }
__device__ __forceinline__ uint2 lds64(uint32_t a) { uint2 v; asm volatile("ld.shared.v2.b32 {%0,%1}, [%2];" : "=r"(v.x), "=r"(v.y) : "r"(a) : "memory"); return v; }
__device__ __forceinline__ float ldsf(uint32_t a) { float v; asm volatile("ld.shared.f32 %0, [%1];" : "=f"(v) : "r"(a) : "memory"); return v; }
__device__ __forceinline__ void sts128(uint32_t a, uint4 v) { asm volatile("st.shared.v4.b32 [%0], {%1,%2,%3,%4};" :: "r"(a), "r"(v.x), "r"(v.y), "r"(v.z), "r"(v.w) : "memory"); }
__device__ __forceinline__ void sts64(uint32_t a, uint32_t x, uint32_t y) { asm volatile("st.shared.v2.b32 [%0], {%1,%2};" :: "r"(a), "r"(x), "r"(y) : "memory"); }
__device__ __forceinline__ void sts32(uint32_t a, uint32_t x) { asm volatile("st.shared.b32 [%0], %1;" :: "r"(a), "r"(x) : "memory"); }
__device__ __forceinline__ void stsf(uint32_t a, float x) { asm volatile("st.shared.f32 [%0], %1;" :: "r"(a), "f"(x) : "memory"); }
__device__ __forceinline__ float u2f(uint32_t v) { return __uint_as_float(v); }
__device__ __forceinline__ uint32_t f2u(float v) { return __float_as_uint(v); }

__device__ __forceinline__ uint32_t ldg32(const void* p) { uint32_t v; asm volatile("ld.global.nc.b32 %0, [%1];" : "=r"(v) : "l"(p)); return v; }
__device__ __forceinline__ void stg128(void* p, uint4 v) { asm volatile("st.global.v4.b32 [%0], {%1,%2,%3,%4};" :: "l"(p), "r"(v.x), "r"(v.y), "r"(v.z), "r"(v.w) : "memory"); }
__device__ __forceinline__ void stg_zero(void* p) { stg128(p, make_uint4(0, 0, 0, 0)); }
__device__ __forceinline__ void fence_gpu() { asm volatile("fence.release.gpu;" ::: "memory"); }
__device__ __forceinline__ void st_ll(uint4* p, uint32_t x, uint32_t y, uint32_t z, uint32_t w) {
    asm volatile("st.relaxed.gpu.global.v4.b32 [%0], {%1,%2,%3,%4};" :: "l"(p), "r"(x), "r"(y), "r"(z), "r"(w) : "memory");
}
__device__ __forceinline__ uint4 ld_ll(const uint4* p) {
    uint4 v;
    asm volatile("ld.relaxed.gpu.global.v4.b32 {%0,%1,%2,%3}, [%4];" : "=r"(v.x), "=r"(v.y), "=r"(v.z), "=r"(v.w) : "l"(p) : "memory");
    return v;
}
template<uint32_t LUT> __device__ __forceinline__ uint32_t lop3(uint32_t a, uint32_t b, uint32_t c) { uint32_t d; asm("lop3.b32 %0, %1, %2, %3, %4;" : "=r"(d) : "r"(a), "r"(b), "r"(c), "n"(LUT)); return d; }
__device__ __forceinline__ uint32_t tag_bad(uint32_t bad, uint32_t w, uint32_t tag) { return lop3<0xF6>(bad, w, tag); }
__device__ __forceinline__ void st_ll4(uint4* p, float a, float b, float c, float d, uint32_t tag) { st_ll(p, f2u(a), f2u(b), f2u(c), lop3<0xD8>(f2u(d), tag, 3u)); }
__device__ __forceinline__ unsigned ld_rlx(const void* p) { unsigned v; asm volatile("ld.relaxed.gpu.global.u32 %0, [%1];" : "=r"(v) : "l"(p) : "memory"); return v; }
__device__ __forceinline__ void st_flag(uint4* p, uint32_t tag, uint32_t v, int lane) { if (lane < 2) st_ll(p + lane, tag, v, tag, v); }
__device__ __forceinline__ uint2 ld_flag(const uint4* p) { uint2 v; asm volatile("ld.relaxed.gpu.global.v2.b32 {%0,%1}, [%2];" : "=r"(v.x), "=r"(v.y) : "l"(p) : "memory"); return v; }
__device__ __forceinline__ uint32_t poll_flags(const uint4* f, uint32_t tag) {
    uint2 v = make_uint2(0, 0);
    #pragma unroll 1
    for (int it = 0; it < POLL_MAX; it++) {
        if (v.x != tag) v = ld_flag(f);
        if (__all_sync(0xffffffffu, v.x == tag)) break;
    }
    return v.y;
}
template<int Z> __device__ __forceinline__ uint32_t ll_bad(uint32_t bad, const uint4& v, uint32_t tag) {
    bad = tag_bad(bad, v.w, tag);
    return Z && lop3<0x80>(v.x, v.y, v.z) == ~0u ? 1u : bad;
}
template<int N, int Z, uint32_t M = ~0u, int AW = 0> __device__ __forceinline__ void poll_words(uint4 (&v)[N], const uint4* p, int stride, uint32_t tag) {
    #pragma unroll 1
    for (int it = 0; it < POLL_MAX; it++) {
        uint32_t bad = 0;
        #pragma unroll
        for (int i = 0; i < N; i++) v[i] = ld_ll(p + i * stride);
        #pragma unroll
        for (int i = 0; i < N; i++) bad = ll_bad<Z>(bad, v[i], tag);
        if (__all_sync(0xffffffffu, !(bad & M))) break;
        if (AW) it += awake_zero();
    }
}
constexpr uint32_t ONE2 = 0x3F803F80u;
__device__ __forceinline__ uint32_t pack2(float lo, float hi) { uint32_t d; asm("cvt.rn.bf16x2.f32 %0, %1, %2;" : "=r"(d) : "f"(hi), "f"(lo)); return d; }
__device__ __forceinline__ float bf_lo(uint32_t v) { return u2f(v << 16); }
__device__ __forceinline__ float bf_hi(uint32_t v) { return u2f(v & 0xffff0000u); }
__device__ __forceinline__ float rbf(float x) { return bf_lo(pack2(x, 0.f)); }
__device__ __forceinline__ uint32_t hsub2(uint32_t a, uint32_t b) { uint32_t d; asm("sub.rn.bf16x2 %0, %1, %2;" : "=r"(d) : "r"(a), "r"(b)); return d; }
__device__ __forceinline__ uint32_t hadd2(uint32_t a, uint32_t b) { uint32_t d; asm("add.rn.bf16x2 %0, %1, %2;" : "=r"(d) : "r"(a), "r"(b)); return d; }
__device__ __forceinline__ uint32_t hmul2(uint32_t a, uint32_t b) { uint32_t d; asm("mul.rn.bf16x2 %0, %1, %2;" : "=r"(d) : "r"(a), "r"(b)); return d; }
__device__ __forceinline__ uint32_t hfma2(uint32_t a, uint32_t b, uint32_t c) { uint32_t d; asm("fma.rn.bf16x2 %0, %1, %2, %3;" : "=r"(d) : "r"(a), "r"(b), "r"(c)); return d; }
__device__ __forceinline__ uint32_t hmax2(uint32_t a, uint32_t b) { uint32_t d; asm("max.bf16x2 %0, %1, %2;" : "=r"(d) : "r"(a), "r"(b)); return d; }
__device__ __forceinline__ uint32_t hmin2(uint32_t a, uint32_t b) { uint32_t d; asm("min.bf16x2 %0, %1, %2;" : "=r"(d) : "r"(a), "r"(b)); return d; }
__device__ __forceinline__ float ex2(float x) { float y; asm("ex2.approx.ftz.f32 %0, %1;" : "=f"(y) : "f"(x)); return y; }
__device__ __forceinline__ float rcp(float x) { float y; asm("rcp.approx.ftz.f32 %0, %1;" : "=f"(y) : "f"(x)); return y; }
__device__ __forceinline__ float shfl_x(float v, int m) { return __shfl_xor_sync(0xffffffffu, v, m); }
__device__ __forceinline__ uint32_t hdiv2(uint32_t d, uint32_t rh, uint32_t rl) { return hfma2(d, rh, hmul2(d, rl)); }
__device__ __forceinline__ void split_rcp(float r, uint32_t& rh, uint32_t& rl) { rh = pack2(r, r); const float l = r - bf_lo(rh); rl = pack2(l, l); }
__device__ __forceinline__ uint32_t lnmod(uint32_t x, uint32_t m, uint32_t rh, uint32_t rl, uint32_t a, uint32_t s) { return hadd2(hmul2(hdiv2(hsub2(x, m), rh, rl), a), s); }
__device__ __forceinline__ void ln_final(float s1, float s2, uint32_t& m2, float& rinv) {
    const float mean = s1 * (1.0f / 1024.0f), var = fmaf(-mean, mean, s2 * (1.0f / 1024.0f));
    m2 = pack2(mean, mean);
    float sd;
    asm("sqrt.approx.ftz.f32 %0, %1;" : "=f"(sd) : "f"(rbf(rbf(fmaxf(var, 0.f)) + 1e-5f)));
    rinv = rcp(rbf(sd));
}
__device__ __forceinline__ float sigmoid_f(float x) { return rcp(1.0f + ex2(-1.4426950408889634f * x)); }
__device__ __forceinline__ uint32_t silu2(uint32_t v) { return pack2(bf_lo(v) * sigmoid_f(bf_lo(v)), bf_hi(v) * sigmoid_f(bf_hi(v))); }
__device__ __forceinline__ uint32_t f2key(float f) { uint32_t u = f2u(f); return (u & 0x80000000u) ? ~u : (u | 0x80000000u); }
__device__ __forceinline__ float key2f(uint32_t k) { return u2f((k & 0x80000000u) ? k ^ 0x80000000u : ~k); }
template<int N> __device__ __forceinline__ void top2(uint32_t (&k)[N], uint32_t& b0, uint32_t& b1) {
    uint32_t m = k[0];
    #pragma unroll
    for (int i = 1; i < N; i++) m = max(m, k[i]);
    b0 = __reduce_max_sync(0xffffffffu, m);
    m = 0;
    #pragma unroll
    for (int i = 0; i < N; i++) m = max(m, k[i] == b0 ? 0u : k[i]);
    b1 = __reduce_max_sync(0xffffffffu, m);
}
template<class T> __device__ __forceinline__ T sel4(int c, T a0, T a1, T a2, T a3) { return (c & 2) ? ((c & 1) ? a3 : a2) : ((c & 1) ? a1 : a0); }

__device__ __forceinline__ void fm_max(const float (&a)[16], uint32_t* p, uint32_t* mm) {
    #pragma unroll
    for (int i = 0; i < 8; i++) p[i] = pack2(a[2 * i], a[2 * i + 1]);
    #pragma unroll
    for (int h = 0; h < 2; h++) {
        const uint32_t mx = hmax2(hmax2(p[h], p[2 + h]), hmax2(p[4 + h], p[6 + h]));
        const uint32_t mn = hmin2(hmin2(p[h], p[2 + h]), hmin2(p[4 + h], p[6 + h])) ^ 0x80008000u;
        mm[h] = hmax2(__byte_perm(mx, mn, 0x5410), __byte_perm(mx, mn, 0x7632));
    }
    #pragma unroll
    for (int d = 1; d <= 2; d++) { mm[0] = hmax2(mm[0], __shfl_xor_sync(0xffffffffu, mm[0], d)); mm[1] = hmax2(mm[1], __shfl_xor_sync(0xffffffffu, mm[1], d)); }
}
constexpr float LOG2E = 1.4426950408889634f;
__device__ __forceinline__ void fm_pos(const uint32_t* p, const uint32_t* mm, float (&e)[32]) {
    #pragma unroll
    for (int h = 0; h < 2; h++) {
        const float cp = -bf_lo(mm[h]) * LOG2E;
        #pragma unroll
        for (int j = 0; j < 4; j++) {
            const float f0 = bf_lo(p[2 * j + h]), f1 = bf_hi(p[2 * j + h]);
            e[8 * h + 2 * j] = ex2(fmaf(f0, LOG2E, cp)); e[8 * h + 2 * j + 1] = ex2(fmaf(f1, LOG2E, cp));
            e[16 + 8 * h + 2 * j] = f0; e[16 + 8 * h + 2 * j + 1] = f1;
        }
    }
}
__device__ __forceinline__ void fm_neg(const uint32_t* mm, float nl, float (&e)[32]) {
    #pragma unroll
    for (int i = 16; i < 32; i++) e[i] = ex2(fmaf(e[i], -LOG2E, bf_hi(mm[(i >> 3) & 1]) * (i < 16 + NFREE ? -LOG2E : nl)));
}
__device__ __forceinline__ void fm_norm(const float (&e)[32], uint32_t* ph) {
    float s[4];
    #pragma unroll
    for (int k = 0; k < 4; k++) s[k] = ((e[8 * k] + e[8 * k + 1]) + (e[8 * k + 2] + e[8 * k + 3])) + ((e[8 * k + 4] + e[8 * k + 5]) + (e[8 * k + 6] + e[8 * k + 7]));
    #pragma unroll
    for (int k = 0; k < 4; k++) s[k] += shfl_x(s[k], 1);
    #pragma unroll
    for (int k = 0; k < 4; k++) s[k] = rcp(s[k] + shfl_x(s[k], 2));
    #pragma unroll
    for (int k = 0; k < 4; k++)
        #pragma unroll
        for (int j = 0; j < 4; j++) ph[8 * (k >> 1) + 2 * j + (k & 1)] = pack2(e[8 * k + 2 * j] * s[k], e[8 * k + 2 * j + 1] * s[k]);
}
template<class T> __device__ __forceinline__ T* pin_ptr(T* p) { asm volatile("" : "+l"(p) :: "memory"); return p; }
template<int N> __device__ __forceinline__ void pin(uint32_t* d) {
    #pragma unroll
    for (int i = 0; i < N; i++) asm volatile("" : "+r"(d[i]) :: "memory");
}

template<uint32_t BO, uint32_t BH> __device__ __forceinline__ void mma192_rs(float (&d)[96], const uint32_t* a, uint32_t blo) {
  asm volatile("{\n.reg .pred p;\n.reg .b32 ta, tb;\n.reg .b64 da, db;\nadd.u32 tb, %100, %101;\nmov.b64 db, {tb, %102};\nsetp.ne.b32 p, 1, 0;\n"
    "wgmma.mma_async.sync.aligned.m64n192k16.f32.bf16.bf16 {%0, %1, %2, %3, %4, %5, %6, %7, %8, %9, %10, %11, %12, %13, %14, %15, %16, %17, %18, %19, %20, %21, %22, %23, %24, %25, %26, %27, %28, %29, %30, %31, %32, %33, %34, %35, %36, %37, %38, %39, %40, %41, %42, %43, %44, %45, %46, %47, %48, %49, %50, %51, %52, %53, %54, %55, %56, %57, %58, %59, %60, %61, %62, %63, %64, %65, %66, %67, %68, %69, %70, %71, %72, %73, %74, %75, %76, %77, %78, %79, %80, %81, %82, %83, %84, %85, %86, %87, %88, %89, %90, %91, %92, %93, %94, %95}, {%96,%97,%98,%99}, db, p, 1, 1, 1;\n}\n"
    : "+f"(d[0]), "+f"(d[1]), "+f"(d[2]), "+f"(d[3]), "+f"(d[4]), "+f"(d[5]), "+f"(d[6]), "+f"(d[7]), "+f"(d[8]), "+f"(d[9]), "+f"(d[10]), "+f"(d[11]), "+f"(d[12]), "+f"(d[13]), "+f"(d[14]), "+f"(d[15]), "+f"(d[16]), "+f"(d[17]), "+f"(d[18]), "+f"(d[19]), "+f"(d[20]), "+f"(d[21]), "+f"(d[22]), "+f"(d[23]), "+f"(d[24]), "+f"(d[25]), "+f"(d[26]), "+f"(d[27]), "+f"(d[28]), "+f"(d[29]), "+f"(d[30]), "+f"(d[31]), "+f"(d[32]), "+f"(d[33]), "+f"(d[34]), "+f"(d[35]), "+f"(d[36]), "+f"(d[37]), "+f"(d[38]), "+f"(d[39]), "+f"(d[40]), "+f"(d[41]), "+f"(d[42]), "+f"(d[43]), "+f"(d[44]), "+f"(d[45]), "+f"(d[46]), "+f"(d[47]), "+f"(d[48]), "+f"(d[49]), "+f"(d[50]), "+f"(d[51]), "+f"(d[52]), "+f"(d[53]), "+f"(d[54]), "+f"(d[55]), "+f"(d[56]), "+f"(d[57]), "+f"(d[58]), "+f"(d[59]), "+f"(d[60]), "+f"(d[61]), "+f"(d[62]), "+f"(d[63]), "+f"(d[64]), "+f"(d[65]), "+f"(d[66]), "+f"(d[67]), "+f"(d[68]), "+f"(d[69]), "+f"(d[70]), "+f"(d[71]), "+f"(d[72]), "+f"(d[73]), "+f"(d[74]), "+f"(d[75]), "+f"(d[76]), "+f"(d[77]), "+f"(d[78]), "+f"(d[79]), "+f"(d[80]), "+f"(d[81]), "+f"(d[82]), "+f"(d[83]), "+f"(d[84]), "+f"(d[85]), "+f"(d[86]), "+f"(d[87]), "+f"(d[88]), "+f"(d[89]), "+f"(d[90]), "+f"(d[91]), "+f"(d[92]), "+f"(d[93]), "+f"(d[94]), "+f"(d[95])
    : "r"(a[0]), "r"(a[1]), "r"(a[2]), "r"(a[3]), "r"(blo), "n"(BO), "n"(BH));
}
template<uint32_t BO, uint32_t BH> __device__ __forceinline__ void mma192_rsp(float (&d)[96], const uint32_t* a, uint32_t blo, int sc) {
  asm volatile("{\n.reg .pred p;\n.reg .b32 ta, tb;\n.reg .b64 da, db;\nadd.u32 tb, %100, %101;\nmov.b64 db, {tb, %102};\nsetp.ne.b32 p, %103, 0;\n"
    "wgmma.mma_async.sync.aligned.m64n192k16.f32.bf16.bf16 {%0, %1, %2, %3, %4, %5, %6, %7, %8, %9, %10, %11, %12, %13, %14, %15, %16, %17, %18, %19, %20, %21, %22, %23, %24, %25, %26, %27, %28, %29, %30, %31, %32, %33, %34, %35, %36, %37, %38, %39, %40, %41, %42, %43, %44, %45, %46, %47, %48, %49, %50, %51, %52, %53, %54, %55, %56, %57, %58, %59, %60, %61, %62, %63, %64, %65, %66, %67, %68, %69, %70, %71, %72, %73, %74, %75, %76, %77, %78, %79, %80, %81, %82, %83, %84, %85, %86, %87, %88, %89, %90, %91, %92, %93, %94, %95}, {%96,%97,%98,%99}, db, p, 1, 1, 1;\n}\n"
    : "+f"(d[0]), "+f"(d[1]), "+f"(d[2]), "+f"(d[3]), "+f"(d[4]), "+f"(d[5]), "+f"(d[6]), "+f"(d[7]), "+f"(d[8]), "+f"(d[9]), "+f"(d[10]), "+f"(d[11]), "+f"(d[12]), "+f"(d[13]), "+f"(d[14]), "+f"(d[15]), "+f"(d[16]), "+f"(d[17]), "+f"(d[18]), "+f"(d[19]), "+f"(d[20]), "+f"(d[21]), "+f"(d[22]), "+f"(d[23]), "+f"(d[24]), "+f"(d[25]), "+f"(d[26]), "+f"(d[27]), "+f"(d[28]), "+f"(d[29]), "+f"(d[30]), "+f"(d[31]), "+f"(d[32]), "+f"(d[33]), "+f"(d[34]), "+f"(d[35]), "+f"(d[36]), "+f"(d[37]), "+f"(d[38]), "+f"(d[39]), "+f"(d[40]), "+f"(d[41]), "+f"(d[42]), "+f"(d[43]), "+f"(d[44]), "+f"(d[45]), "+f"(d[46]), "+f"(d[47]), "+f"(d[48]), "+f"(d[49]), "+f"(d[50]), "+f"(d[51]), "+f"(d[52]), "+f"(d[53]), "+f"(d[54]), "+f"(d[55]), "+f"(d[56]), "+f"(d[57]), "+f"(d[58]), "+f"(d[59]), "+f"(d[60]), "+f"(d[61]), "+f"(d[62]), "+f"(d[63]), "+f"(d[64]), "+f"(d[65]), "+f"(d[66]), "+f"(d[67]), "+f"(d[68]), "+f"(d[69]), "+f"(d[70]), "+f"(d[71]), "+f"(d[72]), "+f"(d[73]), "+f"(d[74]), "+f"(d[75]), "+f"(d[76]), "+f"(d[77]), "+f"(d[78]), "+f"(d[79]), "+f"(d[80]), "+f"(d[81]), "+f"(d[82]), "+f"(d[83]), "+f"(d[84]), "+f"(d[85]), "+f"(d[86]), "+f"(d[87]), "+f"(d[88]), "+f"(d[89]), "+f"(d[90]), "+f"(d[91]), "+f"(d[92]), "+f"(d[93]), "+f"(d[94]), "+f"(d[95])
    : "r"(a[0]), "r"(a[1]), "r"(a[2]), "r"(a[3]), "r"(blo), "n"(BO), "n"(BH), "r"(sc));
}
template<uint32_t BO, uint32_t BH> __device__ __forceinline__ void mma32_rs(float (&d)[16], const uint32_t* a, uint32_t blo) {
  asm volatile("{\n.reg .pred p;\n.reg .b32 ta, tb;\n.reg .b64 da, db;\nadd.u32 tb, %20, %21;\nmov.b64 db, {tb, %22};\nsetp.ne.b32 p, 1, 0;\n"
    "wgmma.mma_async.sync.aligned.m64n32k16.f32.bf16.bf16 {%0, %1, %2, %3, %4, %5, %6, %7, %8, %9, %10, %11, %12, %13, %14, %15}, {%16,%17,%18,%19}, db, p, 1, 1, 1;\n}\n"
    : "+f"(d[0]), "+f"(d[1]), "+f"(d[2]), "+f"(d[3]), "+f"(d[4]), "+f"(d[5]), "+f"(d[6]), "+f"(d[7]), "+f"(d[8]), "+f"(d[9]), "+f"(d[10]), "+f"(d[11]), "+f"(d[12]), "+f"(d[13]), "+f"(d[14]), "+f"(d[15])
    : "r"(a[0]), "r"(a[1]), "r"(a[2]), "r"(a[3]), "r"(blo), "n"(BO), "n"(BH));
}
template<uint32_t BO, uint32_t BH> __device__ __forceinline__ void mma32_rs0(float (&d)[16], const uint32_t* a, uint32_t blo) {
  asm volatile("{\n.reg .pred p;\n.reg .b32 ta, tb;\n.reg .b64 da, db;\nadd.u32 tb, %20, %21;\nmov.b64 db, {tb, %22};\nsetp.ne.b32 p, 0, 0;\n"
    "wgmma.mma_async.sync.aligned.m64n32k16.f32.bf16.bf16 {%0, %1, %2, %3, %4, %5, %6, %7, %8, %9, %10, %11, %12, %13, %14, %15}, {%16,%17,%18,%19}, db, p, 1, 1, 1;\n}\n"
    : "=f"(d[0]), "=f"(d[1]), "=f"(d[2]), "=f"(d[3]), "=f"(d[4]), "=f"(d[5]), "=f"(d[6]), "=f"(d[7]), "=f"(d[8]), "=f"(d[9]), "=f"(d[10]), "=f"(d[11]), "=f"(d[12]), "=f"(d[13]), "=f"(d[14]), "=f"(d[15])
    : "r"(a[0]), "r"(a[1]), "r"(a[2]), "r"(a[3]), "r"(blo), "n"(BO), "n"(BH));
}
template<uint32_t BO, uint32_t BH> __device__ __forceinline__ void mma40_rs(float (&d)[20], const uint32_t* a, uint32_t blo) {
  asm volatile("{\n.reg .pred p;\n.reg .b32 ta, tb;\n.reg .b64 da, db;\nadd.u32 tb, %24, %25;\nmov.b64 db, {tb, %26};\nsetp.ne.b32 p, 1, 0;\n"
    "wgmma.mma_async.sync.aligned.m64n40k16.f32.bf16.bf16 {%0, %1, %2, %3, %4, %5, %6, %7, %8, %9, %10, %11, %12, %13, %14, %15, %16, %17, %18, %19}, {%20,%21,%22,%23}, db, p, 1, 1, 1;\n}\n"
    : "+f"(d[0]), "+f"(d[1]), "+f"(d[2]), "+f"(d[3]), "+f"(d[4]), "+f"(d[5]), "+f"(d[6]), "+f"(d[7]), "+f"(d[8]), "+f"(d[9]), "+f"(d[10]), "+f"(d[11]), "+f"(d[12]), "+f"(d[13]), "+f"(d[14]), "+f"(d[15]), "+f"(d[16]), "+f"(d[17]), "+f"(d[18]), "+f"(d[19])
    : "r"(a[0]), "r"(a[1]), "r"(a[2]), "r"(a[3]), "r"(blo), "n"(BO), "n"(BH));
}
template<uint32_t BO, uint32_t BH> __device__ __forceinline__ void mma40_rs0(float (&d)[20], const uint32_t* a, uint32_t blo) {
  asm volatile("{\n.reg .pred p;\n.reg .b32 ta, tb;\n.reg .b64 da, db;\nadd.u32 tb, %24, %25;\nmov.b64 db, {tb, %26};\nsetp.ne.b32 p, 0, 0;\n"
    "wgmma.mma_async.sync.aligned.m64n40k16.f32.bf16.bf16 {%0, %1, %2, %3, %4, %5, %6, %7, %8, %9, %10, %11, %12, %13, %14, %15, %16, %17, %18, %19}, {%20,%21,%22,%23}, db, p, 1, 1, 1;\n}\n"
    : "=f"(d[0]), "=f"(d[1]), "=f"(d[2]), "=f"(d[3]), "=f"(d[4]), "=f"(d[5]), "=f"(d[6]), "=f"(d[7]), "=f"(d[8]), "=f"(d[9]), "=f"(d[10]), "=f"(d[11]), "=f"(d[12]), "=f"(d[13]), "=f"(d[14]), "=f"(d[15]), "=f"(d[16]), "=f"(d[17]), "=f"(d[18]), "=f"(d[19])
    : "r"(a[0]), "r"(a[1]), "r"(a[2]), "r"(a[3]), "r"(blo), "n"(BO), "n"(BH));
}
template<uint32_t AO, uint32_t AH, uint32_t BO, uint32_t BH> __device__ __forceinline__ void mma40_tt(float (&d)[20], uint32_t alo, uint32_t blo) {
  asm volatile("{\n.reg .pred p;\n.reg .b32 ta, tb;\n.reg .b64 da, db;\nadd.u32 ta, %20, %21;\nmov.b64 da, {ta, %22};\nadd.u32 tb, %23, %24;\nmov.b64 db, {tb, %25};\nsetp.ne.b32 p, 1, 0;\n"
    "wgmma.mma_async.sync.aligned.m64n40k16.f32.bf16.bf16 {%0, %1, %2, %3, %4, %5, %6, %7, %8, %9, %10, %11, %12, %13, %14, %15, %16, %17, %18, %19}, da, db, p, 1, 1, 1, 1;\n}\n"
    : "+f"(d[0]), "+f"(d[1]), "+f"(d[2]), "+f"(d[3]), "+f"(d[4]), "+f"(d[5]), "+f"(d[6]), "+f"(d[7]), "+f"(d[8]), "+f"(d[9]), "+f"(d[10]), "+f"(d[11]), "+f"(d[12]), "+f"(d[13]), "+f"(d[14]), "+f"(d[15]), "+f"(d[16]), "+f"(d[17]), "+f"(d[18]), "+f"(d[19])
    : "r"(alo), "n"(AO), "n"(AH), "r"(blo), "n"(BO), "n"(BH));
}
template<uint32_t AO, uint32_t AH, uint32_t BO, uint32_t BH> __device__ __forceinline__ void mma40_tt0(float (&d)[20], uint32_t alo, uint32_t blo) {
  asm volatile("{\n.reg .pred p;\n.reg .b32 ta, tb;\n.reg .b64 da, db;\nadd.u32 ta, %20, %21;\nmov.b64 da, {ta, %22};\nadd.u32 tb, %23, %24;\nmov.b64 db, {tb, %25};\nsetp.ne.b32 p, 0, 0;\n"
    "wgmma.mma_async.sync.aligned.m64n40k16.f32.bf16.bf16 {%0, %1, %2, %3, %4, %5, %6, %7, %8, %9, %10, %11, %12, %13, %14, %15, %16, %17, %18, %19}, da, db, p, 1, 1, 1, 1;\n}\n"
    : "=f"(d[0]), "=f"(d[1]), "=f"(d[2]), "=f"(d[3]), "=f"(d[4]), "=f"(d[5]), "=f"(d[6]), "=f"(d[7]), "=f"(d[8]), "=f"(d[9]), "=f"(d[10]), "=f"(d[11]), "=f"(d[12]), "=f"(d[13]), "=f"(d[14]), "=f"(d[15]), "=f"(d[16]), "=f"(d[17]), "=f"(d[18]), "=f"(d[19])
    : "r"(alo), "n"(AO), "n"(AH), "r"(blo), "n"(BO), "n"(BH));
}
template<uint32_t AO, uint32_t AH, uint32_t BO, uint32_t BH> __device__ __forceinline__ void mma8_tn(float (&d)[4], uint32_t alo, uint32_t blo) {
  asm volatile("{\n.reg .pred p;\n.reg .b32 ta, tb;\n.reg .b64 da, db;\nadd.u32 ta, %4, %5;\nmov.b64 da, {ta, %6};\nadd.u32 tb, %7, %8;\nmov.b64 db, {tb, %9};\nsetp.ne.b32 p, 1, 0;\n"
    "wgmma.mma_async.sync.aligned.m64n8k16.f32.bf16.bf16 {%0, %1, %2, %3}, da, db, p, 1, 1, 1, 0;\n}\n"
    : "+f"(d[0]), "+f"(d[1]), "+f"(d[2]), "+f"(d[3])
    : "r"(alo), "n"(AO), "n"(AH), "r"(blo), "n"(BO), "n"(BH));
}
template<uint32_t AO, uint32_t AH, uint32_t BO, uint32_t BH> __device__ __forceinline__ void mma8_tn0(float (&d)[4], uint32_t alo, uint32_t blo) {
  asm volatile("{\n.reg .pred p;\n.reg .b32 ta, tb;\n.reg .b64 da, db;\nadd.u32 ta, %4, %5;\nmov.b64 da, {ta, %6};\nadd.u32 tb, %7, %8;\nmov.b64 db, {tb, %9};\nsetp.ne.b32 p, 0, 0;\n"
    "wgmma.mma_async.sync.aligned.m64n8k16.f32.bf16.bf16 {%0, %1, %2, %3}, da, db, p, 1, 1, 1, 0;\n}\n"
    : "=f"(d[0]), "=f"(d[1]), "=f"(d[2]), "=f"(d[3])
    : "r"(alo), "n"(AO), "n"(AH), "r"(blo), "n"(BO), "n"(BH));
}
template<uint32_t AO, uint32_t AH, uint32_t BO, uint32_t BH> __device__ __forceinline__ void mma128_ss(float (&d)[64], uint32_t alo, uint32_t blo) {
  asm volatile("{\n.reg .pred p;\n.reg .b32 ta, tb;\n.reg .b64 da, db;\nadd.u32 ta, %64, %65;\nmov.b64 da, {ta, %66};\nadd.u32 tb, %67, %68;\nmov.b64 db, {tb, %69};\nsetp.ne.b32 p, 1, 0;\n"
    "wgmma.mma_async.sync.aligned.m64n128k16.f32.bf16.bf16 {%0, %1, %2, %3, %4, %5, %6, %7, %8, %9, %10, %11, %12, %13, %14, %15, %16, %17, %18, %19, %20, %21, %22, %23, %24, %25, %26, %27, %28, %29, %30, %31, %32, %33, %34, %35, %36, %37, %38, %39, %40, %41, %42, %43, %44, %45, %46, %47, %48, %49, %50, %51, %52, %53, %54, %55, %56, %57, %58, %59, %60, %61, %62, %63}, da, db, p, 1, 1, 0, 1;\n}\n"
    : "+f"(d[0]), "+f"(d[1]), "+f"(d[2]), "+f"(d[3]), "+f"(d[4]), "+f"(d[5]), "+f"(d[6]), "+f"(d[7]), "+f"(d[8]), "+f"(d[9]), "+f"(d[10]), "+f"(d[11]), "+f"(d[12]), "+f"(d[13]), "+f"(d[14]), "+f"(d[15]), "+f"(d[16]), "+f"(d[17]), "+f"(d[18]), "+f"(d[19]), "+f"(d[20]), "+f"(d[21]), "+f"(d[22]), "+f"(d[23]), "+f"(d[24]), "+f"(d[25]), "+f"(d[26]), "+f"(d[27]), "+f"(d[28]), "+f"(d[29]), "+f"(d[30]), "+f"(d[31]), "+f"(d[32]), "+f"(d[33]), "+f"(d[34]), "+f"(d[35]), "+f"(d[36]), "+f"(d[37]), "+f"(d[38]), "+f"(d[39]), "+f"(d[40]), "+f"(d[41]), "+f"(d[42]), "+f"(d[43]), "+f"(d[44]), "+f"(d[45]), "+f"(d[46]), "+f"(d[47]), "+f"(d[48]), "+f"(d[49]), "+f"(d[50]), "+f"(d[51]), "+f"(d[52]), "+f"(d[53]), "+f"(d[54]), "+f"(d[55]), "+f"(d[56]), "+f"(d[57]), "+f"(d[58]), "+f"(d[59]), "+f"(d[60]), "+f"(d[61]), "+f"(d[62]), "+f"(d[63])
    : "r"(alo), "n"(AO), "n"(AH), "r"(blo), "n"(BO), "n"(BH));
}
template<uint32_t AO, uint32_t AH, uint32_t BO, uint32_t BH> __device__ __forceinline__ void mma128_ss0(float (&d)[64], uint32_t alo, uint32_t blo) {
  asm volatile("{\n.reg .pred p;\n.reg .b32 ta, tb;\n.reg .b64 da, db;\nadd.u32 ta, %64, %65;\nmov.b64 da, {ta, %66};\nadd.u32 tb, %67, %68;\nmov.b64 db, {tb, %69};\nsetp.ne.b32 p, 0, 0;\n"
    "wgmma.mma_async.sync.aligned.m64n128k16.f32.bf16.bf16 {%0, %1, %2, %3, %4, %5, %6, %7, %8, %9, %10, %11, %12, %13, %14, %15, %16, %17, %18, %19, %20, %21, %22, %23, %24, %25, %26, %27, %28, %29, %30, %31, %32, %33, %34, %35, %36, %37, %38, %39, %40, %41, %42, %43, %44, %45, %46, %47, %48, %49, %50, %51, %52, %53, %54, %55, %56, %57, %58, %59, %60, %61, %62, %63}, da, db, p, 1, 1, 0, 1;\n}\n"
    : "=f"(d[0]), "=f"(d[1]), "=f"(d[2]), "=f"(d[3]), "=f"(d[4]), "=f"(d[5]), "=f"(d[6]), "=f"(d[7]), "=f"(d[8]), "=f"(d[9]), "=f"(d[10]), "=f"(d[11]), "=f"(d[12]), "=f"(d[13]), "=f"(d[14]), "=f"(d[15]), "=f"(d[16]), "=f"(d[17]), "=f"(d[18]), "=f"(d[19]), "=f"(d[20]), "=f"(d[21]), "=f"(d[22]), "=f"(d[23]), "=f"(d[24]), "=f"(d[25]), "=f"(d[26]), "=f"(d[27]), "=f"(d[28]), "=f"(d[29]), "=f"(d[30]), "=f"(d[31]), "=f"(d[32]), "=f"(d[33]), "=f"(d[34]), "=f"(d[35]), "=f"(d[36]), "=f"(d[37]), "=f"(d[38]), "=f"(d[39]), "=f"(d[40]), "=f"(d[41]), "=f"(d[42]), "=f"(d[43]), "=f"(d[44]), "=f"(d[45]), "=f"(d[46]), "=f"(d[47]), "=f"(d[48]), "=f"(d[49]), "=f"(d[50]), "=f"(d[51]), "=f"(d[52]), "=f"(d[53]), "=f"(d[54]), "=f"(d[55]), "=f"(d[56]), "=f"(d[57]), "=f"(d[58]), "=f"(d[59]), "=f"(d[60]), "=f"(d[61]), "=f"(d[62]), "=f"(d[63])
    : "r"(alo), "n"(AO), "n"(AH), "r"(blo), "n"(BO), "n"(BH));
}
template<uint32_t AO, uint32_t AH, uint32_t BO, uint32_t BH> __device__ __forceinline__ void mma128_ssp(float (&d)[64], uint32_t alo, uint32_t blo, int sc) {
  asm volatile("{\n.reg .pred p;\n.reg .b32 ta, tb;\n.reg .b64 da, db;\nadd.u32 ta, %64, %65;\nmov.b64 da, {ta, %66};\nadd.u32 tb, %67, %68;\nmov.b64 db, {tb, %69};\nsetp.ne.b32 p, %70, 0;\n"
    "wgmma.mma_async.sync.aligned.m64n128k16.f32.bf16.bf16 {%0, %1, %2, %3, %4, %5, %6, %7, %8, %9, %10, %11, %12, %13, %14, %15, %16, %17, %18, %19, %20, %21, %22, %23, %24, %25, %26, %27, %28, %29, %30, %31, %32, %33, %34, %35, %36, %37, %38, %39, %40, %41, %42, %43, %44, %45, %46, %47, %48, %49, %50, %51, %52, %53, %54, %55, %56, %57, %58, %59, %60, %61, %62, %63}, da, db, p, 1, 1, 0, 1;\n}\n"
    : "+f"(d[0]), "+f"(d[1]), "+f"(d[2]), "+f"(d[3]), "+f"(d[4]), "+f"(d[5]), "+f"(d[6]), "+f"(d[7]), "+f"(d[8]), "+f"(d[9]), "+f"(d[10]), "+f"(d[11]), "+f"(d[12]), "+f"(d[13]), "+f"(d[14]), "+f"(d[15]), "+f"(d[16]), "+f"(d[17]), "+f"(d[18]), "+f"(d[19]), "+f"(d[20]), "+f"(d[21]), "+f"(d[22]), "+f"(d[23]), "+f"(d[24]), "+f"(d[25]), "+f"(d[26]), "+f"(d[27]), "+f"(d[28]), "+f"(d[29]), "+f"(d[30]), "+f"(d[31]), "+f"(d[32]), "+f"(d[33]), "+f"(d[34]), "+f"(d[35]), "+f"(d[36]), "+f"(d[37]), "+f"(d[38]), "+f"(d[39]), "+f"(d[40]), "+f"(d[41]), "+f"(d[42]), "+f"(d[43]), "+f"(d[44]), "+f"(d[45]), "+f"(d[46]), "+f"(d[47]), "+f"(d[48]), "+f"(d[49]), "+f"(d[50]), "+f"(d[51]), "+f"(d[52]), "+f"(d[53]), "+f"(d[54]), "+f"(d[55]), "+f"(d[56]), "+f"(d[57]), "+f"(d[58]), "+f"(d[59]), "+f"(d[60]), "+f"(d[61]), "+f"(d[62]), "+f"(d[63])
    : "r"(alo), "n"(AO), "n"(AH), "r"(blo), "n"(BO), "n"(BH), "r"(sc));
}

#define XD 600
#define XSTEP 300
#define XPD 550
#define XPB 8192
#define SPG 5600
#define WL0 1800
#define WLS 350
#define NB0 2
#define WP1 2000
#define PF_START 5600
#define PFP 126
#define NM0 3
#define PWAIT 600
#define AWAKE 1
#define WDW 3
#define WDGAP 150
#define YWAIT 600
#define CWAIT 350
#define RDV 1
#define MSTEP 1200
#define MSLP 1000
#define MPOLL 3200
#define LMP 8
#define FLO(q, cta) (p.s->flo + (q) * 256 + (cta) * 2)
#define NUD 4u
#define U1Q 0
#define SWA 4
#define NDF 10
#define UPS 4
#define WD0 (UPS + 5)
#define CLR0 22000
#define UPGAP 180
#define OUTGAP 110
#define MPROMO P128
#define MLOAD tma_load_ef
struct Ptrs { const bf16 *x, *wmod, *c, *wr, *wqkv; int by_sm; Scratch* s; const bf16 *wg, *wu, *wd, *wo; bf16* out; uint16_t role[132]; };

#define BAR(i) (sb + OFF_BAR + 8u * (i))

__device__ __forceinline__ uint32_t get_tag(uint32_t sb) { mbar_wait(BAR(B_TAG), 0); const uint32_t d = __shfl_sync(0xffffffffu, lds32(sb + OFF_CST + 32), 0); return d + 1 + (d & 2); }
__device__ __forceinline__ int d_kb(int n, int hg) {
    if (n < 2) return 2 * hg + n;
    const int h = n >= 9, q = n - 2 - 7 * h;
    return 2 * (q + (q >= hg)) + h;
}

__global__ void __launch_bounds__(NTHREADS, 1)
fused_kernel(const Ptrs p, const __grid_constant__ CUtensorMap tmM, const __grid_constant__ CUtensorMap tmX, const __grid_constant__ CUtensorMap tmW,
             const __grid_constant__ CUtensorMap tmWo, const __grid_constant__ CUtensorMap tmPhi, const __grid_constant__ CUtensorMap tmG,
             const __grid_constant__ CUtensorMap tmU, const __grid_constant__ CUtensorMap tmD, const __grid_constant__ CUtensorMap tmO)
{
    extern __shared__ __align__(1024) uint8_t smem_raw[];
    const uint32_t sb = smem_u32(smem_raw);
    const uint32_t cstart = __shfl_sync(0xffffffffu, clk32(), 0);
    const int tid = threadIdx.x, lane = tid & 31, warp = __shfl_sync(0xffffffffu, tid >> 5, 0);
    if (blockIdx.x < 128) {
        if (warp == 8) asm volatile("prefetch.global.L2 [%0];" :: "l"(p.wmod + (size_t)(blockIdx.x * 8 + (lane >> 2)) * 6144 + (lane & 1) * 64 + (lane & 2) * 512));
        if (warp == 13 && (lane & 1) < NM0 - 2) asm volatile("prefetch.global.L2 [%0];" :: "l"(p.wmod + (size_t)(blockIdx.x * 8 + (lane >> 2)) * 6144 + 128 + (lane & 1) * 64 + (lane & 2) * 512));
        if (warp == 11) asm volatile("prefetch.global.L2 [%0];" :: "l"((lane < 16 ? p.c : p.wr) + (lane & 15) * 64));
        if (warp == 12) l2_prefetch(p.wqkv + (size_t)blockIdx.x * 1536, 3072);
        if (warp == 9) { spin_until(cstart + XPD); l2_prefetch(p.x + (size_t)blockIdx.x * 16384, XPB); }
    }
    if (warp == 10) { tmap_prefetch(&tmM); tmap_prefetch(&tmX); tmap_prefetch(&tmW); }
    #pragma unroll
    for (int i = 0; i < 5; i++) e_init(BAR(5 * warp + i), warp < 5 ? 1 : warp < 7 ? 2 : warp < 9 ? 4 : warp < 14 ? 8 : warp < 15 ? 12 : 1);
    mbar_init_fence();
    if (warp == B_TAG / 5) { e_arrive_tx(BAR(B_TAG), 16); bulk_load(sb + OFF_CST + 32, p.s->done, 16, BAR(B_TAG)); }
    uint32_t role;
    asm("mov.u32 %0, %%smid;" : "=r"(role));
    role = p.role[p.by_sm ? role : blockIdx.x];
    const int b = role & 255;
    if (b >= 128 && warp == 0) {
        #pragma unroll
        for (int i = 0; i < 2; i++) { e_arrive_tx(BAR(i), 32768); MLOAD(sb + i * 32768u, &tmM, (b & 1) * 1024, (b & 2) * 256 + i * 256, BAR(i)); }
    }
    __syncthreads();

    if (b >= 128) {
        const int sp = b & 3;
        if (warp == 8) {
            #pragma unroll 1
            for (int j = 2, st = 2, ph = 1; j < 64; j++) {
                if (j == 2 * NM0) spin_until(cstart + SPG);
                mbar_wait(BAR(B_EA + st), ph);
                e_arrive_tx(BAR(st), 32768);
                MLOAD(sb + st * 32768u, &tmM, j < 32 ? (sp & 1) * 1024 + (j >> 1) * 64 : 2560 + sp * 512 + (j >> 2) * 64, (j < 32 ? (sp & 2) + (j & 1) : j & 3) * 256, BAR(st));
                if (++st == 6) { st = 0; ph ^= 1; }
            }
        } else if (warp < 8) {
            const int g = lane >> 2, c = lane & 3;
            {
                const bf16* cp = p.c + (tid >> 3) * 32 + (tid & 1) * 16 + (tid & 6);
                const uint32_t c0 = ldg32(cp), c1 = ldg32(cp + 8);
                stg_zero(p.s->llm1 + (tid >> 4) * 64 + sp * 16 + (tid & 15));
                if (tid < 128) stg_zero(p.s->llmod2 + sp * 128 + tid);
                sts64(sb + 200704u + tid * 8, silu2(c0), silu2(c1));
                bar_sync(1, 256);
                TR(57);
            }
            const uint32_t wa = sb + (warp * 32 + (lane & 7) + (lane >> 4) * 8) * 128u + ((((lane >> 3) & 1) ^ (lane & 7)) << 4);
            float m[4][4];
            #pragma unroll
            for (int i = 0; i < 4; i++) m[i][0] = m[i][1] = m[i][2] = m[i][3] = 0.f;
            #pragma unroll 1
            for (int r = 0, st = 0, ph = 0; r < 32; r++) {
                const uint32_t sa = sb + 200704u + ((r < 16 ? sp >> 1 : r & 1) * 16 + warp) * 64 + c * 16;
                #pragma unroll
                for (int q = 0; q < 2; q++) {
                    const uint4 sv = lds128(sa + q * 512);
                    uint32_t f[8][4];
                    mbar_wait(BAR(st + q), ph);
                    if (r == 0 && warp == 0) TR(60 + q);
                    #pragma unroll
                    for (int i = 0; i < 8; i++) ldsm4t(f[i], (wa + (st + q) * 32768u + (i >> 2) * 2048u) ^ ((i & 3) << 5));
                    e_arrive_after(BAR(B_EA + st + q), (f[0][0] ^ f[1][0] ^ f[2][0]) ^ (f[3][0] ^ f[4][0] ^ f[5][0]) ^ (f[6][0] ^ f[7][0]));
                    #pragma unroll
                    for (int i = 0; i < 8; i++) mma16816(m[i & 3], f[i][0], f[i][1], f[i][2], f[i][3], (i & 4) ? sv.z : sv.x, (i & 4) ? sv.w : sv.y);
                }
                st += 2; if (st == 6) { st = 0; ph ^= 1; }
                if (r >= 16 && !(r & 1)) continue;
                const int n = r < 16 ? r : (r >> 1) + 8;
                const uint32_t a = sb + 196608u + (n & 1) * 2048u + warp * 256u + (c * 16 + (g >> 1) * 4 + (g & 1)) * 4u;
                mbar_wait(BAR(B_XP + (n & 1)), ~(n >> 1) & 1);
                stsf(a, sel4(c, m[0][0], m[1][0], m[2][0], m[3][0])); stsf(a + 8, sel4(c, m[0][2], m[1][2], m[2][2], m[3][2]));
                #pragma unroll
                for (int i = 0; i < 4; i++) m[i][0] = m[i][1] = m[i][2] = m[i][3] = 0.f;
                __syncwarp();
                e_arrive(BAR(B_PF + (n & 1)));
            }
        } else if (warp == 9) {
            const int c = lane & 3;
            const uint32_t tag = get_tag(sb);
            #pragma unroll 1
            for (int n = 0; n < 24; n++) {
                const bf16* wr = p.wr + (sp & 1) * 512 + (n & 7) * 64 + ((lane >> 2) & 3) * 16 + 2 * c;
                const uint32_t wr0 = ldg32(wr), wr1 = ldg32(wr + 8);
                const uint32_t ra = sb + 196608u + (n & 1) * 2048u + (lane >> 4) * 1024u + (lane & 15) * 16u;
                uint4* d = n < 16 ? p.s->llm1 + n * 64 + sp * 16 + lane : p.s->llmod2 + sp * 128 + (n & 7) * 16 + lane;
                mbar_wait(BAR(B_PF + (n & 1)), (n >> 1) & 1);
                const uint4 r0 = lds128(ra), r1 = lds128(ra + 256), r2 = lds128(ra + 512), r3 = lds128(ra + 768);
                e_arrive(BAR(B_XP + (n & 1)));
                #define F4(f) ((u2f(r0.f) + u2f(r1.f)) + (u2f(r2.f) + u2f(r3.f)))
                float x = F4(x), y = F4(y), z = F4(z), w = F4(w);
                #undef F4
                x += shfl_x(x, 16); y += shfl_x(y, 16); z += shfl_x(z, 16); w += shfl_x(w, 16);
                if (n < 16) {
                    if (lane < 16) st_ll4(d, x, y, z, w, tag);
                } else {
                    uint32_t lo = pack2(x, y), hi2 = pack2(z, w);
                    float e = fmaf(bf_lo(lo), bf_lo(wr0), bf_hi(lo) * bf_hi(wr0)) + fmaf(bf_lo(hi2), bf_lo(wr1), bf_hi(hi2) * bf_hi(wr1));
                    if (sp >= 2) {
                        lo = hadd2(lo, ONE2); hi2 = hadd2(hi2, ONE2);
                        const uint32_t q0 = hmul2(lo, wr0), q1 = hmul2(hi2, wr1);
                        e = (bf_lo(q0) + bf_hi(q0)) + (bf_lo(q1) + bf_hi(q1));
                    }
                    #pragma unroll 1
                    for (int k = 1; k < 16; k <<= 1) e += shfl_x(e, k);
                    if (lane < 16) st_ll(d, lo, hi2, f2u(e), tag);
                }
                TR(n);
            }
        }
    } else if (warp >= 12) {
        reg_dec<24>();
        const int rb = b >> 3, hg = b & 7, fs = role >> 8;
        const bool ffn = fs < 112;
        if (warp == 12) {
            #pragma unroll 1
            for (int j = 0, s = 0, ph = 1; j < 16; j++) {
                if (j < 2) mbar_wait(j ? BAR(B_STS) : BAR(B_STP), 0);
                mbar_wait(BAR(B_EA + s), ph);
                e_arrive_tx(BAR(B_FA + s), 16384); tma_load(sb + OFF_A + s * 16384u, &tmX, j * 64, rb * 128, BAR(B_FA + s));
                if (j == 0) TS(2);
                if (j == 1) GT(0);
                if (j == 6) GT(1);
                if (j == 11) GT(2);
                if (++s == 3) { s = 0; ph ^= 1; }
            }
            if (ffn) {
                #pragma unroll 1
                for (int i = 3; i >= 0; i--) {
                    if (i & 1) mbar_wait(U1Q ? BAR(B_QE) : BAR(B_EA + (i >> 1)), !U1Q && i == 1);
                    tma_load_ef(sb + OFF_U1 + i * 8192u, &tmU, fs * 32, 512 + i * 128, BAR(B_UF));
                }
            }
            tmap_prefetch(&tmO);
            const uint32_t tag = get_tag(sb);
            e_arrive(BAR(B_FD)); e_arrive(BAR(B_FD + 1));
            const uint4* osrc = pin_ptr(p.s->os + (size_t)rb * 16 * 1024);
            #pragma unroll 1
            for (int q = 0; q < 3; q++) {
                mbar_wait(q < 2 ? BAR(B_KST + 1 + 2 * q) : BAR(B_OWN), 0);
                const uint32_t chk = poll_flags(q < 2 ? p.s->flk + (q + 1) * 256 + (hg * 16 + (lane & 15)) * 2 : FLO(0, rb * 8 + (lane & 7)), tag);
                if (q == 2) { sts32(sb + OFF_CHK + 64 + (lane & 7) * 8, chk); __syncwarp(); break; }
                e_arrive_tx(BAR(B_KVL + q), 16896); bulk_load(sb + (q ? OFF_KL1 : OFF_KL), p.s->kvacc + hg * 2112 + q * 1056, 16896, BAR(B_KVL + q));
                TS(12 + q);
                if (!q) GT(4);
            }
            TS(3); GT(5);
            #pragma unroll
            for (int n = 2; n < 6; n++) {
                if (n >= 4) mbar_wait(BAR(B_ED + (n & 3)), 0); else if (n == 3) mbar_wait(BAR(B_OWN + 1), 0);
                e_arrive_tx(BAR(B_FD + (n & 3)), 16384);
                bulk_load(sb + (n == 5 ? OFF_X1 : OFF_R0 + (n & 3) * 16384u), osrc + (n - 2 >= hg ? n - 1 : n - 2) * 2048, 16384, BAR(B_FD + (n & 3)));
                TR(32 + n);
            }
            #pragma unroll 1
            for (int n = 6; n < 16; n++) {
                const uint32_t s = n & 3, fb = BAR(B_FD + s);
                const uint4* src = osrc + d_kb(n, hg) * 1024;
                if (n == 9) mbar_wait(BAR(B_O1), 0);
                mbar_wait(BAR(B_ED + s), ((n >> 2) - 1) & 1);
                e_arrive_tx(fb, 16384);
                bulk_load(sb + OFF_R0 + s * 16384u, src, 16384, fb);
                TR(32 + n);
            }
            e_arrive_tx(BAR(B_WPHI), 32768);
            mbar_wait(BAR(B_ED), 1);
            tma_load(sb + OFF_R0, &tmX, hg * 128, rb * 128, BAR(B_WPHI));
            tma_load(sb + OFF_X1, &tmX, hg * 128 + 64, rb * 128, BAR(B_WPHI));
            GT(6);
            mbar_wait(BAR(B_CAND), 0);
            GT(7);
            const uint2 lc = lds64(sb + OFF_CST + 16);
            const uint32_t w0 = __shfl_sync(0xffffffffu, lc.x >> 4, 0), w1 = __shfl_sync(0xffffffffu, lc.y >> 4, 0);
            mbar_wait(BAR(B_SWP), 0);
            fence_async_smem();
            #pragma unroll 1
            for (uint32_t w = 0; w < 8; w++)
                if (w != w0 && w != w1) { tma_store4(&tmO, rb * 128 + w * 16, hg * 2, sb + OFF_OUT + w * 4096u); spin_until(clk32() + OUTGAP); }
            mbar_wait(BAR(B_SEL), 0);
            const uint2 sel = lds64(sb + OFF_CST + 24);
            #pragma unroll 1
            for (uint32_t i = 0; i < (w0 == w1 ? 8u : 16u); i++) {
                const uint32_t w = i < 8 ? w0 : w1, r = (i & 7) * 2 + (lane >> 4), row = rb * 128 + w * 16 + r;
                const uint4 o = lds128(sb + OFF_OUT + w * 4096u + ((lane >> 3) & 1) * 2048u + r * 128u + (((lane ^ r) & 7) << 4));
                if (row != (~sel.x & 2047u) && row != (~sel.y & 2047u)) stg128(p.out + (size_t)row * 1024 + hg * 128 + (lane & 15) * 8, o);
            }
            bulk_wait_read();
        } else if (warp == 14) {
            const uint32_t fb = ffn ? 65536 : 0;
            e_arrive_tx(BAR(B_GF), fb); e_arrive_tx(BAR(B_UD), ffn ? NUD * 8192 : 0); e_arrive_tx(BAR(B_UF), fb); e_arrive_tx(BAR(B_WD), fb);
            uint32_t due = cstart + WP1;
            #pragma unroll 1
            for (int i = -2; i < 26; i++) {
                if (i >= 0) {
                    const bf16* a = i < 8 ? p.wg + (size_t)(i * 128 + b) * 3584 : i < 16 ? p.wu + (size_t)((i - 8) * 128 + b) * 3584
                                  : i < 18 ? p.wo + (size_t)(b * 2 + i - 16) * 4096 : p.wd + (size_t)(b * 8 + i - 18) * 3584;
                    sleep_until(due);
                    l2_prefetch(a, (i >> 1) == 8 ? 8192 : 7168);
                    due += 7 * PFP;
                }
                if (i == 1) { tmap_prefetch(&tmPhi); tmap_prefetch(&tmG); tmap_prefetch(&tmWo); tmap_prefetch(&tmU); tmap_prefetch(&tmD); mbar_wait(BAR(B_STS), 0); }
                if (ffn && (uint32_t)(i - 3) < 8u) tma_load_ef(sb + OFF_R0 + (i - 3) * 8192u, &tmG, fs * 32, (i - 3) * 128, BAR(B_GF));
                if (ffn && (uint32_t)(i - 11) < NUD) tma_load(sb + OFF_WPHI, &tmU, fs * 32, (i - 11) * 128, BAR(B_UD));
                if (i == 19) { mbar_wait(BAR(B_UD), 0); e_arrive_tx(BAR(B_WPHI), 8192); tma_load(sb + OFF_WPHI, &tmPhi, 0, hg * 128, BAR(B_WPHI)); }
                if (i == LMP + 2 * (b & 3) + (b >> 6)) tma_prefetch(&tmM, 2048 + (b >> 6) * 2048 + (b >> 2) * 64, (b & 3) * 256);
                if (i < 13) {
                    sleep_until(due);
                    l2_prefetch(p.wqkv + (size_t)((i + 3) * 128 + b) * 1536, 3072);
                    due += i == -2 ? PF_START - WP1 : 3 * PFP;
                }
            }
            if (lane < 4) stg_zero(FLO(lane >> 1, b) + (lane & 1));
            const uint32_t tag = get_tag(sb);
            #pragma unroll 1
            for (int q = 0; q < 2; q++) {
                mbar_wait(BAR(B_OWN + q), 0);
                if (q) mbar_wait(BAR(B_FD + 2), 0);
                bulk_store(p.s->os + ((size_t)b * 2 + q) * 1024, sb + OFF_R0 + q * 16384u, 16384);
                mbar_wait(BAR(B_CS + q), 0);
                uint32_t chk = __reduce_xor_sync(0xffffffffu, lane < 8 ? lds32(sb + OFF_CHK + q * 32 + lane * 4) : 0u);
                bulk_wait();
                __syncwarp();
                st_flag(FLO(q, b), tag, chk, lane);
                TS(7 + q);
            }
            e_arrive(BAR(B_OST));
            fence_gpu();
            __syncwarp();
            st_flag(FLO(2, b), tag, 0, lane);
        } else {
            uint4* fk = p.s->flk + (hg * 16 + rb) * 2;
            if (warp == 13) {
                #pragma unroll 1
                for (int i = 0; i < 32; i++) {
                    const uint32_t s = i & 3;
                    if (i < NB0) spin_until(cstart + WL0 + WLS * i); else if (i == NB0) mbar_wait(BAR(B_STS), 0);
                    mbar_wait(BAR(B_EB + s), ((i >> 2) - 1) & 1);
                    e_arrive_tx(BAR(B_FB + s), 24576); tma_load4(sb + OFF_B + s * 24576u, &tmW, i * 32, hg * 2, BAR(B_FB + s));
                    TR(64 + i);
                }
                mbar_wait(BAR(B_EB), 1); mbar_wait(BAR(B_EB + 1), 1);
                e_arrive_tx(BAR(B_LMF), 32768); tma_load_ef(sb + OFF_DB, &tmM, 2048 + (b >> 6) * 2048 + (b >> 2) * 64, (b & 3) * 256, BAR(B_LMF));
            } else {
                sleep_until(cstart + CLR0);
                const uint32_t tag = get_tag(sb);
                #pragma unroll 1
                for (int i = lane; i < 132; i += 32) stg_zero(p.s->kvacc + hg * 2112 + rb * 132 + i);
                if (lane < 4) stg_zero(fk + 256 + (lane >> 1) * 256 + (lane & 1));
                fence_gpu();
                __syncwarp();
                st_flag(fk, tag, 0, lane);
                sleep_until(clk32() + 2000);
                poll_flags(p.s->flk + (hg * 16 + (lane & 15)) * 2, tag);
                mbar_wait(BAR(B_QE), 0);
                #pragma unroll 1
                for (int i = 0; i < 4; i++) {
                    stg_zero(p.s->llln2 + b * 128 + i * 32 + lane);
                    stg_zero(p.s->llrowh + (i >> 1) * 8192 + (rb * 2 + (i & 1)) * 256 + hg * 32 + lane);
                    #pragma unroll
                    for (int k = 0; k < 4; k++) stg_zero(p.s->lly + (fs & 127) * 512 + i * 128 + k * 32 + lane);
                }
                if (lane < 2 && hg == (rb & 7)) stg_zero(p.s->llcand + rb * 2 + lane);
                __syncwarp();
                e_arrive(BAR(B_KZ));
            }
            const int q = warp == 13;
            const uint32_t tag = get_tag(sb);
            mbar_wait(BAR(B_KZ), 0);
            #pragma unroll 1
            for (int h = 2 * q; h < 2 * q + 2; h++) {
                mbar_wait(BAR(B_KST + h), 0);
                uint4* acc = p.s->kvacc + (hg * 4 + h) * 528;
                bulk_reduce(acc, sb + (h ? OFF_V + (h - 1) * 8192u : OFF_KL), 8192); bulk_reduce(acc + 512, sb + OFF_ZS + h * 256u, 256);
            }
            bulk_wait();
            if (q) e_arrive(BAR(B_KZ));
            TR(158 + q);
            fence_gpu();
            __syncwarp();
            st_flag(fk + 256 + q * 256, tag, 0, lane);
            TS(10 + q);
            if (q) {
                #pragma unroll 1
                for (int n = 4; n < 16; n++) {
                    const uint32_t s = n & 3;
                    mbar_wait(BAR(B_ED + s), ((n >> 2) - 1) & 1);
                    e_arrive_tx(BAR(B_FD + s), 16384);
                    tma_load4(sb + OFF_DB + s * 16384u, &tmWo, d_kb(n, hg) * 64, hg * 2, BAR(B_FD + s));
                    TR(96 + n);
                    if (ffn && (uint32_t)(n - WD0) < 4u) {
                        #pragma unroll
                        for (int k = 0; k < 2; k++) tma_load_ef(sb + OFF_F2 + (n - WD0) * 8192u + k * 4096u, &tmD, (n - WD0) * 256 + k * 128, fs * 32, BAR(B_WD));
                    }
                }
                if (ffn) {
                    mbar_wait(BAR(B_ED + WDW), 1);
                    #pragma unroll 1
                    for (int z = 0; z < 8; z++) { tma_load_ef(sb + OFF_DB + z * 4096u, &tmD, z * 128 + 64, fs * 32, BAR(B_WD)); sleep_until(clk32() + WDGAP); }
                }
            } else {
                mbar_wait(BAR(B_LMD), 0);
                mbar_wait(BAR(B_KVL), 0);
                mbar_wait(BAR(B_KZ), 1);
                #pragma unroll 1
                for (int i = 0; i < 8; i++) {
                    const int n = i < 2 ? i : i < 6 ? i + 2 : i - 4;
                    if (i == 6) mbar_wait(BAR(B_KVT + 1), 0);
                    if (n < 4) { e_arrive_tx(BAR(B_FD + n), 16384); tma_load4(sb + OFF_DB + n * 16384u, &tmWo, d_kb(n, hg) * 64, hg * 2, BAR(B_FD + n)); }
                    else if (ffn) { tma_load_ef(sb + OFF_F2 + (7 - n) * 8192u, &tmU, fs * 32, (7 - n) * 128, BAR(B_UF)); sleep_until(clk32() + UPGAP); }
                }
                mbar_wait(BAR(B_OST), 0);
                sts32(sb + OFF_CHK + 68 + (lane & 7) * 8, poll_flags(FLO(1, rb * 8 + (lane & 7)), tag));
                __syncwarp();
                e_arrive(BAR(B_O1));
                TS(4);
            }
        }
    } else if (warp >= 8) {
        reg_dec<24>();
        const int rb = b >> 3, hg = b & 7, w4 = warp & 3, g = lane >> 2, c = lane & 3, t = tid & 127;
        const uint32_t sv = silu2(ldg32(p.c + (b & 3) * 256 + 2 * t)), tag = get_tag(sb);
        if (w4 < 3) {
            spin_until(cstart + MPOLL + MSTEP * w4);
            #pragma unroll 1
            for (int j = w4, ph = 1; j < 16; j += 3, ph ^= 1) {
                uint4 w[2];
                poll_words<2, 0, 3>(w, p.s->llm1 + j * 64 + lane, 32, tag);
                uint32_t lo = pack2(u2f(w[0].x) + u2f(w[1].x), u2f(w[0].y) + u2f(w[1].y)), hi = pack2(u2f(w[0].z) + u2f(w[1].z), u2f(w[0].w) + u2f(w[1].w));
                if (lane >= 16) { lo = hadd2(lo, ONE2); hi = hadd2(hi, ONE2); }
                sts64(sb + OFF_TAB + j * 256 + (lane & 15) * 16 + (lane < 16 ? 8 : 0), lo, hi);
                __syncwarp();
                if (j == 0) TS(5);
                TR(16 + j);
                mbar_wait(BAR(B_EA + w4), ph);
                e_arrive(BAR(B_FA + w4));
                __nanosleep(MSLP);
            }
        }
        mbar_wait(BAR(B_QE), 0);
        if (warp == 8) GT(3);
        sts32(sb + OFF_Z + w4 * 1024u + lane * 4, sv);
        reg_inc<56>();
        #pragma unroll 1
        for (int h = 0; h < 4; h++) {
            float okv[20];
            const uint32_t vb = OFF_V + h * 8192u, dp = desc_lo(sb + OFF_PHI + (h & 1) * 16384u, 16), dv = desc_lo(sb + vb, OFF_ONES - vb);
            const uint32_t xa = sb + (h ? vb - 8192u : OFF_KL) + t * 16u;
            if (h) mbar_wait(BAR(B_KST - 1 + h), 0);
            mbar_wait(BAR(B_PF + h), 0);
            fence_async_smem();
            wg_fence();
            #define KVS(i) mma40_tt<(i) * 128, H128, (i) * (64u - (64u << 16)), H64>(okv, dp, dv)
            mma40_tt0<0, H128, 0, H64>(okv, dp, dv); KVS(1); KVS(2); KVS(3); KVS(4); KVS(5); KVS(6); KVS(7);
            #undef KVS
            wg_commit();
            wg_wait<0>();
            acc_fence(okv);
            #pragma unroll
            for (int k = 0; k < 4; k++) sts128(xa + k * 2048u, make_uint4(f2u(okv[4 * k]), f2u(okv[4 * k + 1]), f2u(okv[4 * k + 2]), f2u(okv[4 * k + 3])));
            if (c == 0) sts64(sb + OFF_ZS + h * 256u + (w4 * 8 + g) * 8u, f2u(okv[16]), f2u(okv[18]));
            fence_async_smem();
            __syncwarp();
            e_arrive(BAR(B_KST + h));
            if (warp == 8) TR(151 + h);
        }
        {
            float m0[4], m1[4];
            const uint32_t da = desc_lo(sb + OFF_DB, 16), db = desc_lo(sb + OFF_Z, 16);
            mbar_wait(BAR(B_LMF), 0);
            wg_fence();
            #define LMS(f, i) f<(i) * 256, H128, ((i) >> 1) * 64 + ((i) & 1) * 4, H128>(m0, da, db); f<(i) * 256 + 128, H128, ((i) >> 1) * 64 + ((i) & 1) * 4 + 2, H128>(m1, da, db)
            LMS(mma8_tn0, 0); LMS(mma8_tn, 1); LMS(mma8_tn, 2); LMS(mma8_tn, 3); LMS(mma8_tn, 4); LMS(mma8_tn, 5); LMS(mma8_tn, 6); LMS(mma8_tn, 7);
            #undef LMS
            wg_commit();
            wg_wait<0>();
            acc_fence(m0); acc_fence(m1);
            e_arrive(BAR(B_LMD));
            const float v0 = m0[0] + m1[0], v1 = m0[2] + m1[2], u0 = shfl_x(v0, 4), u1 = shfl_x(v1, 4);
            if (!(lane & 7)) st_ll4(p.s->llg + (b >> 6) * 1024 + (b & 3) * 256 + ((b >> 2) & 15) * 16 + w4 * 4 + (lane >> 3), v0, u0, v1, u1, tag);
            if (warp == 8) TR(150);
        }
        e_arrive(BAR(B_ED)); e_arrive(BAR(B_ED + 1));
        mbar_wait(BAR(B_LMD), 0);
        #pragma unroll 1
        for (int q = 0; q < 2; q++) {
            const uint32_t f = w4 * 16 + g, kl = sb + (q ? OFF_KL1 : OFF_KL), ta = sb + (q ? OFF_KL : OFF_KVT) + f * 64u + ((g >> 1) << 4) + 4 * c;
            const uint32_t za = sb + OFF_Z + (f + 8 * (c & 1)) * 64u + (((2 * q) ^ (g >> 1)) << 4) + (c >> 1) * 8;
            mbar_wait(q ? BAR(B_KVT) : BAR(B_STP), q ^ 1);
            mbar_wait(BAR(B_KVL + q), 0);
            uint4 v[8]; float z[2];
            #pragma unroll
            for (int k = 0; k < 8; k++) v[k] = lds128(kl + (k >> 2) * 8448u + (k & 3) * 2048u + t * 16u);
            #pragma unroll
            for (int hh = 0; hh < 2; hh++) z[hh] = ldsf(kl + hh * 8448u + 8192u + (w4 * 8 + g) * 8u + (c & 1) * 4);
            #pragma unroll
            for (int k = 0; k < 8; k++) {
                sts32((ta ^ ((k & 3) << 4)) + (k >> 2) * 4096u, pack2(u2f(v[k].x), u2f(v[k].y))); sts32((ta ^ ((k & 3) << 4)) + (k >> 2) * 4096u + 512, pack2(u2f(v[k].z), u2f(v[k].w)));
            }
            #pragma unroll
            for (int hh = 0; hh < 2; hh++) { const uint32_t zz = pack2(z[hh], z[hh]); sts64(za ^ (hh << 4), zz, zz); }
            fence_async_smem();
            __syncwarp();
            e_arrive(BAR(B_KVT + q));
            if (warp == 8) TR(155 + q);
        }
        reg_dec<24>();
        if (w4 == 0 || w4 == 3) {
            float s[4] = {0.f, 0.f, 0.f, 0.f};
            #pragma unroll 1
            for (int k = 0; k < 2; k++) {
                uint4 w[2];
                poll_words<2, 0, 3>(w, p.s->llg + (w4 & 1) * 1024 + k * 512 + hg * 32 + lane, 256, tag);
                s[0] += u2f(w[0].x) + u2f(w[1].x); s[1] += u2f(w[0].y) + u2f(w[1].y); s[2] += u2f(w[0].z) + u2f(w[1].z); s[3] += u2f(w[0].w) + u2f(w[1].w);
            }
            const uint32_t lo = pack2(s[0], s[1]), hi = pack2(s[2], s[3]);
            sts64(w4 ? sb + OFF_T3 + lane * 8 : sb + OFF_T1 + lane * 16, lo, hi);
            if (!w4) sts64(sb + OFF_T1 + 512 + lane * 16, lo, hi);
        }
        if (w4 == 1 || w4 == 2) {
            const bf16* wr = p.wr + hg * 128 + g * 16 + 2 * c;
            const uint32_t wr0 = ldg32(wr), wr1 = ldg32(wr + 8);
            uint4 w[2];
            poll_words<2, 1>(w, p.s->llmod2 + (w4 - 1) * 256 + hg * 32 + lane, (lane & 15) * 16 - hg * 32 - lane, tag);
            sts64(sb + OFF_T2 + lane * 16 + (w4 & 1) * 8, w[0].x, w[0].y);
            if (w4 == 2) sts64(sb + OFF_T1 + 512 + lane * 16 + 8, hmul2(w[0].x, wr0), hmul2(w[0].y, wr1));
            float d = u2f(w[1].z);
            #pragma unroll 1
            for (int k = 1; k < 16; k <<= 1) d += shfl_x(d, k);
            stsf(sb + OFF_CST + 8 + (w4 & 1) * 4, d);
        }
        if (warp == 10) TS(6);
        {
            const uint32_t a = sb + w4 * 4096u + g * 128u + (((2 * c) ^ g) << 4) + (g >> 1) * 4;
            uint32_t x = 0;
            #pragma unroll 1
            for (int n = 2; n < 16; n++) {
                const uint32_t ta = a + (n == 5 ? OFF_X1 : OFF_R0 + (n & 3) * 16384u), ca = sb + OFF_CHK + 64 + d_kb(n, hg) * 4;
                mbar_wait(BAR(B_FD + (n & 3)), (n >> 2) & 1);
                const uint32_t v0 = lds32(ta), v1 = lds32(ta + 1024), v2 = lds32(ta + 2048), v3 = lds32(ta + 3072);
                x = __funnelshift_l(x, x, 1) ^ v0 ^ v1 ^ v2 ^ v3;
                e_arrive_after(BAR(B_ED + (n & 3)), x);
                if (t == 0) x ^= lds32(ca);
            }
            sts32(sb + OFF_CHK + 128 + w4 * 4, __reduce_xor_sync(0xffffffffu, x));
        }
        __syncwarp();
        e_arrive(BAR(B_PAR));
        if (w4 < 2) {
            mbar_wait(BAR(B_PAR), 0);
            const uint4 ta = lds128(sb + OFF_T2 + lane * 16);
            const uint2 gb = lds64(sb + OFF_T3 + lane * 8);
            uint4* d = pin_ptr(p.s->llrowh + (rb * 2 + w4) * 256 + hg * 32 + lane);
            mbar_wait(BAR(B_KEYS), 0);
            const uint4 kk = lds128(sb + OFF_KEY + lane * 16);
            uint32_t k[4] = {kk.x, kk.y, kk.z, kk.w}, b0, b1;
            top2<4>(k, b0, b1);
            const uint32_t cd = ~(w4 ? b1 : b0) & 127u;
            const uint32_t xa = sb + OFF_R0 + (g >> 2) * (OFF_X1 - OFF_R0) + cd * 128u + ((((g & 3) * 2) ^ (cd & 7)) << 4) + c * 4;
            const uint32_t x0 = lds32(xa), x1 = lds32(xa ^ 16);
            const uint4 st = lds128(sb + OFF_ST2 + cd * 16);
            st_ll(d, lnmod(x0, st.x, st.y, st.z, ta.x, ta.z), lnmod(x1, st.x, st.y, st.z, ta.y, ta.w), gb.x, tag);
            st_ll(d + 8192, x0, x1, gb.y, tag);
            sts32(sb + OFF_CST + 16 + w4 * 4, cd);
            __syncwarp();
            e_arrive(BAR(B_CAND));
            if (warp == 8) TS(9);
        } else if (w4 == 2) {
            uint4* cp = pin_ptr(p.s->llcand + lane);
            mbar_wait(BAR(B_KEYS), 0);
            if (hg == (rb & 7)) {
                const uint4 kk = lds128(sb + OFF_KEY + lane * 16);
                uint32_t k[4] = {kk.x, kk.y, kk.z, kk.w}, b0, b1;
                top2<4>(k, b0, b1);
                if ((lane >> 1) == rb) st_ll(cp, tag, (lane & 1) ? b1 : b0, tag, tag);
            } else spin_until(clk32() + CWAIT);
            uint32_t k[1] = {poll_flags(cp, tag)}, b0, b1;
            top2<1>(k, b0, b1);
            sts64(sb + OFF_CST + 24, b0, b1);
            __syncwarp();
            e_arrive(BAR(B_SEL));
        }
    } else {
        reg_inc<232>();
        float a0[96], a1[96];
        {
            const int g = lane >> 2, c = lane & 3;
            uint4* stp = p.s->llstat + b * 16 + warp * 2 + (lane >> 4);
            if (lane == 0 || lane == 18) stg_zero(stp);
            spin_until(cstart + XD + XSTEP * warp);
            e_arrive_tx(BAR(B_XP + warp), 4096);
            bulk_load(sb + OFF_R0 + warp * 4096u, p.x + (size_t)(b * 16 + 2 * warp) * 1024, 4096, BAR(B_XP + warp));
            const uint32_t tag = get_tag(sb);
            if (tid < 64) sts128(sb + OFF_ONES + tid * 16, make_uint4(ONE2, ONE2, ONE2, ONE2));
            if (tid == 64) { sts64(sb + OFF_CST, role, tag); stsf(sb + OFF_CST + 48, -LOG2E); }
            if (AWAKE & 1) mbar_wait_awake(BAR(B_XP + warp), 0); else mbar_wait(BAR(B_XP + warp), 0);
            e_arrive(BAR(B_STP));
            if (warp == 7) TS(14);
            float s[2][4], q0[2][4], q1[2][4];
            #pragma unroll
            for (int i = 0; i < 4; i++) s[0][i] = s[1][i] = q0[0][i] = q0[1][i] = q1[0][i] = q1[1][i] = 0.f;
            uint32_t xa[8][4], xb[8][4];
            const uint32_t la = sb + OFF_R0 + warp * 4096u + (lane & 7) * 16u;
            #pragma unroll
            for (int i = 0; i < 8; i++) {
                ldsm4(xa[i], la + ((lane >> 3) & 1) * 2048u + (lane >> 4) * 128u + i * 256u);
                ldsm4(xb[i], la + ((lane >> 3) & 1) * 128u + (lane >> 4) * 2048u + i * 256u);
            }
            #pragma unroll
            for (int i = 0; i < 8; i++) {
                mma16816(q0[i & 1], xa[i][0], xa[i][1], xa[i][2], xa[i][3], xb[i][0], xb[i][1]);
                mma16816(q1[i & 1], xa[i][0], xa[i][1], xa[i][2], xa[i][3], xb[i][2], xb[i][3]);
                mma16816(s[i & 1], xa[i][0], xa[i][1], xa[i][2], xa[i][3], ONE2, ONE2);
            }
            const float s0 = s[0][0] + s[1][0], s1 = s[0][2] + s[1][2];
            const float sq0 = (g & 1) ? q0[0][1] + q0[1][1] : q0[0][0] + q0[1][0], sq1 = (g & 1) ? q1[0][3] + q1[1][3] : q1[0][2] + q1[1][2];
            const bool up = lane >= 16;
            float sm = (up ? s1 : s0) + shfl_x(up ? s0 : s1, 18), sq = (up ? sq1 : sq0) + shfl_x(up ? sq0 : sq1, 18);
            sm += shfl_x(sm, 9); sq += shfl_x(sq, 9);
            sm += shfl_x(sm, 4); sq += shfl_x(sq, 4);
            uint32_t m2, rh, rl; float rinv;
            ln_final(sm, sq, m2, rinv);
            split_rcp(rinv, rh, rl);
            if (lane == 0 || lane == 18) st_ll(stp, m2, rh, rl, tag);
            if (warp == 7) TS(15);
            uint4 st[2];
            if (PWAIT) { mbar_wait(BAR(B_STP), 0); if (warp < 7) spin_until(clk32() + PWAIT); }
            #pragma unroll 1
            for (int it = 0; it < POLL_MAX; it++) {
                st[0] = ld_ll(p.s->llstat + (b >> 3) * 128 + warp * 16 + g); st[1] = ld_ll(p.s->llstat + (b >> 3) * 128 + warp * 16 + g + 8);
                const uint32_t o = RDV ? ld_rlx(&p.s->llstat[((b >> 5) * 4 + c) * 128 + warp * 16 + 15].w) : tag;
                if (__all_sync(0xffffffffu, !tag_bad(tag_bad(o ^ tag, st[0].w, tag), st[1].w, tag))) break;
                if (AWAKE & 1) it += awake_zero();
            }
            e_arrive(BAR(B_STS));
            if (warp == 0) TS(16);
            const uint32_t lrow = warp * 16 + (lane & 15);
            uint32_t aad = sb + OFF_A + lrow * 128u + (((lane >> 4) ^ (lrow & 7)) << 4);
            uint32_t tad = sb + OFF_TAB + c * 16, ab = BAR(B_FA), pa = 0;
            uint32_t f0[4], f1[4];
            #define PREP(f, q) do { \
                const uint4 t = lds128(tad + (q) * 64); \
                ldsm4(f, aad ^ ((q) << 5)); \
                f[0] = lnmod(f[0], st[0].x, st[0].y, st[0].z, t.x, t.z); f[1] = lnmod(f[1], st[1].x, st[1].y, st[1].z, t.x, t.z); \
                f[2] = lnmod(f[2], st[0].x, st[0].y, st[0].z, t.y, t.w); f[3] = lnmod(f[3], st[1].x, st[1].y, st[1].z, t.y, t.w); } while (0)
            #define MMA(f, off) do { wg_fence(); mma192_rs<(off), H128>(a0, f, blo); mma192_rs<(off) + 768, H128>(a1, f, blo); wg_commit(); wg_wait<1>(); } while (0)
            mbar_wait(ab, 0);
            PREP(f0, 0);
            if (RDV) mbar_wait(BAR(B_STS), 0);
            #pragma unroll 1
            for (int j = 0; j < 16; j++) {
                const uint32_t bb = BAR(B_FB) + (j & 1) * 16, blo = desc_lo(sb + OFF_B, 4096) + (j & 1) * 3072, pb = (j >> 1) & 1;
                mbar_wait(bb, pb);
                wg_fence(); mma192_rsp<0, H128>(a0, f0, blo, j); mma192_rsp<768, H128>(a1, f0, blo, j); wg_commit(); wg_wait<1>();
                if (j) e_arrive((bb ^ 16) + 8 * (B_EB - B_FB) + 8);
                PREP(f1, 1);
                MMA(f1, 128);
                PREP(f0, 2);
                mbar_wait(bb + 8, pb);
                MMA(f0, 1536);
                e_arrive(bb + 8 * (B_EB - B_FB));
                PREP(f1, 3);
                MMA(f1, 1536 + 128);
                e_arrive(ab + 8 * (B_EA - B_FA));
                ab += 8; aad += 16384; tad += 256;
                if (ab == BAR(B_FA + 3)) { ab -= 24; aad -= 49152; pa ^= 1; }
                if (j < 15) mbar_wait(ab, pa);
                PREP(f0, 0);
            }
            #undef PREP
            #undef MMA
        }
        int tid_o; asm volatile("mov.u32 %0, %%tid.x;" : "=r"(tid_o) :: "memory");
        const int tid = tid_o, lane = tid & 31, warp = __shfl_sync(0xffffffffu, tid >> 5, 0), wgi = warp >> 2, g = lane >> 2, c = lane & 3;
        const uint32_t srow = warp * 16 + (lane & 15);
        #define T128(t) (sb + (((t) >> 5) * 16 + ((t) & 15)) * 128u + (((((t) >> 4) & 1) ^ ((t) & 7)) << 4))
        const uint32_t pa = T128(tid);
        mbar_wait(BAR(B_WPHI), 0);
        mbar_wait(BAR(B_EB + 2), 1);
        wg_wait<0>();
        acc_fence(a0); acc_fence(a1);
        e_arrive(BAR(B_QE));
        if (warp == 0) TS(18);
        uint32_t ph[4][16];
        {
            uint32_t f1[16], kq[32], pk[16], mm[4], mn[2];
            float ea[32], eb[32], p0[16], p1[16];
            const uint32_t dw = desc_lo(sb + OFF_WPHI, 16);
            #define PMMA(f, o) do { wg_fence(); mma32_rs0<(o), H64>(p0, f, dw); mma32_rs0<(o) + 128, H64>(p1, f + 8, dw); \
                mma32_rs<(o) + 64, H64>(p0, f + 4, dw); mma32_rs<(o) + 192, H64>(p1, f + 12, dw); wg_commit(); } while (0)
            #define PWAIT0() do { wg_wait<0>(); acc_fence(p0); acc_fence(p1); } while (0)
            #define V_OUT(lo, n) _Pragma("unroll") for (int i = lo; i < lo + n; i++) { const int o = 32 + 8 * i; \
                stsm4(sb + OFF_V + (i >> 1) * 8192u + srow * 64u + (((2 * (i & 1) + (lane >> 4)) ^ ((srow >> 1) & 3)) << 4), \
                      pack2(a1[o], a1[o + 1]), pack2(a1[o + 2], a1[o + 3]), pack2(a1[o + 4], a1[o + 5]), pack2(a1[o + 6], a1[o + 7])); }
            V_OUT(0, 4);
            #pragma unroll
            for (int i = 0; i < 16; i++) pk[i] = pack2(a0[64 + 2 * i], a0[65 + 2 * i]);
            PMMA(pk, 0);
            V_OUT(4, 2);
            #pragma unroll
            for (int i = 0; i < 16; i++) f1[i] = pack2(a1[2 * i], a1[2 * i + 1]);
            #pragma unroll
            for (int i = 0; i < 32; i++) kq[i] = pack2(a0[2 * i], a0[2 * i + 1]);
            mbar_wait(BAR(B_QE), 0);
            V_OUT(6, 2);
            #undef V_OUT
            PWAIT0();
            reg_dec<216>();
            if (warp == 0) TS(19);
            #define PHI_OUT(h) do { if (u == 0) { \
                    if ((h) >= 2) mbar_wait(BAR(B_KST + ((h) & 1)), 0);          \
                    _Pragma("unroll") for (int q = 0; q < 4; q++) stsm4((pa ^ (q << 5)) + OFF_PHI + ((h) & 1) * 16384u, ph[h][4 * q], ph[h][4 * q + 1], ph[h][4 * q + 2], ph[h][4 * q + 3]); \
                    __syncwarp(); \
                    e_arrive(BAR(B_PF + (h))); } } while (0)
            #define NL() ldsf(sb + OFF_CST + 48)
            #pragma unroll 1
            for (int u = 0; u < 2; u++) {
                fm_max(p0, pk, mm); fm_max(p1, pk + 8, mm + 2);
                PMMA(f1, 256);
                fm_pos(pk, mm, ea);
                acc_fence(ea);
                PWAIT0();
                if (u) e_arrive(BAR(B_STP));
                fm_neg(mm, NL(), ea); fm_pos(pk + 8, mm + 2, eb);
                fm_norm(ea, ph[0]); fm_max(p0, pk, mm);
                PHI_OUT(0);
                fm_neg(mm + 2, NL(), eb); fm_pos(pk, mm, ea);
                fm_norm(eb, ph[1]); fm_max(p1, pk + 8, mn);
                PHI_OUT(1);
                if (warp == 0) TS(21 + 2 * u);
                fm_neg(mm, NL(), ea); fm_pos(pk + 8, mn, eb);
                fm_norm(ea, ph[2]);
                PHI_OUT(2);
                PMMA(kq, 0);
                fm_neg(mn, NL(), eb);
                fm_norm(eb, ph[3]);
                PHI_OUT(3);
                PWAIT0();
                #pragma unroll
                for (int i = 0; i < 16; i++) f1[i] = kq[16 + i];
                if (warp == 0) TS(22 + 2 * u);
            }
            #undef NL
            #undef PHI_OUT
            #undef PWAIT0
            #undef PMMA
        }
        uint32_t gf[16][4], uf[16][4];
        const uint32_t fo = sb + (warp >> 1) * 2048u + ((lane & 7) + (lane >> 4) * 8) * 64u + (((2 * (warp & 1) + ((lane >> 3) & 1)) ^ ((lane >> 1) & 3)) << 4);
        #define F_LOAD(f, off, i) ldsm4t(f[i], fo + (off) + ((i) >> 1) * 8192u + ((i) & 1) * 1024u)
        #define G_LOAD(lo, n) _Pragma("unroll") for (int i = lo; i < lo + n; i++) F_LOAD(gf, OFF_R0, i)
        #define O_BLOCK(pp, ph0, ph1) do { \
            if ((AWAKE & 2) && !(pp)) mbar_wait_awake(BAR(B_KVT + (pp)), 0); else mbar_wait(BAR(B_KVT + (pp)), 0); \
            if (warp == 0) TS(25 + 3 * (pp)); \
            const uint32_t oa = T128(tid + (lds32(sb + OFF_CST) >> 16)); \
            float o0[20], o1[20]; \
            const uint32_t dk = (pp) ? desc_lo(sb + OFF_KL, OFF_Z + 32 - OFF_KL) : desc_lo(sb + OFF_KVT, OFF_Z - OFF_KVT); \
            constexpr uint32_t K1 = 256u - (255u << 16);          \
            wg_fence(); \
            mma40_rs0<0, H64>(o0, ph0, dk); mma40_rs0<K1, H64>(o1, ph1, dk); \
            mma40_rs<64, H64>(o0, ph0 + 4, dk); mma40_rs<K1 + 64, H64>(o1, ph1 + 4, dk); \
            mma40_rs<128, H64>(o0, ph0 + 8, dk); mma40_rs<K1 + 128, H64>(o1, ph1 + 8, dk); \
            mma40_rs<192, H64>(o0, ph0 + 12, dk); mma40_rs<K1 + 192, H64>(o1, ph1 + 12, dk); \
            wg_commit(); \
            wg_wait<0>(); \
            acc_fence(o0); acc_fence(o1); \
            if (pp) e_arrive(BAR(B_ED)); \
            if (warp == 0) TS(26 + 3 * (pp)); \
              \
            if (pp) { G_LOAD(12, 4); } \
            mbar_wait(BAR(B_GE + (pp)), 0);          \
            uint32_t chk = 0; \
            _Pragma("unroll") for (int hh = 0; hh < 2; hh++) { \
                const float (&o)[20] = hh ? o1 : o0; \
                uint32_t h0, l0, h1, l1; \
                split_rcp(rcp(rbf(rbf(o[16]) + 1e-6f)), h0, l0); split_rcp(rcp(rbf(rbf(o[18]) + 1e-6f)), h1, l1); \
                _Pragma("unroll") for (int q = 0; q < 2; q++) { \
                    const uint32_t r0 = hdiv2(pack2(o[8 * q], o[8 * q + 1]), h0, l0), r1 = hdiv2(pack2(o[8 * q + 2], o[8 * q + 3]), h1, l1); \
                    stsm4((oa ^ ((2 * hh + q) << 5)) + OFF_R0 + (pp) * 16384u, r0, r1, \
                          hdiv2(pack2(o[8 * q + 4], o[8 * q + 5]), h0, l0), hdiv2(pack2(o[8 * q + 6], o[8 * q + 7]), h1, l1)); \
                    chk ^= r0 ^ r1; \
                } \
            } \
            fence_async_smem(); \
            __syncwarp(); \
            e_arrive(BAR(B_OWN + (pp))); \
            sts32(sb + OFF_CHK + (pp) * 32 + warp * 4, __reduce_xor_sync(0xffffffffu, c == (g >> 1) ? chk : 0u)); \
            if (!(pp)) { G_LOAD(4, 8); fence_async_smem(); } \
            __syncwarp(); \
            e_arrive(BAR(B_CS + (pp))); \
            if (warp == 0) TS(27 + 3 * (pp)); \
        } while (0)
        float acc[64];
        const uint32_t da = desc_lo(sb + OFF_R0 + wgi * 8192u, 16), db = desc_lo(sb + OFF_DB, 8192);
        #define D_MMA(first, a, s) do { \
            wg_fence(); \
            first<(a), H128, (s) * 1024, H128>(acc, da, db); mma128_ss<(a) + 2, H128, (s) * 1024 + 128, H128>(acc, da, db); \
            mma128_ss<(a) + 4, H128, (s) * 1024 + 256, H128>(acc, da, db); mma128_ss<(a) + 6, H128, (s) * 1024 + 384, H128>(acc, da, db); \
            wg_commit(); } while (0)
        mbar_wait(BAR(B_GF), 0);
        G_LOAD(0, 4);
        e_arrive(BAR(B_GE));
        O_BLOCK(0, ph[0], ph[1]);
        mbar_wait(BAR(B_OWN), 0);
        mbar_wait(BAR(B_FD), 0);
        D_MMA(mma128_ss0, 0, 0);
        O_BLOCK(1, ph[2], ph[3]);
        reg_inc<232>();
        mbar_wait(BAR(B_OWN + 1), 0);
        #undef O_BLOCK
        #define D_STEP(n) do { \
            mbar_wait(BAR(B_FD + ((n) & 3)), ((n) >> 2) & 1); \
            if (warp == 0) TR(112 + (n)); \
            D_MMA(mma128_ss, (n) == 5 ? OFF_X1 / 16 : ((n) & 3) * 1024, (n) & 3); \
            if ((n) == UPS) mbar_wait(BAR(B_UF), 0); \
            if ((n) >= UPS && (n) < UPS + 2) { _Pragma("unroll") for (int i = 0; i < 4; i++) F_LOAD(uf, OFF_F2, 4 * (((n) - UPS) & 1) + i); } \
            wg_wait<1>(); \
            if ((n) == UPS + 2) fence_async_smem();         \
            if ((n) > 2) e_arrive(BAR(B_ED + (((n) + 3) & 3))); } while (0)
        D_STEP(1);
        wg_wait<0>();
        e_arrive(BAR(B_ED + 1));
        D_STEP(2);
        if (warp == 0) TS(31);
        D_STEP(3); D_STEP(4); D_STEP(5); D_STEP(6); D_STEP(7); D_STEP(8); D_STEP(9); D_STEP(10); D_STEP(11); D_STEP(12); D_STEP(13); D_STEP(14); D_STEP(15);
        #undef D_STEP
        #undef D_MMA
        mbar_wait(BAR(B_PAR), 0);
        const uint4 mis = lds128(sb + OFF_CHK + 128);
        if (mis.x ^ mis.y ^ mis.z ^ mis.w) {
            const uint2 rt = lds64(sb + OFF_CST);
            const int rb = (rt.x >> 3) & 15;
            wg_wait<0>();
            poll_flags(FLO(2, rb * 8 + (lane & 7)), rt.y);
            #pragma unroll 1
            for (int kb = 0; kb < 16; kb++) {
                bar_sync(1, 256);
                if (warp == 0) {
                    e_arrive_tx(BAR(B_RD), 32768);
                    bulk_load(sb + OFF_R0 + 32768, p.s->os + (size_t)(rb * 16 + kb) * 1024, 16384, BAR(B_RD));
                    tma_load4(sb + OFF_DB + 32768, &tmWo, kb * 64, (rt.x & 7) * 2, BAR(B_RD));
                }
                mbar_wait(BAR(B_RD), kb & 1);
                wg_fence();
                mma128_ssp<2048, H128, 2048, H128>(acc, da, db, kb); mma128_ss<2050, H128, 2048 + 128, H128>(acc, da, db);
                mma128_ss<2052, H128, 2048 + 256, H128>(acc, da, db); mma128_ss<2054, H128, 2048 + 384, H128>(acc, da, db);
                wg_commit();
                wg_wait<0>();
            }
        }
        #define XADDR(i) ((xa ^ (((i) & 3) << 5)) + ((i) < 4 ? OFF_R0 : OFF_X1))
        const uint4 cst = lds128(sb + OFF_CST);
        const int b = cst.x & 255;
        const uint32_t tag = cst.y, xa = T128(tid + (cst.x >> 16));
        uint32_t fx, fh, fg, fs2, frow;
        uint4 w[4];
        const uint32_t rl = warp * 16 + g + 8 * (c & 1);
        const uint4* ws = pin_ptr(p.s->llln2 + ((b & ~7) + (c >> 1) * 4) * 128 + rl);
        {
        {
            uint32_t x2[8][4];
            mbar_wait(BAR(B_WPHI), 1);
            #pragma unroll
            for (int i = 0; i < 8; i++) ldsm4(x2[i], XADDR(i));
            uint4* d = pin_ptr(p.s->llln2 + b * 128 + warp * 16 + g);
            const uint32_t ta = sb + OFF_T1 + (g & 1) * 512 + c * 16;
            uint4 t = lds128(ta), tn = lds128(ta + 64);
            wg_wait<0>();
            acc_fence(acc);
            e_arrive(BAR(B_ED + 3));
            if (warp == 0) TS(32);
            float sd[4] = {0.f, 0.f, 0.f, 0.f}, qa[4] = {0.f, 0.f, 0.f, 0.f}, qb[4] = {0.f, 0.f, 0.f, 0.f};
            #pragma unroll
            for (int i = 0; i < 8; i++) {
                x2[i][0] = hadd2(x2[i][0], hmul2(t.x, pack2(acc[8 * i], acc[8 * i + 1]))); x2[i][1] = hadd2(x2[i][1], hmul2(t.x, pack2(acc[8 * i + 2], acc[8 * i + 3])));
                x2[i][2] = hadd2(x2[i][2], hmul2(t.y, pack2(acc[8 * i + 4], acc[8 * i + 5]))); x2[i][3] = hadd2(x2[i][3], hmul2(t.y, pack2(acc[8 * i + 6], acc[8 * i + 7])));
                mma16816(sd, x2[i][0], x2[i][1], x2[i][2], x2[i][3], t.z, t.w);
                t = tn;
                if (i < 6) tn = lds128(ta + (i + 2) * 64);
                mma16816(qa, x2[i][0], x2[i][1], x2[i][2], x2[i][3], x2[i][0], x2[i][2]);
                mma16816(qb, x2[i][0], x2[i][1], x2[i][2], x2[i][3], x2[i][1], x2[i][3]);
            }
            if (c == (g >> 1)) {
                st_ll(d, f2u(sd[0]), f2u((g & 1) ? qa[1] : qa[0]), f2u(sd[1]), tag);
                st_ll(d + 8, f2u(sd[2]), f2u((g & 1) ? qb[3] : qb[2]), f2u(sd[3]), tag);
            }
            __syncwarp();
            #pragma unroll
            for (int i = 0; i < 4; i++) w[i] = ld_ll(ws + i * 128);
            if (warp == 0) TS(33);
            #pragma unroll
            for (int i = 0; i < 8; i++) stsm4(XADDR(i), x2[i][0], x2[i][1], x2[i][2], x2[i][3]);
        }
        uint4 t2[8]; uint2 t3[8];
        #define T_LOAD(lo, hi) _Pragma("unroll") for (int i = lo; i < hi; i++) { t2[i] = lds128(sb + OFF_T2 + i * 64 + c * 16); t3[i] = lds64(sb + OFF_T3 + i * 32 + c * 8); }
        #pragma unroll
        for (int i = 8; i < 16; i++) F_LOAD(uf, OFF_U1 - 32768, i);
        T_LOAD(0, SWA);
        mbar_wait(BAR(B_ED + 3), 1);
        {
            #pragma unroll 1
            for (int it = 0; it < POLL_MAX; it++) {
                if (__all_sync(0xffffffffu, !(tag_bad(w[0].w ^ tag, w[1].w, tag) | tag_bad(w[2].w ^ tag, w[3].w, tag)))) break;
                #pragma unroll
                for (int i = 0; i < 4; i++) if (w[i].w != tag) w[i] = ld_ll(ws + i * 128);
            }
            float s1 = (u2f(w[0].x) + u2f(w[1].x)) + (u2f(w[2].x) + u2f(w[3].x));
            float s2 = (u2f(w[0].y) + u2f(w[1].y)) + (u2f(w[2].y) + u2f(w[3].y));
            float dt = (u2f(w[0].z) + u2f(w[1].z)) + (u2f(w[2].z) + u2f(w[3].z));
            s1 += shfl_x(s1, 2); s2 += shfl_x(s2, 2); dt += shfl_x(dt, 2);
            uint32_t m2, rh, rl2; float rinv;
            ln_final(s1, s2, m2, rinv);
            const uint32_t key = (f2key(fmaf(fmaf(-bf_lo(m2), u2f(cst.z), dt), rinv, u2f(cst.w))) | 2047u) ^ ((b >> 3) * 128 + rl);
            split_rcp(rinv, rh, rl2);
            if (c < 2) { sts32(sb + OFF_KEY + rl * 4, key); sts128(sb + OFF_ST2 + rl * 16, make_uint4(m2, rh, rl2, 0)); }
            __syncwarp();
            e_arrive(BAR(B_KEYS));
        }
        if (warp == 0) TS(34);
        const uint4 s0 = lds128(sb + OFF_ST2 + (warp * 16 + g) * 16), s1 = lds128(sb + OFF_ST2 + (warp * 16 + g + 8) * 16);
        uint32_t x2[8][4];
        #pragma unroll
        for (int i = 0; i < 8; i++) ldsm4(x2[i], XADDR(i));
        const uint32_t oa = xa + warp * 2048u;
        #define SWEEP(lo, hi) _Pragma("unroll") for (int i = lo; i < hi; i++) { \
                const uint4 t = t2[i]; const uint2 gb = t3[i]; \
                stsm4((oa ^ ((i & 3) << 5)) + OFF_OUT + (i >> 2) * 2048u, \
                      hadd2(x2[i][0], hmul2(gb.x, lnmod(x2[i][0], s0.x, s0.y, s0.z, t.x, t.z))), hadd2(x2[i][1], hmul2(gb.x, lnmod(x2[i][1], s1.x, s1.y, s1.z, t.x, t.z))), \
                      hadd2(x2[i][2], hmul2(gb.y, lnmod(x2[i][2], s0.x, s0.y, s0.z, t.y, t.w))), hadd2(x2[i][3], hmul2(gb.y, lnmod(x2[i][3], s1.x, s1.y, s1.z, t.y, t.w)))); }
        SWEEP(0, 2);
        T_LOAD(SWA, 8);
        SWEEP(2, 8);
        __syncwarp();
        e_arrive(BAR(B_SWP));
        }
        uint32_t df[16][4];
        const uint32_t dfo = sb + warp * 4096u + ((lane & 7) + (lane >> 4) * 8) * 128u + ((((lane >> 3) & 1) ^ (lane & 7)) << 4);
        #define DF_LOAD(i) ldsm4t(df[i], (dfo + ((i) < 8 ? OFF_F2 : OFF_DB) + ((i) & 1) * 2048u) ^ ((((i) >> 1) & 3) << 5))
        if (warp == 0) TS(35);
        {
            const int wi = ((tid >> 3) & 7) * 32 + (tid >> 6) * 8 + (tid & 7);
            const uint4* rh = pin_ptr(p.s->llrowh + wi);
            mbar_wait(BAR(B_SEL), 0);
            const uint2 bb = lds64(sb + OFF_CST + 24);
            const uint32_t b0 = bb.x, b1 = bb.y;
            if (warp == 0) TS(36);
            const uint32_t o0 = (~b0 & 0x780u) * 4, o1 = (~b1 & 0x780u) * 4, slot0 = o0, slot1 = o1 + (o0 == o1 ? 256 : 0);
            const int wd = ((g & 1) ? slot1 : slot0) + b * 2 + (c >> 1) - wi;
            uint4 hv[2], fv[2];
            fv[0] = fv[1] = make_uint4(0, 0, 0, tag);
            #define R_LOAD() do { hv[0] = ld_ll(rh + slot0); hv[1] = ld_ll(rh + slot1); if (warp == 0) { fv[0] = ld_ll(rh + wd + 8192); fv[1] = ld_ll(rh + wd); } } while (0)
            R_LOAD();
            mbar_wait(BAR(B_WD), 0);
            #pragma unroll
            for (int i = 0; i < NDF; i++) DF_LOAD(i);
            #pragma unroll 1
            for (int it = 0; it < POLL_MAX; it++) {
                if (__all_sync(0xffffffffu, !ll_bad<1>(ll_bad<1>(tag_bad(fv[0].w ^ tag, fv[1].w, tag), hv[0], tag), hv[1], tag))) break;
                R_LOAD();
            }
            fx = (g & 2) ? fv[0].y : fv[0].x; fh = (g & 2) ? fv[1].y : fv[1].x; fg = (g & 2) ? fv[0].z : fv[1].z;
            const uint32_t ha = sb + OFF_HSEL + (tid >> 3) * 128u + c * 16u + (g & 1) * 8u;
            sts64(ha, hv[0].x, hv[0].y); sts64(ha + 64, hv[1].x, hv[1].y);
            bar_sync(2 + (warp >> 1), 64);
            const uint32_t bk = (g & 1) ? b1 : b0;
            frow = ~bk & 2047u;
            const float sg = sigmoid_f(rbf(key2f((bk & ~2047u) | 1024u)));
            fs2 = pack2(sg, sg);
        }
        if (warp == 0) TS(37);
        uint4* yd = p.s->lly + (cst.x >> 8) * 512 + (warp * 8 + c) * 8 + g;
        const uint4* ys = p.s->lly + (tid >> 2) * 512 + b * 4 + c;
        uint16_t* od = (uint16_t*)p.out + (size_t)frow * 1024 + (b >> 1) * 16 + (b & 1) * 4 + c + 8 * (g >> 1);
        {
            float ag[2][4], au[2][4];
            #pragma unroll
            for (int i = 0; i < 4; i++) ag[0][i] = ag[1][i] = au[0][i] = au[1][i] = 0.f;
            const uint32_t ha = sb + OFF_HSEL + (warp >> 1) * 1024u + (lane & 7) * 16u;
            uint4 hn = lds128(ha), hm = lds128(ha + 128);
            #pragma unroll
            for (int i = 0; i < 8; i++) {
                const uint4 h = hn;
                hn = hm;
                if (i < 6) hm = lds128(ha + (i + 2) * 128u);
                mma16816(ag[0], gf[2 * i][0], gf[2 * i][1], gf[2 * i][2], gf[2 * i][3], h.x, h.y);
                mma16816(au[0], uf[2 * i][0], uf[2 * i][1], uf[2 * i][2], uf[2 * i][3], h.x, h.y);
                mma16816(ag[1], gf[2 * i + 1][0], gf[2 * i + 1][1], gf[2 * i + 1][2], gf[2 * i + 1][3], h.z, h.w);
                mma16816(au[1], uf[2 * i + 1][0], uf[2 * i + 1][1], uf[2 * i + 1][2], uf[2 * i + 1][3], h.z, h.w);
                if (NDF + 2 * i < 16) { DF_LOAD((NDF + 2 * i) & 15); DF_LOAD((NDF + 2 * i + 1) & 15); }
            }
            sts64(sb + OFF_RED + (warp >> 1) * 512u + (c & 1) * 256u + ((warp & 1) * 16 + (c >> 1) * 8 + g) * 8u,
                  f2u(sel4(c, ag[0][0], ag[0][1], ag[0][2], ag[0][3]) + sel4(c, ag[1][0], ag[1][1], ag[1][2], ag[1][3])),
                  f2u(sel4(c, au[0][0], au[0][1], au[0][2], au[0][3]) + sel4(c, au[1][0], au[1][1], au[1][2], au[1][3])));
        }
        yd = pin_ptr(yd); ys = pin_ptr(ys); od = pin_ptr(od); pin<1>(&fs2);
        bar_sync(1, 256);
        {
            const uint32_t ra = sb + OFF_RED + lane * 16u;
            const uint4 r0 = lds128(ra), r1 = lds128(ra + 512), r2 = lds128(ra + 1024), r3 = lds128(ra + 1536);
            #define F4(f) ((u2f(r0.f) + u2f(r1.f)) + (u2f(r2.f) + u2f(r3.f)))
            const uint32_t hid = hmul2(silu2(pack2(F4(x), F4(z))), pack2(F4(y), F4(w)));
            #undef F4
            if (warp == 0) TS(38);
            const int src = (g & 1) * 16 + c;
            const uint32_t b0 = __shfl_sync(0xffffffffu, hid, src), b1 = __shfl_sync(0xffffffffu, hid, src + 4), b2 = __shfl_sync(0xffffffffu, hid, src + 8), b3 = __shfl_sync(0xffffffffu, hid, src + 12);
            float y[8][4];
            #pragma unroll
            for (int i = 0; i < 8; i++) {
                y[i][0] = y[i][1] = y[i][2] = y[i][3] = 0.f;
                mma16816(y[i], df[2 * i][0], df[2 * i][1], df[2 * i][2], df[2 * i][3], b0, b1);
            }
            #pragma unroll
            for (int i = 0; i < 8; i++) mma16816(y[i], df[2 * i + 1][0], df[2 * i + 1][1], df[2 * i + 1][2], df[2 * i + 1][3], b2, b3);
            if (cst.x < 112 * 256) {
                #pragma unroll
                for (int h = 0; h < 2; h++) {
                    #define YS(e) sel4(c, y[4 * h][e], y[4 * h + 1][e], y[4 * h + 2][e], y[4 * h + 3][e])
                    st_ll4(yd + 32 * h, YS(0), YS(1), YS(2), YS(3), tag);
                    #undef YS
                }
            }
        }
        if (warp == 0) TS(39);
        if (warp < 7) {
            uint4 v[2];
            v[0].w = v[1].w = 0;
            spin_until(clk32() + YWAIT);
            #pragma unroll 1
            for (int it = 0; it < POLL_MAX; it++) {
                if ((v[0].w ^ tag) & 3) v[0] = ld_ll(ys);
                if ((v[1].w ^ tag) & 3) v[1] = ld_ll(ys + 56 * 512);
                if (__all_sync(0xffffffffu, !(tag_bad(v[0].w ^ tag, v[1].w, tag) & 3))) break;
            }
            float y0 = u2f(v[0].x) + u2f(v[1].x), y1 = u2f(v[0].y) + u2f(v[1].y), y2 = u2f(v[0].z) + u2f(v[1].z), y3 = u2f(v[0].w) + u2f(v[1].w);
            const bool g0 = g & 1, g1 = g & 2;
            const float k0 = (g0 ? y1 : y0) + shfl_x(g0 ? y0 : y1, 4), k1 = (g0 ? y3 : y2) + shfl_x(g0 ? y2 : y3, 4);
            const float y = (g1 ? k1 : k0) + shfl_x(g1 ? k0 : k1, 8);
            stsf(sb + OFF_RED2 + (lane & 15) * 64u + (lane >> 4) * 32u + warp * 4u, y);
            bar_sync(6, 224);
            if (tid < 16) {
                const uint32_t a = sb + OFF_RED2 + lane * 64u;
                const uint4 ya = lds128(a), yb = lds128(a + 16), yc = lds128(a + 32), ye = lds128(a + 48);
                const float s = (((u2f(ya.x) + u2f(ya.y)) + (u2f(ya.z) + u2f(ya.w))) + ((u2f(yb.x) + u2f(yb.y)) + u2f(yb.z)))
                              + (((u2f(yc.x) + u2f(yc.y)) + (u2f(yc.z) + u2f(yc.w))) + ((u2f(ye.x) + u2f(ye.y)) + u2f(ye.z)));
                const uint32_t o = hadd2(fx, hmul2(fg, hadd2(fh, hmul2(pack2(s, s), fs2))));
                *od = (c & 1) ? o >> 16 : o;
                if (b == 0 && tid == 0) p.s->done[0] = tag;
                TS(40);
            }
        }
    }
}

typedef CUresult (*EncodeFn)(CUtensorMap*, CUtensorMapDataType, cuuint32_t, void*, const cuuint64_t*, const cuuint64_t*, const cuuint32_t*,
                             const cuuint32_t*, CUtensorMapInterleave, CUtensorMapSwizzle, CUtensorMapL2promotion, CUtensorMapFloatOOBfill);

CUtensorMap make_map(EncodeFn enc, const void* ptr, uint64_t cols, uint64_t rows, uint32_t bc, uint32_t br, CUtensorMapSwizzle swz, CUtensorMapL2promotion promo) {
    CUtensorMap m;
    cuuint64_t dims[2] = {cols, rows}, strides[1] = {cols * 2};
    cuuint32_t box[2] = {bc, br}, es[2] = {1, 1};
    enc(&m, CU_TENSOR_MAP_DATA_TYPE_BFLOAT16, 2, const_cast<void*>(ptr), dims, strides, box, es, CU_TENSOR_MAP_INTERLEAVE_NONE, swz, promo,
        CU_TENSOR_MAP_FLOAT_OOB_FILL_NONE);
    return m;
}
CUtensorMap make_map4(EncodeFn enc, const void* ptr, uint32_t groups, uint64_t rows, uint32_t br, CUtensorMapL2promotion promo) {
    CUtensorMap m;
    cuuint64_t dims[4] = {64, rows, 16, groups}, strides[3] = {groups * 2048ull, 128, 2048};
    cuuint32_t box[4] = {64, br, 2, groups}, es[4] = {1, 1, 1, 1};
    enc(&m, CU_TENSOR_MAP_DATA_TYPE_BFLOAT16, 4, const_cast<void*>(ptr), dims, strides, box, es, CU_TENSOR_MAP_INTERLEAVE_NONE, CU_TENSOR_MAP_SWIZZLE_128B, promo,
        CU_TENSOR_MAP_FLOAT_OOB_FILL_NONE);
    return m;
}

}

extern "C" void kernel_launch(void* const* d_in, const int* in_sizes, int n_in, void* d_out, int out_size) {
    (void)in_sizes; (void)n_in; (void)out_size;
    void* fn = nullptr; cudaDriverEntryPointQueryResult qr;
    cudaGetDriverEntryPoint("cuTensorMapEncodeTiled", &fn, cudaEnableDefault, &qr);
    EncodeFn enc = (EncodeFn)fn;
    void* hs = nullptr;
    cudaGetSymbolAddress(&hs, g_scratch);
    int dev = 0, sms = 0;
    cudaGetDevice(&dev);
    cudaDeviceGetAttribute(&sms, cudaDevAttrMultiProcessorCount, dev);
    const CUtensorMapL2promotion P256 = CU_TENSOR_MAP_L2_PROMOTION_L2_256B, P128 = CU_TENSOR_MAP_L2_PROMOTION_L2_128B, P0 = CU_TENSOR_MAP_L2_PROMOTION_NONE;
    CUtensorMap tmW = make_map4(enc, d_in[1], 3, 1024, 32, P256);
    CUtensorMap tmWo = make_map4(enc, d_in[3], 1, 1024, 64, P256);
    CUtensorMap tmO = make_map4(enc, d_out, 1, 2048, 16, P0);
    CUtensorMap tmPhi = make_map(enc, d_in[2], 32, 1024, 32, 128, CU_TENSOR_MAP_SWIZZLE_64B, P128);
    CUtensorMap tmG = make_map(enc, d_in[6], 3584, 1024, 32, 128, CU_TENSOR_MAP_SWIZZLE_64B, P0);
    CUtensorMap tmU = make_map(enc, d_in[7], 3584, 1024, 32, 128, CU_TENSOR_MAP_SWIZZLE_64B, P0);
    CUtensorMap tmD = make_map(enc, d_in[8], 1024, 3584, 64, 32, CU_TENSOR_MAP_SWIZZLE_128B, P128);
    CUtensorMap tmX = make_map(enc, d_in[0], 1024, 2048, 64, 128, CU_TENSOR_MAP_SWIZZLE_128B, P128);
    CUtensorMap tmM = make_map(enc, d_in[10], 6144, 1024, 64, 256, CU_TENSOR_MAP_SWIZZLE_128B, MPROMO);
    Ptrs p;
    p.x = (const bf16*)d_in[0]; p.c = (const bf16*)d_in[9]; p.wmod = (const bf16*)d_in[10]; p.wr = (const bf16*)d_in[5];
    p.wg = (const bf16*)d_in[6]; p.wu = (const bf16*)d_in[7]; p.wd = (const bf16*)d_in[8]; p.out = (bf16*)d_out; p.s = (Scratch*)hs;
    p.wqkv = (const bf16*)d_in[1]; p.wo = (const bf16*)d_in[3];
    p.by_sm = sms == 132;
    const int pos[8] = {0, 5, 2, 3, 1, 4, 6, 7}, extra[12] = {128, 129, 130, 131, 2, 10, 3, 11, 26, 27, 18, 19};
    for (int g = 0, f = 0; g < 8; g++)
        for (int sm = 0; sm < 132; sm++) {
            const int tp = sm >> 1, u = tp - 32, sl = 2 * (tp < 32 ? tp >> 3 : 4 + u / 7) + (sm & 1);
            if ((tp < 32 ? tp & 7 : tp < 60 ? 1 + u % 7 : 0) != g) continue;
            const int b = tp >= 60 ? extra[sm - 120] : ((pos[g] >> 1) * 4 + (sl & 3)) * 8 + (pos[g] & 1) * 4 + (sl >> 2);
            const bool ffn = tp < 60 ? sl < (g < 4 ? 16 : 13) : tp == 62 || tp == 65;
            p.role[sm] = (uint16_t)(b | (ffn ? f++ : 255) << 8);
        }
    cudaFuncSetAttribute(fused_kernel, cudaFuncAttributeMaxDynamicSharedMemorySize, SMEM_BYTES);
    fused_kernel<<<132, NTHREADS, SMEM_BYTES, cudaStreamPerThread>>>(p, tmM, tmX, tmW, tmWo, tmPhi, tmG, tmU, tmD, tmO);
}
```
